```python
import torch

def _softmax(x, axis=-1):
    return torch.softmax(x, dim=axis)
def _gelu(x):
    return torch.nn.functional.gelu(x, approximate="tanh")
def _silu(x):
    return torch.nn.functional.silu(x)
def _sigmoid(x):
    return torch.sigmoid(x)
def _layernorm(x, axis=-1, eps=1e-5):
    m = x.mean(dim=axis, keepdim=True)
    v = x.var(dim=axis, keepdim=True, unbiased=False)
    return (x - m) / torch.sqrt(v + eps)
def _scatter_add(tgt, idx, src, axis=0):
    return tgt.clone().index_add_(axis, idx, src)
def _segment_sum(src, seg, n):
    out = torch.zeros((n,) + src.shape[1:], dtype=src.dtype)
    return out.index_add_(0, seg, src)
def _pad(x, pw):
    flat = tuple(v for pair in reversed(pw) for v in pair)
    return torch.nn.functional.pad(x, flat)

kernel_name = 'standalone__hybrid_graph_tf_exphormer__graph'

def setup_inputs():

    _w = (lambda a: (lambda t: t.to(torch.bfloat16) if t.is_floating_point() else t)(torch.as_tensor(a)))
    N, deg, D = 10000, 16, 256
    E = N * deg
    exp_deg = 4
    Ee = N * exp_deg
    src = (lambda lo, hi, *s: torch.randint(lo, hi, s))(0, N, E).to(torch.int64)
    dst = (lambda lo, hi, *s: torch.randint(lo, hi, s))(0, N, E).to(torch.int64)
    esrc = (lambda lo, hi, *s: torch.randint(lo, hi, s))(0, N, Ee).to(torch.int64)
    edst = torch.repeat_interleave(torch.arange(N), exp_deg).to(torch.int64)
    deg_cnt = torch.bincount(dst, minlength=N).to(float) + 1.0
    return {
        "x": _w((lambda *s: torch.randn(*s, dtype=torch.bfloat16) * 0.05)(N, D)),
        "src": _w(src),
        "dst": _w(dst),
        "esrc": _w(esrc),
        "edst": _w(edst),
        "deg_inv_sqrt": _w(1.0 / (lambda _x: torch.sqrt(torch.as_tensor(_x)))(deg_cnt)),
        "w_l": _w((lambda *s: torch.randn(*s, dtype=torch.bfloat16) * 0.05)(D, D)),
        "wq": _w((lambda *s: torch.randn(*s, dtype=torch.bfloat16) * 0.05)(D, D)),
        "wk": _w((lambda *s: torch.randn(*s, dtype=torch.bfloat16) * 0.05)(D, D)),
        "wv": _w((lambda *s: torch.randn(*s, dtype=torch.bfloat16) * 0.05)(D, D)),
    }

def reference(x, src, dst, esrc, edst, deg_inv_sqrt, w_l, wq, wk, wv):
    N, D = x.shape
    h = x @ w_l
    msg = h[src] * deg_inv_sqrt[src, None] * deg_inv_sqrt[dst, None]
    h_local = _segment_sum(msg, dst, N)
    q = x @ wq
    k = x @ wk
    v = x @ wv
    e = (q[edst] * k[esrc]).sum(-1) * (D ** -0.5)
    exp_e = torch.exp(e)
    denom = _segment_sum(exp_e[:, None], edst, N)[:, 0] + 1e-9
    alpha = exp_e / denom[edst]
    h_attn = _segment_sum(alpha[:, None] * v[esrc], edst, N)
    return h_local + h_attn
```

```cpp
#include <cuda_runtime.h>
#include <cuda_bf16.h>
#include <cuda.h>
#include <stdint.h>

namespace {

constexpr int NN = 10000, NE = 160000, NEE = 40000;
constexpr int TILE = 80, NT = 125, NCTA = 128, NG = 625, EPC = 1280;
constexpr int CELL = 32;
constexpr int LCAP = 80;
constexpr int OVCAP = EPC + NT * CELL;
constexpr unsigned DUMMY2 = 1250u | (1250u << 16);

constexpr int OFF_T = 0;
constexpr int OFF_S = 40960;
constexpr int OFF_R = 204800;
constexpr int OFF_MAIL = OFF_R;
constexpr int OFF_CNT1 = OFF_MAIL + 16000;
constexpr int OFF_CNT2 = OFF_CNT1 + 512;
constexpr int OFF_START = OFF_CNT2 + 2560;
constexpr int OFF_MRED = OFF_START + 640;
constexpr int OFF_DIS = OFF_MRED + 6144;
constexpr int OFF_BAR = OFF_DIS + 320;
constexpr int OFF_MISC = OFF_BAR + 128;
constexpr int SMEM_BYTES = OFF_MISC + 64;
static_assert(SMEM_BYTES <= 232448, "smem");
static_assert(OFF_BAR % 8 == 0 && OFF_MRED % 16 == 0 && OFF_CNT2 % 16 == 0, "align");

__device__ uint4 g_wf[3 * 8192];
__device__ uint4 g_hs[32 * NN];
__device__ uint4 g_mail[NT * 1024];
__device__ uint4 g_lists[(NG + 16) * 96];
__device__ unsigned char g_codes[640];
__device__ unsigned g_ovf[NCTA * OVCAP];
__device__ unsigned g_ovfn[NCTA];
__device__ unsigned g_stat[NCTA];
__device__ unsigned g_bar[4 * 64];
#define STAMP(i)

__device__ __forceinline__ void bar_arrive(int i) {
    asm volatile("red.release.gpu.global.add.u32 [%0],1;" ::"l"(&g_bar[i * 64]) : "memory");
}
__device__ __forceinline__ void bar_poll(int i, unsigned target) {
    unsigned v;
    int lim = 0;
    do {
        asm volatile("ld.acquire.gpu.global.u32 %0,[%1];" : "=r"(v) : "l"(&g_bar[i * 64]) : "memory");
        if (++lim > (1 << 22)) __trap();
    } while ((int)(v - target) < 0);
}
__device__ __forceinline__ void mbar_wait(unsigned a, unsigned par) {
    unsigned ok;
    int lim = 0;
    do {
        asm volatile("{.reg .pred p; mbarrier.try_wait.parity.shared.b64 p,[%1],%2; selp.u32 %0,1,0,p;}" : "=r"(ok) : "r"(a), "r"(par) : "memory");
        if (++lim > (1 << 22)) __trap();
    } while (!ok);
}
__device__ __forceinline__ uint4 ldg_na(const uint4* p) {
    uint4 v;
    asm volatile("ld.global.L1::no_allocate.v4.u32 {%0,%1,%2,%3},[%4];" : "=r"(v.x), "=r"(v.y), "=r"(v.z), "=r"(v.w) : "l"(p) : "memory");
    return v;
}
__device__ __forceinline__ uint4 lds128(unsigned a) {
    uint4 v;
    asm volatile("ld.shared.v4.u32 {%0,%1,%2,%3},[%4];" : "=r"(v.x), "=r"(v.y), "=r"(v.z), "=r"(v.w) : "r"(a) : "memory");
    return v;
}
__device__ __forceinline__ void sts128(unsigned a, uint4 v) {
    asm volatile("st.shared.v4.u32 [%0],{%1,%2,%3,%4};" ::"r"(a), "r"(v.x), "r"(v.y), "r"(v.z), "r"(v.w) : "memory");
}
__device__ __forceinline__ void sts32(unsigned a, unsigned v) { asm volatile("st.shared.u32 [%0],%1;" ::"r"(a), "r"(v) : "memory"); }
__device__ __forceinline__ unsigned lds32(unsigned a) { unsigned v; asm volatile("ld.shared.u32 %0,[%1];" : "=r"(v) : "r"(a) : "memory"); return v; }
__device__ __forceinline__ unsigned atoms_inc(unsigned a) { unsigned v; asm volatile("atom.shared.add.u32 %0,[%1],1;" : "=r"(v) : "r"(a) : "memory"); return v; }
__device__ __forceinline__ float blo(unsigned v) { return __uint_as_float(v << 16); }
__device__ __forceinline__ float bhi(unsigned v) { return __uint_as_float(v & 0xFFFF0000u); }
__device__ __forceinline__ float blo_v(unsigned v) { float r; asm volatile("shl.b32 %0,%1,16;" : "=f"(r) : "r"(v)); return r; }
__device__ __forceinline__ float bhi_v(unsigned v) { float r; asm volatile("and.b32 %0,%1,0xFFFF0000;" : "=f"(r) : "r"(v)); return r; }
__device__ __forceinline__ unsigned pack2(float lo, float hi) { unsigned r; asm("cvt.rn.bf16x2.f32 %0,%1,%2;" : "=r"(r) : "f"(hi), "f"(lo)); return r; }
__device__ __forceinline__ int slot_of(int s) { return (s & ~7) | ((s & 1) << 2) | ((s >> 1) & 3); }

__device__ __forceinline__ void mma16816(float* d, unsigned a0, unsigned a1, unsigned a2, unsigned a3, unsigned b0, unsigned b1) {
    asm volatile("mma.sync.aligned.m16n8k16.row.col.f32.bf16.bf16.f32 {%0,%1,%2,%3},{%4,%5,%6,%7},{%8,%9},{%0,%1,%2,%3};"
                 : "+f"(d[0]), "+f"(d[1]), "+f"(d[2]), "+f"(d[3]) : "r"(a0), "r"(a1), "r"(a2), "r"(a3), "r"(b0), "r"(b1));
}
#define R10(b) "+f"(d[b + 0]), "+f"(d[b + 1]), "+f"(d[b + 2]), "+f"(d[b + 3]), "+f"(d[b + 4]), "+f"(d[b + 5]), "+f"(d[b + 6]), "+f"(d[b + 7]), "+f"(d[b + 8]), "+f"(d[b + 9])
__device__ __forceinline__ void wg80(float* d, const uint4& a, unsigned long long desc, int sc) {
    asm volatile("{.reg .pred p; setp.ne.b32 p,%45,0;\n"
                 "wgmma.mma_async.sync.aligned.m64n80k16.f32.bf16.bf16 "
                 "{%0,%1,%2,%3,%4,%5,%6,%7,%8,%9,%10,%11,%12,%13,%14,%15,%16,%17,%18,%19,%20,%21,%22,%23,%24,%25,%26,%27,%28,%29,%30,%31,%32,%33,%34,%35,%36,%37,%38,%39},"
                 "{%40,%41,%42,%43},%44,p,1,1,0;}"
                 : R10(0), R10(10), R10(20), R10(30) : "r"(a.x), "r"(a.y), "r"(a.z), "r"(a.w), "l"(desc), "r"(sc));
}
__device__ __forceinline__ void wg_fence() { asm volatile("wgmma.fence.sync.aligned;" ::: "memory"); }
__device__ __forceinline__ void wg_commit() { asm volatile("wgmma.commit_group.sync.aligned;" ::: "memory"); }
template <int N> __device__ __forceinline__ void wg_wait() { asm volatile("wgmma.wait_group.sync.aligned %0;" ::"n"(N) : "memory"); }
__device__ __forceinline__ void wg_quarter(float* d, const uint4* f, unsigned long long desc0, int q) {
    wg_fence();
#pragma unroll
    for (int s = 0; s < 4; s++) wg80(d, f[s], desc0 + q * 640 + s * 2, (q | s) != 0);
    wg_commit();
}
__device__ __forceinline__ void load_quarter(uint4* f, const uint4* p) {
#pragma unroll
    for (int s = 0; s < 4; s++) f[s] = ldg_na(p + s * 32);
}

__device__ __forceinline__ unsigned hsat(unsigned a, unsigned c) { unsigned r; asm("add.sat.f16x2 %0,%1,%2;" : "=r"(r) : "r"(a), "r"(c)); return r; }
__device__ __forceinline__ unsigned hset(unsigned a, unsigned c) { unsigned r; asm("set.le.f16x2.f16x2 %0,%1,%2;" : "=r"(r) : "r"(a), "r"(c)); return r; }
__host__ __device__ constexpr unsigned h2c(int v) { return (0x6400u | v) | ((0x6400u | v) << 16); }
__device__ __forceinline__ unsigned dp2lo(unsigned a, unsigned c) { unsigned r; asm("dp2a.lo.u32.u32 %0,%1,%2,%3;" : "=r"(r) : "r"(a), "r"(0x80000080u), "r"(c)); return r; }
__device__ __forceinline__ unsigned dp2hi(unsigned a, unsigned c) { unsigned r; asm("dp2a.hi.u32.u32 %0,%1,%2,%3;" : "=r"(r) : "r"(a), "r"(0x80000080u), "r"(c)); return r; }
__device__ __forceinline__ void p3_step(float* acc0, float* acc1, unsigned addr, int s, unsigned sA, unsigned nB) {
    unsigned b0, b1, b2, b3;
    asm volatile("ldmatrix.sync.aligned.m8n8.x4.trans.shared.b16 {%0,%1,%2,%3},[%4];" : "=r"(b0), "=r"(b1), "=r"(b2), "=r"(b3) : "r"(addr));
    mma16816(acc0, hset(sA, h2c(4 * s + 0)), hsat(nB, h2c(4 * s + 1)), hset(sA, h2c(4 * s + 1)), hsat(nB, h2c(4 * s + 2)), b0, b1);
    mma16816(acc1, hset(sA, h2c(4 * s + 2)), hsat(nB, h2c(4 * s + 3)), hset(sA, h2c(4 * s + 3)), hsat(nB, h2c(4 * s + 4)), b2, b3);
}
template <int NS> __device__ __forceinline__ void p3_steps(float* acc0, float* acc1, const unsigned* ad, unsigned sA, unsigned nB) {
#pragma unroll
    for (int s = 0; s < NS; s++) p3_step(acc0, acc1, ad[s], s, sA, nB);
}
__device__ __noinline__ float4 p3_overflow(int grp, unsigned sS) {
    int lane = threadIdx.x & 31, g = lane >> 2, t = lane & 3;
    float4 r = make_float4(0.f, 0.f, 0.f, 0.f);
    for (int c = 0; c < NT; c++) {
        int n = (int)__ldcg(&g_ovfn[c]);
        for (int i0 = 0; i0 < n; i0 += 32) {
            unsigned e = (i0 + lane < n) ? __ldcg(&g_ovf[c * OVCAP + i0 + lane]) : 0xFFFFFFFFu;
            unsigned m = __ballot_sync(~0u, (int)(e >> 18) == grp);
            while (m) {
                int j = __ffs(m) - 1;
                m &= m - 1;
                unsigned ee = __shfl_sync(~0u, e, j);
                int row = (ee >> 14) & 15;
                unsigned v = lds32(sS + (ee & 0x3FFF) * 16 + t * 4);
                if ((row & 7) == g) {
                    if (row < 8) { r.x += blo(v); r.y += bhi(v); } else { r.z += blo(v); r.w += bhi(v); }
                }
            }
        }
    }
    const float k = 1.f / 128.f;
    r.x *= k; r.y *= k; r.z *= k; r.w *= k;
    return r;
}
__device__ __noinline__ uint4 attn_generic(int node, uint4 yv, const uint4* __restrict__ x, const int* __restrict__ esrc, const int* __restrict__ edst) {
    int lane = threadIdx.x & 31;
    float y[8] = {blo(yv.x), bhi(yv.x), blo(yv.y), bhi(yv.y), blo(yv.z), bhi(yv.z), blo(yv.w), bhi(yv.w)};
    float o[8] = {0, 0, 0, 0, 0, 0, 0, 0};
    float den = 0.f;
    for (int i0 = 0; i0 < NEE; i0 += 32) {
        unsigned m = __ballot_sync(~0u, edst[i0 + lane] == node);
        while (m) {
            int j = __ffs(m) - 1;
            m &= m - 1;
            uint4 gv = x[(size_t)esrc[i0 + j] * 32 + lane];
            float gq[8] = {blo(gv.x), bhi(gv.x), blo(gv.y), bhi(gv.y), blo(gv.z), bhi(gv.z), blo(gv.w), bhi(gv.w)};
            float p = 0.f;
            for (int k = 0; k < 8; k++) p = fmaf(y[k], gq[k], p);
            for (int k = 16; k; k >>= 1) p += __shfl_xor_sync(~0u, p, k);
            float ex = exp2f(p);
            den += ex;
            for (int k = 0; k < 8; k++) o[k] = fmaf(ex, gq[k], o[k]);
        }
    }
    float inv = 1.f / (den + 1e-9f);
    return make_uint4(pack2(o[0] * inv, o[1] * inv), pack2(o[2] * inv, o[3] * inv), pack2(o[4] * inv, o[5] * inv), pack2(o[6] * inv, o[7] * inv));
}

__global__ void __launch_bounds__(512, 1)
exphormer_kernel(const uint4* __restrict__ x, const int4* __restrict__ src4, const int4* __restrict__ dst4,
                 const int* __restrict__ esrc, const int* __restrict__ edst, const unsigned short* __restrict__ dis,
                 const unsigned* __restrict__ w_l, const uint4* __restrict__ wq, const uint4* __restrict__ wk,
                 const unsigned* __restrict__ wv, unsigned* __restrict__ out,
                 const __grid_constant__ CUtensorMap tm_x, const __grid_constant__ CUtensorMap tm_o256,
                 const __grid_constant__ CUtensorMap tm_o16) {
    extern __shared__ __align__(1024) unsigned char smem_raw[];
    const unsigned sb = (unsigned)__cvta_generic_to_shared(smem_raw);
    const int tid = threadIdx.x, w = tid >> 5, lane = tid & 31, g = lane >> 2, t = lane & 3;
    const int b = blockIdx.x;
    const bool rowcta = b < NT;
    const unsigned bar_x = sb + OFF_BAR, bar_fill = sb + OFF_BAR + 8, bar_rd = sb + OFF_BAR + 16;
    STAMP(0);

    unsigned target = 0;
    if (tid == 0) {
        asm volatile("mbarrier.init.shared.b64 [%0],1;" ::"r"(bar_x));
        asm volatile("mbarrier.init.shared.b64 [%0],1;" ::"r"(bar_fill));
        for (int i = 0; i < 10; i++) asm volatile("mbarrier.init.shared.b64 [%0],16;" ::"r"(bar_rd + 8 * i));
        asm volatile("fence.proxy.async.shared::cta;" ::: "memory");
    }
    if (lane == 0) {
        unsigned v;
        asm volatile("ld.relaxed.gpu.global.u32 %0,[%1];" : "=r"(v) : "l"(&g_bar[3 * 64]) : "memory");
        target = (v & ~(unsigned)(NCTA - 1)) + NCTA;
    }
    unsigned r4[4];
    uint4 mk[4], mq[4];
    const int fw = b >> 3;
    if (w < 4) {
        const unsigned* W = (w < 2) ? w_l : wv;
        int s = 2 * (b & 7) + (w & 1);
        const unsigned* p = W + (16 * s + 2 * t) * 128 + 8 * fw + g;
        r4[0] = __ldg(p); r4[1] = __ldg(p + 128); r4[2] = __ldg(p + 8 * 128); r4[3] = __ldg(p + 9 * 128);
    } else if (w < 12) {
        int s = 2 * (b & 7) + ((w - 4) >> 2), q = w & 3;
        const uint4* pk = wk + (16 * fw + 2 * g) * 32 + 8 * q + 2 * t;
        const uint4* pq = wq + (16 * s + g) * 32 + 8 * q + 2 * t;
        mk[0] = __ldg(pk); mk[1] = __ldg(pk + 1); mk[2] = __ldg(pk + 32); mk[3] = __ldg(pk + 33);
        mq[0] = __ldg(pq); mq[1] = __ldg(pq + 1); mq[2] = __ldg(pq + 256); mq[3] = __ldg(pq + 257);
    }
    int4 es = make_int4(0, 0, 0, 0), ed = make_int4(0, 0, 0, 0);
    int xs = 0, xd = 0;
    unsigned short disv = 0;
    if (rowcta) {
        if (tid >= 192) { ed = __ldg(dst4 + b * 320 + tid - 192); es = __ldg(src4 + b * 320 + tid - 192); }
        if (lane < 20) { xs = __ldg(esrc + b * 320 + w * 20 + lane); xd = __ldg(edst + b * 320 + w * 20 + lane); }
        if (tid < TILE) disv = __ldg(dis + b * TILE + tid);
        if (tid == 0) {
            asm volatile("mbarrier.arrive.expect_tx.shared.b64 _,[%0],%1;" ::"r"(bar_x), "r"(40960) : "memory");
#pragma unroll
            for (int kb = 0; kb < 4; kb++)
                asm volatile("cp.async.bulk.tensor.2d.shared::cluster.global.mbarrier::complete_tx::bytes [%0],[%1,{%3,%4}],[%2];"
                             ::"r"(sb + OFF_T + kb * 10240), "l"(&tm_x), "r"(bar_x), "r"(kb * 64), "r"(b * TILE) : "memory");
        }
    }
    {
        const uint4 ones = make_uint4(~0u, ~0u, ~0u, ~0u), zero = make_uint4(0, 0, 0, 0);
        sts128(sb + OFF_MAIL + tid * 16, ones);
        if (tid < 1000 - 512) sts128(sb + OFF_MAIL + (tid + 512) * 16, ones);
        if (tid < (512 + 2560) / 16) sts128(sb + OFF_CNT1 + tid * 16, zero);
        if (tid == 511) sts128(sb + OFF_MISC, zero);
    }
    __syncthreads();
    STAMP(1);

    auto issue_gather = [&]() {
        if (rowcta) {
            unsigned dsta = sb + OFF_S + w * (20 * 512) + lane * 16;
#pragma unroll
            for (int j = 0; j < 20; j++) {
                int r = __shfl_sync(~0u, xs, j);
                asm volatile("cp.async.cg.shared.global [%0],[%1],16;" ::"r"(dsta + j * 512), "l"(x + (size_t)r * 32 + lane) : "memory");
            }
            asm volatile("cp.async.commit_group;" ::: "memory");
        }
    };

    if (w < 4) {
        int s = 2 * (b & 7) + (w & 1);
        uint4 f = make_uint4(__byte_perm(r4[0], r4[1], 0x5410), __byte_perm(r4[0], r4[1], 0x7632),
                             __byte_perm(r4[2], r4[3], 0x5410), __byte_perm(r4[2], r4[3], 0x7632));
        g_wf[(w < 2 ? 0 : 2) * 8192 + (fw * 16 + s) * 32 + lane] = f;
        asm volatile("bar.sync 1,128;" ::: "memory");
        if (tid == 0) bar_arrive(0);
        __syncwarp();
    }
    if (w != 1) issue_gather();
    if (w >= 4 && w < 12) {
        float c0[4] = {0, 0, 0, 0}, c1[4] = {0, 0, 0, 0};
        mma16816(c0, mk[0].x, mk[2].x, mk[0].y, mk[2].y, mq[0].x, mq[0].y);
        mma16816(c1, mk[0].x, mk[2].x, mk[0].y, mk[2].y, mq[2].x, mq[2].y);
        mma16816(c0, mk[0].z, mk[2].z, mk[0].w, mk[2].w, mq[0].z, mq[0].w);
        mma16816(c1, mk[0].z, mk[2].z, mk[0].w, mk[2].w, mq[2].z, mq[2].w);
        mma16816(c0, mk[1].x, mk[3].x, mk[1].y, mk[3].y, mq[1].x, mq[1].y);
        mma16816(c1, mk[1].x, mk[3].x, mk[1].y, mk[3].y, mq[3].x, mq[3].y);
        mma16816(c0, mk[1].z, mk[3].z, mk[1].w, mk[3].w, mq[1].z, mq[1].w);
        mma16816(c1, mk[1].z, mk[3].z, mk[1].w, mk[3].w, mq[3].z, mq[3].w);
        int blk = (w - 4) >> 2, q = w & 3;
        unsigned ra = sb + OFF_MRED + blk * 3072 + lane * 16;
        if (q) {
            sts128(ra + (q - 1) * 1024, make_uint4(__float_as_uint(c0[0]), __float_as_uint(c0[1]), __float_as_uint(c0[2]), __float_as_uint(c0[3])));
            sts128(ra + (q - 1) * 1024 + 512, make_uint4(__float_as_uint(c1[0]), __float_as_uint(c1[1]), __float_as_uint(c1[2]), __float_as_uint(c1[3])));
        }
        if (blk == 0) asm volatile("bar.sync 2,128;" ::: "memory"); else asm volatile("bar.sync 3,128;" ::: "memory");
        if (q == 0) {
#pragma unroll
            for (int i = 0; i < 3; i++) {
                uint4 u = lds128(ra + i * 1024), v = lds128(ra + i * 1024 + 512);
                c0[0] += __uint_as_float(u.x); c0[1] += __uint_as_float(u.y); c0[2] += __uint_as_float(u.z); c0[3] += __uint_as_float(u.w);
                c1[0] += __uint_as_float(v.x); c1[1] += __uint_as_float(v.y); c1[2] += __uint_as_float(v.z); c1[3] += __uint_as_float(v.w);
            }
            const float k = 0.0625f * 1.4426950408889634f;
            g_wf[8192 + (fw * 16 + 2 * (b & 7) + blk) * 32 + lane] =
                make_uint4(pack2(c0[0] * k, c0[1] * k), pack2(c0[2] * k, c0[3] * k), pack2(c1[0] * k, c1[1] * k), pack2(c1[2] * k, c1[3] * k));
        }
    }
    if (rowcta && tid >= 192) {
        int dd[4] = {ed.x, ed.y, ed.z, ed.w}, ss[4] = {es.x, es.y, es.z, es.w};
#pragma unroll
        for (int i = 0; i < 4; i++) {
            unsigned o = (unsigned)dd[i] / TILE;
            unsigned sl = slot_of(ss[i]);
            unsigned r = atoms_inc(sb + OFF_CNT1 + o * 4);
            if (r < CELL) sts32(sb + OFF_MAIL + (o * CELL + r) * 4, ((dd[i] - o * TILE) << 14) | sl);
            else g_ovf[b * OVCAP + atoms_inc(sb + OFF_MISC)] = ((unsigned)dd[i] << 14) | sl;
        }
    }
    if (tid < TILE) sts32(sb + OFF_DIS + tid * 4, (unsigned)disv << 16);
    int bad = __syncthreads_or(rowcta && lane < 20 && xd != b * TILE + w * 5 + (lane >> 2));
    if (rowcta) {
        g_mail[(tid >> 3) * 1024 + b * 8 + (tid & 7)] = lds128(sb + OFF_MAIL + tid * 16);
        if (tid < 1000 - 512) g_mail[((tid + 512) >> 3) * 1024 + b * 8 + (tid & 7)] = lds128(sb + OFF_MAIL + (tid + 512) * 16);
    }
    if (tid == 32) g_stat[b] = bad;
    if (tid == 0) bar_poll(0, target);
    __syncthreads();
    STAMP(2);
    if (w == 1) {
        if (lane == 0) bar_arrive(1);
        __syncwarp();
        issue_gather();
    }

    const unsigned long long desc0 = (1ull << 62) | (64ull << 32) | (1ull << 16) | (unsigned long long)(((sb + OFF_T) & 0x3FFFF) >> 4);
    int generic_attn = 0;
    if (rowcta) {
        float d[40];
        uint4 F0[4], F1[4], F2[4];
        const uint4* wf = g_wf + w * 512 + lane;
        load_quarter(F0, wf); load_quarter(F1, wf + 128); load_quarter(F2, wf + 256);
        if (tid < 480) sts128(sb + OFF_MAIL + tid * 16, make_uint4(DUMMY2, DUMMY2, DUMMY2, DUMMY2));
        mbar_wait(bar_x, 0);
        STAMP(3);
        wg_quarter(d, F0, desc0, 0); wg_quarter(d, F1, desc0, 1); wg_quarter(d, F2, desc0, 2);
        if (tid == 0) bar_poll(1, target);
        wg_wait<2>();
        load_quarter(F0, wf + 384);
        __syncthreads();
        STAMP(4);
        uint4 m0 = ldg_na(g_mail + b * 1024 + tid), m1 = make_uint4(~0u, ~0u, ~0u, ~0u);
        if (tid < 1000 - 512) m1 = ldg_na(g_mail + b * 1024 + 512 + tid);
        unsigned stat = (tid < NCTA) ? __ldcg(&g_stat[tid]) : 0;
        wg_wait<1>();
        load_quarter(F1, wf + 8192);
        wg_quarter(d, F0, desc0, 3);
        unsigned en[8] = {m0.x, m0.y, m0.z, m0.w, m1.x, m1.y, m1.z, m1.w};
#pragma unroll
        for (int i = 0; i < 8; i++) {
            if (en[i] != ~0u) {
                unsigned dl = en[i] >> 14;
                unsigned key = ((dl >> 4) << 7) | ((en[i] & 7) << 4) | ((dl & 7) << 1) | ((dl >> 3) & 1);
                unsigned r = atoms_inc(sb + OFF_CNT2 + key * 4);
                en[i] |= min(r, 127u) << 21;
            }
        }
        wg_wait<1>();
        load_quarter(F2, wf + 8192 + 128);
        __syncthreads();
        if (w < 5) {
            uint4 c = lds128(sb + OFF_CNT2 + (w * 128 + lane * 4) * 4);
            unsigned s1 = c.x, s2 = s1 + c.y, s3 = s2 + c.z, tot = s3 + c.w, inc = tot;
            unsigned u = __shfl_up_sync(~0u, inc, 1, 4); if (t >= 1) inc += u;
            u = __shfl_up_sync(~0u, inc, 2, 4); if (t >= 2) inc += u;
            unsigned base = inc - tot;
            unsigned word = min(base, (unsigned)LCAP) | (min(base + s1, (unsigned)LCAP) << 8) | (min(base + s2, (unsigned)LCAP) << 16) | (min(base + s3, (unsigned)LCAP) << 24);
            sts32(sb + OFF_START + (w * 32 + lane) * 4, word);
            unsigned mx = min(__reduce_max_sync(~0u, inc), (unsigned)LCAP);
            unsigned ns = (mx + 3) >> 2;
            if (lane == 0) g_codes[b * 5 + w] = ns <= 9 ? 0 : ns <= 12 ? ns - 9 : 4;
            unsigned wa = __shfl_sync(~0u, word, 8 * t + (g >> 1)), wb = __shfl_sync(~0u, word, 8 * t + 4 + (g >> 1));
            unsigned hdr = __byte_perm(wa, wb, (g & 1) ? 0x7362 : 0x5140);
            float da = __uint_as_float(lds32(sb + OFF_DIS + (w * 16 + g) * 4)) * 128.f, db = __uint_as_float(lds32(sb + OFF_DIS + (w * 16 + g + 8) * 4)) * 128.f;
            asm volatile("st.shared.v2.u32 [%0],{%1,%2};" ::"r"(sb + OFF_MAIL + w * 1536 + lane * 16), "r"(hdr), "r"(pack2(da, db)) : "memory");
        }
        wg_wait<0>();
        load_quarter(F0, wf + 8192 + 256);
        STAMP(5);
        {
            unsigned* hp = (unsigned*)(g_hs + (2 * w + (g >> 2)) * NN + b * TILE + t) + (g & 3);
#pragma unroll
            for (int j = 0; j < 10; j++) {
                float s0, s1;
                asm volatile("ld.shared.v2.f32 {%0,%1},[%2];" : "=f"(s0), "=f"(s1) : "r"(sb + OFF_DIS + (8 * j + 2 * t) * 4));
                hp[(8 * j) * 4] = pack2(d[4 * j] * s0, d[4 * j + 2] * s0);
                hp[(8 * j + 4) * 4] = pack2(d[4 * j + 1] * s1, d[4 * j + 3] * s1);
            }
        }
        wg_quarter(d, F1, desc0, 0); wg_quarter(d, F2, desc0, 1);
        __syncthreads();
        STAMP(6);
#pragma unroll
        for (int i = 0; i < 8; i++) {
            if (en[i] != ~0u) {
                unsigned dl = (en[i] >> 14) & 127, cls = en[i] & 7;
                unsigned key = ((dl >> 4) << 7) | (cls << 4) | ((dl & 7) << 1) | ((dl >> 3) & 1);
                unsigned st;
                asm volatile("ld.shared.u8 %0,[%1];" : "=r"(st) : "r"(sb + OFF_START + key) : "memory");
                unsigned p = st + (en[i] >> 21);
                if (p < LCAP) {
                    unsigned wi = 2 + (p >> 3);
                    unsigned a = (dl >> 4) * 1536 + (wi >> 2) * 512 + ((p & 3) * 8 + cls) * 16 + (wi & 3) * 4 + ((p >> 2) & 1) * 2;
                    asm volatile("st.shared.u16 [%0],%1;" ::"r"(sb + OFF_MAIL + a), "h"((unsigned short)((en[i] & 0x3FFF) >> 3)) : "memory");
                } else {
                    g_ovf[b * OVCAP + atoms_inc(sb + OFF_MISC)] = ((b * TILE + dl) << 14) | (en[i] & 0x3FFF);
                }
            }
        }
        wg_quarter(d, F0, desc0, 2);
        wg_wait<2>();
        load_quarter(F1, wf + 8192 + 384);
        __syncthreads();
        if (tid < 480) g_lists[b * 480 + tid] = lds128(sb + OFF_MAIL + tid * 16);
        if (tid == 480) g_ovfn[b] = lds32(sb + OFF_MISC);
        wg_wait<1>();
        load_quarter(F2, wf + 16384);
        wg_quarter(d, F1, desc0, 3);
        wg_wait<1>();
        load_quarter(F0, wf + 16384 + 128);
        wg_wait<0>();
        load_quarter(F1, wf + 16384 + 256);
        generic_attn = __syncthreads_or(stat != 0);
        STAMP(7);
        if (tid == 32) bar_arrive(2);
        {
            unsigned ya = sb + OFF_T + (w >> 2) * 10240 + (g & 3) * 4;
            unsigned ch = (w & 3) * 2 + (g >> 2);
            unsigned a0 = ya + (2 * t) * 128 + ((ch ^ (2 * t)) << 4), a1 = ya + (2 * t + 1) * 128 + ((ch ^ (2 * t + 1)) << 4);
#pragma unroll
            for (int j = 0; j < 10; j++) {
                sts32(a0 + j * 1024, pack2(d[4 * j], d[4 * j + 2]));
                sts32(a1 + j * 1024, pack2(d[4 * j + 1], d[4 * j + 3]));
            }
        }
        asm volatile("cp.async.wait_group 0;" ::: "memory");
        __syncthreads();
        STAMP(8);
#pragma unroll
        for (int i = 0; i < 5; i++) {
            int n = w * 5 + i;
            unsigned ta = sb + OFF_T + (lane >> 3) * 10240 + n * 128 + (((lane ^ n) & 7) << 4);
            uint4 yv = lds128(ta);
            uint4 res;
            if (!generic_attn) {
                float y[8] = {blo(yv.x), bhi(yv.x), blo(yv.y), bhi(yv.y), blo(yv.z), bhi(yv.z), blo(yv.w), bhi(yv.w)};
                uint4 gv[4];
                float p[4];
#pragma unroll
                for (int e = 0; e < 4; e++) {
                    gv[e] = lds128(sb + OFF_S + (n * 4 + e) * 512 + lane * 16);
                    float a = y[0] * blo(gv[e].x), c = y[1] * bhi(gv[e].x);
                    a = fmaf(y[2], blo(gv[e].y), a); c = fmaf(y[3], bhi(gv[e].y), c);
                    a = fmaf(y[4], blo(gv[e].z), a); c = fmaf(y[5], bhi(gv[e].z), c);
                    a = fmaf(y[6], blo(gv[e].w), a); c = fmaf(y[7], bhi(gv[e].w), c);
                    p[e] = a + c;
                }
                bool h1 = lane & 16, h2 = lane & 8;
                float a = (h1 ? p[2] : p[0]) + __shfl_xor_sync(~0u, h1 ? p[0] : p[2], 16);
                float c = (h1 ? p[3] : p[1]) + __shfl_xor_sync(~0u, h1 ? p[1] : p[3], 16);
                float v = (h2 ? c : a) + __shfl_xor_sync(~0u, h2 ? a : c, 8);
                v += __shfl_xor_sync(~0u, v, 4);
                v += __shfl_xor_sync(~0u, v, 2);
                v += __shfl_xor_sync(~0u, v, 1);
                float ex = exp2f(v);
                float den = ex + __shfl_xor_sync(~0u, ex, 8);
                den += __shfl_xor_sync(~0u, den, 16);
                float al = __fdividef(ex, den + 1e-9f);
                float o[8];
#pragma unroll
                for (int e = 0; e < 4; e++) {
                    float ae = __shfl_sync(~0u, al, 8 * e);
                    float q[8] = {blo(gv[e].x), bhi(gv[e].x), blo(gv[e].y), bhi(gv[e].y), blo(gv[e].z), bhi(gv[e].z), blo(gv[e].w), bhi(gv[e].w)};
#pragma unroll
                    for (int k = 0; k < 8; k++) o[k] = e ? fmaf(ae, q[k], o[k]) : ae * q[k];
                }
                res = make_uint4(pack2(o[0], o[1]), pack2(o[2], o[3]), pack2(o[4], o[5]), pack2(o[6], o[7]));
            } else {
                res = attn_generic(b * TILE + n, yv, x, esrc, edst);
            }
            sts128(ta, res);
        }
        asm volatile("fence.proxy.async.shared::cta;" ::: "memory");
        if (tid == 0) bar_poll(2, target);
        __syncthreads();
        STAMP(9);
        if (lane == 0) {
            if (w == 0) asm volatile("mbarrier.arrive.expect_tx.shared.b64 _,[%0],%1;" ::"r"(bar_fill), "r"(NN * 16) : "memory");
            asm volatile("fence.proxy.async;" ::: "memory");
            asm volatile("cp.async.bulk.shared::cluster.global.mbarrier::complete_tx::bytes [%0],[%1],%2,[%3];"
                         ::"r"(sb + OFF_S + w * 10000), "l"(g_hs + (b >> 2) * NN + w * 625), "r"(10000), "r"(bar_fill) : "memory");
        }
        if (tid < 8) sts128(sb + OFF_S + NN * 16 + tid * 16, make_uint4(0, 0, 0, 0));
        __syncwarp();
        wg_quarter(d, F2, desc0, 0); wg_quarter(d, F0, desc0, 1); wg_quarter(d, F1, desc0, 2);
        wg_wait<2>();
        load_quarter(F2, wf + 16384 + 384);
        wg_quarter(d, F2, desc0, 3);
        wg_wait<0>();
        STAMP(10);
        {
            unsigned* op = out + (size_t)(b * TILE + 2 * t) * 128 + w * 8 + g;
#pragma unroll
            for (int j = 0; j < 10; j++) {
                op[(8 * j) * 128] = pack2(d[4 * j], d[4 * j + 2]);
                op[(8 * j + 1) * 128] = pack2(d[4 * j + 1], d[4 * j + 3]);
            }
        }
    } else {
        if (tid == 32) { g_ovfn[b] = 0; bar_arrive(2); }
        if (tid == 0) bar_poll(2, target);
        __syncthreads();
        if (lane == 0) {
            if (w == 0) asm volatile("mbarrier.arrive.expect_tx.shared.b64 _,[%0],%1;" ::"r"(bar_fill), "r"(NN * 16) : "memory");
            asm volatile("fence.proxy.async;" ::: "memory");
            asm volatile("cp.async.bulk.shared::cluster.global.mbarrier::complete_tx::bytes [%0],[%1],%2,[%3];"
                         ::"r"(sb + OFF_S + w * 10000), "l"(g_hs + (b >> 2) * NN + w * 625), "r"(10000), "r"(bar_fill) : "memory");
        }
        if (tid < 8) sts128(sb + OFF_S + NN * 16 + tid * 16, make_uint4(0, 0, 0, 0));
        __syncwarp();
    }

    const int slice = b >> 2, range = b & 3;
    const int g0 = (range * NG) >> 2, g1 = ((range + 1) * NG) >> 2;
    const int grp0 = g0 + w;
    const int cnt = (g1 - grp0 + 15) >> 4;
    unsigned mycode = (lane < cnt) ? __ldcg(&g_codes[grp0 + 16 * lane]) : 0;
    const uint4* lp = g_lists + grp0 * 96 + lane;
    uint4 L0 = ldg_na(lp), L1 = ldg_na(lp + 32);
    unsigned novf = (tid < NCTA) ? __ldcg(&g_ovfn[tid]) : 0;
    const int anyovf = __syncthreads_or(novf != 0);
    if (tid == 32) bar_arrive(3);
    unsigned codes = __reduce_or_sync(~0u, lane < 10 ? mycode << (3 * lane) : 0);
    mbar_wait(bar_fill, 0);
    STAMP(11);
    const unsigned lb = sb + OFF_S + (lane & 7) * 16;
    const float zmask = (lane >= 28) ? 0.f : -1.f;
    unsigned stg = sb + OFF_T + w * 256;
    auto need_attn = [&]() {
        if (!lds32(sb + OFF_MISC + 4)) { bar_poll(3, target); sts32(sb + OFF_MISC + 4, 1); }
        asm volatile("fence.acq_rel.gpu;" ::: "memory");
        asm volatile("fence.proxy.async;" ::: "memory");
    };
    auto flush_round = [&](int r) {
        mbar_wait(bar_rd + 8 * r, 0);
        need_attn();
        asm volatile("cp.reduce.async.bulk.tensor.2d.global.shared::cta.add.tile.bulk_group [%0,{%2,%3}],[%1];"
                     ::"l"(&tm_o256), "r"(sb + OFF_T + r * 4096), "r"(slice * 8), "r"((g0 + 16 * r) * 16) : "memory");
    };
    for (int it = 0; it < cnt; it++) {
        unsigned ad[12];
        ad[0] = dp2lo(L0.z, lb); ad[1] = dp2hi(L0.z, lb); ad[2] = dp2lo(L0.w, lb); ad[3] = dp2hi(L0.w, lb);
        ad[4] = dp2lo(L1.x, lb); ad[5] = dp2hi(L1.x, lb); ad[6] = dp2lo(L1.y, lb); ad[7] = dp2hi(L1.y, lb);
        ad[8] = dp2lo(L1.z, lb); ad[9] = dp2hi(L1.z, lb); ad[10] = dp2lo(L1.w, lb); ad[11] = dp2hi(L1.w, lb);
        unsigned sA = __byte_perm(L0.x, 0x64646464u, 0x4140), nB = __byte_perm(L0.x, 0xE4E4E4E4u, 0x4342);
        float dA = blo_v(L0.y), dB = bhi_v(L0.y);
        lp += 16 * 96;
        L0 = ldg_na(lp); L1 = ldg_na(lp + 32);
        float acc0[4] = {0, 0, 0, 0}, acc1[4] = {0, 0, 0, 0};
        unsigned c = codes & 7;
        codes >>= 3;
        if (c == 1) p3_steps<10>(acc0, acc1, ad, sA, nB);
        else if (c == 2) p3_steps<11>(acc0, acc1, ad, sA, nB);
        else if (c == 0) p3_steps<9>(acc0, acc1, ad, sA, nB);
        else {
            p3_steps<12>(acc0, acc1, ad, sA, nB);
            if (c == 4) {
                uint4 C2 = ldg_na(lp - 16 * 96 + 64);
                unsigned e2[4] = {C2.x, C2.y, C2.z, C2.w};
#pragma unroll
                for (int s = 12; s < 20; s++) p3_step(acc0, acc1, (s & 1) ? dp2hi(e2[(s - 12) >> 1], lb) : dp2lo(e2[(s - 12) >> 1], lb), s, sA, nB);
            }
        }
        float c0 = acc0[0] + acc1[0], c1 = acc0[1] + acc1[1], c2 = acc0[2] + acc1[2], c3 = acc0[3] + acc1[3];
        float n0 = __shfl_down_sync(~0u, c0, 4), n1 = __shfl_down_sync(~0u, c1, 4);
        float o0 = c0 - c2, o1 = c1 - c3, o2 = fmaf(n0, zmask, c2), o3 = fmaf(n1, zmask, c3);
        if (anyovf) {
            float4 e = p3_overflow(grp0 + 16 * it, sb + OFF_S);
            o0 += e.x; o1 += e.y; o2 += e.z; o3 += e.w;
        }
        asm volatile("stmatrix.sync.aligned.m8n8.x2.shared.b16 [%0],{%1,%2};" ::"r"(stg + (lane & 15) * 16), "r"(pack2(o0 * dA, o1 * dA)), "r"(pack2(o2 * dB, o3 * dB)) : "memory");
        __syncwarp();
        if (lane == 0) {
            if (it < 9) {
                asm volatile("mbarrier.arrive.shared.b64 _,[%0];" ::"r"(bar_rd + 8 * it) : "memory");
                if (it == w + 1) flush_round(w);
                if (w == 15 && it == 8) flush_round(8);
            } else {
                need_attn();
                asm volatile("cp.reduce.async.bulk.tensor.2d.global.shared::cta.add.tile.bulk_group [%0,{%2,%3}],[%1];"
                             ::"l"(&tm_o16), "r"(stg), "r"(slice * 8), "r"((grp0 + 144) * 16) : "memory");
            }
        }
        __syncwarp();
        stg += 4096;
    }
    STAMP(12);
    if (lane == 0) {
        asm volatile("cp.async.bulk.commit_group;" ::: "memory");
        asm volatile("cp.async.bulk.wait_group.read 0;" ::: "memory");
    }
    STAMP(13);
}

typedef CUresult (*EncodeFn)(CUtensorMap*, CUtensorMapDataType, cuuint32_t, void*, const cuuint64_t*, const cuuint64_t*,
                             const cuuint32_t*, const cuuint32_t*, CUtensorMapInterleave, CUtensorMapSwizzle,
                             CUtensorMapL2promotion, CUtensorMapFloatOOBfill);

}

extern "C" void kernel_launch(void* const* d_in, const int* in_sizes, int n_in, void* d_out, int out_size) {
    (void)in_sizes; (void)n_in; (void)out_size;
    static EncodeFn enc = nullptr;
    if (!enc) {
        void* fn = nullptr;
        cudaDriverEntryPointQueryResult qr;
        cudaGetDriverEntryPoint("cuTensorMapEncodeTiled", &fn, cudaEnableDefault, &qr);
        enc = (EncodeFn)fn;
        cudaFuncSetAttribute(exphormer_kernel, cudaFuncAttributeMaxDynamicSharedMemorySize, SMEM_BYTES);
    }
    CUtensorMap tm_x, tm_o256, tm_o16;
    cuuint64_t gd[2] = {256, NN}, gs[1] = {512};
    cuuint32_t es[2] = {1, 1};
    cuuint32_t bx[2] = {64, TILE}, b256[2] = {8, 256}, b16[2] = {8, 16};
    enc(&tm_x, CU_TENSOR_MAP_DATA_TYPE_BFLOAT16, 2, d_in[0], gd, gs, bx, es, CU_TENSOR_MAP_INTERLEAVE_NONE,
        CU_TENSOR_MAP_SWIZZLE_128B, CU_TENSOR_MAP_L2_PROMOTION_L2_256B, CU_TENSOR_MAP_FLOAT_OOB_FILL_NONE);
    enc(&tm_o256, CU_TENSOR_MAP_DATA_TYPE_BFLOAT16, 2, d_out, gd, gs, b256, es, CU_TENSOR_MAP_INTERLEAVE_NONE,
        CU_TENSOR_MAP_SWIZZLE_NONE, CU_TENSOR_MAP_L2_PROMOTION_NONE, CU_TENSOR_MAP_FLOAT_OOB_FILL_NONE);
    enc(&tm_o16, CU_TENSOR_MAP_DATA_TYPE_BFLOAT16, 2, d_out, gd, gs, b16, es, CU_TENSOR_MAP_INTERLEAVE_NONE,
        CU_TENSOR_MAP_SWIZZLE_NONE, CU_TENSOR_MAP_L2_PROMOTION_NONE, CU_TENSOR_MAP_FLOAT_OOB_FILL_NONE);
    exphormer_kernel<<<NCTA, 512, SMEM_BYTES>>>(
        (const uint4*)d_in[0], (const int4*)d_in[1], (const int4*)d_in[2], (const int*)d_in[3], (const int*)d_in[4],
        (const unsigned short*)d_in[5], (const unsigned*)d_in[6], (const uint4*)d_in[7], (const uint4*)d_in[8],
        (const unsigned*)d_in[9], (unsigned*)d_out, tm_x, tm_o256, tm_o16);
}
```

```cpp
#include <cuda_runtime.h>
#include <cuda_bf16.h>
#include <cuda.h>
#include <stdint.h>

namespace {

constexpr int NN = 10000, NE = 160000, NEE = 40000;
constexpr int TILE = 80, NT = 125, NCTA = 128, NG = 625, EPC = 1280;
constexpr int CELL = 32;
constexpr int LCAP = 80;
constexpr int OVCAP = EPC + NT * CELL;
constexpr unsigned DUMMY2 = 1250u | (1250u << 16);

constexpr int OFF_S = 0;
constexpr int OFF_R = 163840;
constexpr int OFF_BAR = OFF_R;
constexpr int OFF_MISC = OFF_R + 512;
constexpr int OFF_DIS = OFF_R + 576;
constexpr int OFF_START = OFF_R + 896;
constexpr int OFF_STG = OFF_R + 2048;
constexpr int OFF_CNT1 = OFF_R + 2048;
constexpr int OFF_CNT2 = OFF_R + 2560;
constexpr int OFF_ALPHA = OFF_R + 5248;
constexpr int OFF_MAIL = OFF_R + 7296;
constexpr int OFF_T = OFF_R + 26624;
constexpr int SMEM_BYTES = OFF_T + 40960;
static_assert(SMEM_BYTES <= 232448 && OFF_T % 1024 == 0 && OFF_STG + 6 * 4096 == OFF_T && OFF_MAIL + 16384 <= OFF_T, "smem");

struct __align__(256) Scratch {
    uint4 mimg[8192];
    uint4 hs[32 * NN];
    uint4 mail[NT * 1024];
    uint4 lists[(NG + 16) * 96];
    unsigned ovfn[NCTA];
    unsigned bar[32];
    unsigned ovf[NCTA * OVCAP];
};
__device__ Scratch g_scratch;
#define STAMPT(th, i)
#define PROF_EXTRA 0
#define STAMP(i) STAMPT(64, i)
#define STAMP2(i) STAMPT(416, i)

__device__ __forceinline__ void bar_arrive(unsigned* p) {
    asm volatile("red.release.gpu.global.add.u32 [%0],1;" ::"l"(p) : "memory");
}
__device__ __forceinline__ void bar_poll(const unsigned* p, unsigned target) {
    unsigned v;
    int lim = 0;
    do {
        asm volatile("ld.acquire.gpu.global.u32 %0,[%1];" : "=r"(v) : "l"(p) : "memory");
        if (++lim > (1 << 22)) __trap();
    } while ((int)(v - target) < 0);
}
__device__ __forceinline__ unsigned bar_poll2(const unsigned* p, unsigned target) {
    unsigned long long v;
    int lim = 0;
    do {
        asm volatile("ld.acquire.gpu.global.u64 %0,[%1];" : "=l"(v) : "l"(p) : "memory");
        if (++lim > (1 << 22)) __trap();
    } while ((int)((unsigned)v - target) < 0);
    unsigned f = (unsigned)(v >> 32);
    return (f & ~3u) == target ? f & 3 : 0;
}
__device__ __noinline__ void raise_flag(unsigned* p, unsigned target, unsigned bit) {
    unsigned old = atomicCAS(p, 0, 0), seen;
    do {
        seen = old;
        old = atomicCAS(p, seen, ((seen & ~3u) == target ? seen : target) | bit);
    } while (old != seen);
}
__device__ __forceinline__ void mbar_wait(unsigned a, unsigned par) {
    asm volatile("{.reg .pred p; .reg .u32 n;\n"
                 "mbarrier.try_wait.parity.shared.b64 p,[%0],%1;\n"
                 "@p bra D;\n"
                 "mov.u32 n,0;\n"
                 "W: mbarrier.try_wait.parity.shared.b64 p,[%0],%1;\n"
                 "@p bra D;\n"
                 "add.u32 n,n,1; setp.lt.u32 p,n,0x400000; @p bra W;\n"
                 "trap;\n"
                 "D: }" ::"r"(a), "r"(par) : "memory");
}
__device__ __forceinline__ uint4 ldg_na(const uint4* p) {
    uint4 v;
    asm volatile("ld.global.L1::no_allocate.v4.u32 {%0,%1,%2,%3},[%4];" : "=r"(v.x), "=r"(v.y), "=r"(v.z), "=r"(v.w) : "l"(p) : "memory");
    return v;
}
__device__ __forceinline__ uint4 lds128(unsigned a) {
    uint4 v;
    asm volatile("ld.shared.v4.u32 {%0,%1,%2,%3},[%4];" : "=r"(v.x), "=r"(v.y), "=r"(v.z), "=r"(v.w) : "r"(a) : "memory");
    return v;
}
__device__ __forceinline__ void sts128(unsigned a, uint4 v) {
    asm volatile("st.shared.v4.u32 [%0],{%1,%2,%3,%4};" ::"r"(a), "r"(v.x), "r"(v.y), "r"(v.z), "r"(v.w) : "memory");
}
__device__ __forceinline__ void sts32(unsigned a, unsigned v) { asm volatile("st.shared.u32 [%0],%1;" ::"r"(a), "r"(v) : "memory"); }
__device__ __forceinline__ unsigned lds32(unsigned a) { unsigned v; asm volatile("ld.shared.u32 %0,[%1];" : "=r"(v) : "r"(a) : "memory"); return v; }
__device__ __forceinline__ unsigned atoms_inc(unsigned a) { unsigned v; asm volatile("atom.shared.add.u32 %0,[%1],1;" : "=r"(v) : "r"(a) : "memory"); return v; }
__device__ __forceinline__ float blo(unsigned v) { return __uint_as_float(v << 16); }
__device__ __forceinline__ float bhi(unsigned v) { return __uint_as_float(v & 0xFFFF0000u); }
__device__ __forceinline__ float blo_v(unsigned v) { float r; asm volatile("shl.b32 %0,%1,16;" : "=f"(r) : "r"(v)); return r; }
__device__ __forceinline__ float bhi_v(unsigned v) { float r; asm volatile("and.b32 %0,%1,0xFFFF0000;" : "=f"(r) : "r"(v)); return r; }
__device__ __forceinline__ unsigned pack2(float lo, float hi) { unsigned r; asm("cvt.rn.bf16x2.f32 %0,%1,%2;" : "=r"(r) : "f"(hi), "f"(lo)); return r; }

__device__ __forceinline__ void mma16816(float* d, unsigned a0, unsigned a1, unsigned a2, unsigned a3, unsigned b0, unsigned b1) {
    asm volatile("mma.sync.aligned.m16n8k16.row.col.f32.bf16.bf16.f32 {%0,%1,%2,%3},{%4,%5,%6,%7},{%8,%9},{%0,%1,%2,%3};"
                 : "+f"(d[0]), "+f"(d[1]), "+f"(d[2]), "+f"(d[3]) : "r"(a0), "r"(a1), "r"(a2), "r"(a3), "r"(b0), "r"(b1));
}
#define R10(b) "+f"(d[b + 0]), "+f"(d[b + 1]), "+f"(d[b + 2]), "+f"(d[b + 3]), "+f"(d[b + 4]), "+f"(d[b + 5]), "+f"(d[b + 6]), "+f"(d[b + 7]), "+f"(d[b + 8]), "+f"(d[b + 9])
__device__ __forceinline__ void wg80(float* d, unsigned long long da, unsigned long long db, int sc) {
    asm volatile("{.reg .pred p; setp.ne.b32 p,%42,0;\n"
                 "wgmma.mma_async.sync.aligned.m64n80k16.f32.bf16.bf16 "
                 "{%0,%1,%2,%3,%4,%5,%6,%7,%8,%9,%10,%11,%12,%13,%14,%15,%16,%17,%18,%19,%20,%21,%22,%23,%24,%25,%26,%27,%28,%29,%30,%31,%32,%33,%34,%35,%36,%37,%38,%39},"
                 "%40,%41,p,1,1,1,0;}"
                 : R10(0), R10(10), R10(20), R10(30) : "l"(da), "l"(db), "r"(sc));
}
__device__ __forceinline__ void wg_fence() { asm volatile("wgmma.fence.sync.aligned;" ::: "memory"); }
__device__ __forceinline__ void wg_commit() { asm volatile("wgmma.commit_group.sync.aligned;" ::: "memory"); }
template <int N> __device__ __forceinline__ void wg_wait() { asm volatile("wgmma.wait_group.sync.aligned %0;" ::"n"(N) : "memory"); }
__device__ __forceinline__ void bulk_g2s(unsigned dst, const void* src, unsigned bytes, unsigned bar) {
    asm volatile("cp.async.bulk.shared::cluster.global.mbarrier::complete_tx::bytes [%0],[%1],%2,[%3];" ::"r"(dst), "l"(src), "r"(bytes), "r"(bar) : "memory");
}
__device__ __forceinline__ void fence_async_smem() { asm volatile("fence.proxy.async.shared::cta;" ::: "memory"); }
__device__ __forceinline__ void fence_async_gmem() { asm volatile("fence.proxy.async.global;" ::: "memory"); }

__device__ __forceinline__ unsigned hsat(unsigned a, unsigned c) { unsigned r; asm("add.sat.f16x2 %0,%1,%2;" : "=r"(r) : "r"(a), "r"(c)); return r; }
__device__ __forceinline__ unsigned hset(unsigned a, unsigned c) { unsigned r; asm("set.le.f16x2.f16x2 %0,%1,%2;" : "=r"(r) : "r"(a), "r"(c)); return r; }
__host__ __device__ constexpr unsigned h2c(int v) { return (0x6400u | v) | ((0x6400u | v) << 16); }
__device__ __forceinline__ unsigned dp2lo(unsigned a, unsigned c) { unsigned r; asm("dp2a.lo.u32.u32 %0,%1,%2,%3;" : "=r"(r) : "r"(a), "r"(0x80000080u), "r"(c)); return r; }
__device__ __forceinline__ unsigned dp2hi(unsigned a, unsigned c) { unsigned r; asm("dp2a.hi.u32.u32 %0,%1,%2,%3;" : "=r"(r) : "r"(a), "r"(0x80000080u), "r"(c)); return r; }
__device__ __forceinline__ void p3_step(float* acc0, float* acc1, unsigned addr, int s, unsigned sA, unsigned nB) {
    unsigned b0, b1, b2, b3;
    asm volatile("ldmatrix.sync.aligned.m8n8.x4.trans.shared.b16 {%0,%1,%2,%3},[%4];" : "=r"(b0), "=r"(b1), "=r"(b2), "=r"(b3) : "r"(addr));
    mma16816(acc0, hset(sA, h2c(4 * s + 0)), hsat(nB, h2c(4 * s + 1)), hset(sA, h2c(4 * s + 1)), hsat(nB, h2c(4 * s + 2)), b0, b1);
    mma16816(acc1, hset(sA, h2c(4 * s + 2)), hsat(nB, h2c(4 * s + 3)), hset(sA, h2c(4 * s + 3)), hsat(nB, h2c(4 * s + 4)), b2, b3);
}
template <int NS> __device__ __forceinline__ void p3_steps(float* acc0, float* acc1, const unsigned* ad, unsigned sA, unsigned nB) {
#pragma unroll
    for (int s = 0; s < NS; s++) p3_step(acc0, acc1, ad[s], s, sA, nB);
}
__device__ __noinline__ float4 p3_overflow(const Scratch* sc, int grp, unsigned sS) {
    int lane = threadIdx.x & 31, g = lane >> 2, t = lane & 3;
    float4 r = make_float4(0.f, 0.f, 0.f, 0.f);
    for (int c = 0; c < NT; c++) {
        int n = (int)__ldcg(&sc->ovfn[c]);
        for (int i0 = 0; i0 < n; i0 += 32) {
            unsigned e = (i0 + lane < n) ? __ldcg(&sc->ovf[c * OVCAP + i0 + lane]) : 0xFFFFFFFFu;
            unsigned m = __ballot_sync(~0u, (int)(e >> 18) == grp);
            while (m) {
                int j = __ffs(m) - 1;
                m &= m - 1;
                unsigned ee = __shfl_sync(~0u, e, j);
                int row = (ee >> 14) & 15;
                unsigned v = lds32(sS + (ee & 0x3FFF) * 16 + t * 4);
                if ((row & 7) == g) {
                    if (row < 8) { r.x += blo(v); r.y += bhi(v); } else { r.z += blo(v); r.w += bhi(v); }
                }
            }
        }
    }
    const float k = 1.f / 128.f;
    r.x *= k; r.y *= k; r.z *= k; r.w *= k;
    return r;
}
__device__ __forceinline__ void unpack8(float* f, uint4 v) {
    f[0] = blo(v.x); f[1] = bhi(v.x); f[2] = blo(v.y); f[3] = bhi(v.y); f[4] = blo(v.z); f[5] = bhi(v.z); f[6] = blo(v.w); f[7] = bhi(v.w);
}
__device__ __forceinline__ void vec_mat(float* o, const float* v, const uint4* __restrict__ W, int lane) {
    for (int k = 0; k < 8; k++) o[k] = 0.f;
    for (int l = 0; l < 32; l++) {
#pragma unroll
        for (int i = 0; i < 8; i++) {
            float a = __shfl_sync(~0u, v[i], l), wr[8];
            unpack8(wr, W[(l * 8 + i) * 32 + lane]);
#pragma unroll
            for (int k = 0; k < 8; k++) o[k] = fmaf(a, wr[k], o[k]);
        }
    }
}
__device__ __noinline__ uint4 attn_generic(int node, const uint4* __restrict__ x, const int* __restrict__ esrc, const int* __restrict__ edst,
                                           const uint4* __restrict__ wq, const uint4* __restrict__ wk, const uint4* __restrict__ wv) {
    int lane = threadIdx.x & 31;
    float xr[8], q[8], y[8], o[8];
    unpack8(xr, x[node * 32 + lane]);
    vec_mat(q, xr, wq, lane);
    for (int l = 0; l < 32; l++) {
#pragma unroll
        for (int i = 0; i < 8; i++) {
            float wr[8], p = 0.f;
            unpack8(wr, wk[(l * 8 + i) * 32 + lane]);
#pragma unroll
            for (int k = 0; k < 8; k++) p = fmaf(q[k], wr[k], p);
            for (int k = 16; k; k >>= 1) p += __shfl_xor_sync(~0u, p, k);
            if (lane == l) y[i] = p;
        }
    }
    for (int k = 0; k < 8; k++) o[k] = 0.f;
    float den = 0.f;
    for (int i0 = 0; i0 < NEE; i0 += 32) {
        unsigned m = __ballot_sync(~0u, edst[i0 + lane] == node);
        while (m) {
            int j = __ffs(m) - 1;
            m &= m - 1;
            float gq[8], p = 0.f;
            unpack8(gq, x[esrc[i0 + j] * 32 + lane]);
#pragma unroll
            for (int k = 0; k < 8; k++) p = fmaf(y[k], gq[k], p);
            for (int k = 16; k; k >>= 1) p += __shfl_xor_sync(~0u, p, k);
            float ex = __expf(p * 0.0625f);
            den += ex;
#pragma unroll
            for (int k = 0; k < 8; k++) o[k] = fmaf(ex, gq[k], o[k]);
        }
    }
    float inv = 1.f / (den + 1e-9f);
    for (int k = 0; k < 8; k++) o[k] *= inv;
    vec_mat(q, o, wv, lane);
    return make_uint4(pack2(q[0], q[1]), pack2(q[2], q[3]), pack2(q[4], q[5]), pack2(q[6], q[7]));
}

__device__ __forceinline__ unsigned hfma2(unsigned a, unsigned b, unsigned c) { unsigned r; asm("fma.rn.bf16x2 %0,%1,%2,%3;" : "=r"(r) : "r"(a), "r"(b), "r"(c)); return r; }
__device__ __forceinline__ unsigned hmul2(unsigned a, unsigned b) { unsigned r; asm("mul.rn.bf16x2 %0,%1,%2;" : "=r"(r) : "r"(a), "r"(b)); return r; }

__device__ __forceinline__ void attn_nodes(unsigned sb, int n0, int lane, unsigned alsm, const uint4 (*gv)[4]) {
    float v[5];
    const bool h1 = lane & 16, h2 = lane & 8, h3 = lane & 4, h4 = lane & 2, h5 = lane & 1;
    const unsigned tb = sb + OFF_T + (lane >> 3) * 10240;
#pragma unroll
    for (int i = 0; i < 5; i++) {
        int n = n0 + i;
        uint4 yv = lds128(tb + n * 128 + (((lane ^ n) & 7) << 4));
        float y[8] = {blo(yv.x), bhi(yv.x), blo(yv.y), bhi(yv.y), blo(yv.z), bhi(yv.z), blo(yv.w), bhi(yv.w)};
        float p[4];
#pragma unroll
        for (int e = 0; e < 4; e++) {
            float a = y[0] * blo(gv[i][e].x);
            a = fmaf(y[1], bhi(gv[i][e].x), a);
            a = fmaf(y[2], blo(gv[i][e].y), a); a = fmaf(y[3], bhi(gv[i][e].y), a);
            a = fmaf(y[4], blo(gv[i][e].z), a); a = fmaf(y[5], bhi(gv[i][e].z), a);
            a = fmaf(y[6], blo(gv[i][e].w), a); a = fmaf(y[7], bhi(gv[i][e].w), a);
            p[e] = a;
        }
        float a = (h1 ? p[2] : p[0]) + __shfl_xor_sync(~0u, h1 ? p[0] : p[2], 16);
        float c = (h1 ? p[3] : p[1]) + __shfl_xor_sync(~0u, h1 ? p[1] : p[3], 16);
        v[i] = (h2 ? c : a) + __shfl_xor_sync(~0u, h2 ? a : c, 8);
    }
    float u0 = (h3 ? v[1] : v[0]) + __shfl_xor_sync(~0u, h3 ? v[0] : v[1], 4);
    float u1 = (h3 ? v[3] : v[2]) + __shfl_xor_sync(~0u, h3 ? v[2] : v[3], 4);
    float u2 = v[4] + __shfl_xor_sync(~0u, v[4], 4);
    float z0 = (h4 ? u1 : u0) + __shfl_xor_sync(~0u, h4 ? u0 : u1, 2);
    float z1 = u2 + __shfl_xor_sync(~0u, u2, 2);
    float u = (h5 ? z1 : z0) + __shfl_xor_sync(~0u, h5 ? z0 : z1, 1);
    const int nn = h5 ? 4 : (h4 ? 2 : 0) + h3;
    float ex = exp2f(u);
    float den = ex + __shfl_xor_sync(~0u, ex, 8);
    den += __shfl_xor_sync(~0u, den, 16);
    float al = __fdividef(ex, den + 1e-9f);
    sts32(alsm + nn * 16 + (lane >> 3) * 4, pack2(al, al));
    __syncwarp();
#pragma unroll
    for (int i = 0; i < 5; i++) {
        int n = n0 + i;
        uint4 a = lds128(alsm + i * 16);
        uint4 o;
        o.x = hfma2(a.w, gv[i][3].x, hfma2(a.z, gv[i][2].x, hfma2(a.y, gv[i][1].x, hmul2(a.x, gv[i][0].x))));
        o.y = hfma2(a.w, gv[i][3].y, hfma2(a.z, gv[i][2].y, hfma2(a.y, gv[i][1].y, hmul2(a.x, gv[i][0].y))));
        o.z = hfma2(a.w, gv[i][3].z, hfma2(a.z, gv[i][2].z, hfma2(a.y, gv[i][1].z, hmul2(a.x, gv[i][0].z))));
        o.w = hfma2(a.w, gv[i][3].w, hfma2(a.z, gv[i][2].w, hfma2(a.y, gv[i][1].w, hmul2(a.x, gv[i][0].w))));
        sts128(tb + n * 128 + (((lane ^ n) & 7) << 4), o);
    }
}
__device__ __forceinline__ void pack_acc(unsigned* pk, const float* d) {
#pragma unroll
    for (int j = 0; j < 20; j++) pk[j] = pack2(d[2 * j], d[2 * j + 1]);
}
__device__ __forceinline__ void acc_to_tile(const unsigned* pk, unsigned sb, int w, int lane) {
    const unsigned a = sb + OFF_T + (w >> 2) * 10240 + (lane >> 4) * 1024 + (lane & 7) * 128 + (((2 * (w & 3) + ((lane >> 3) & 1)) ^ (lane & 7)) << 4);
#pragma unroll
    for (int j = 0; j < 5; j++)
        asm volatile("stmatrix.sync.aligned.m8n8.x4.trans.shared.b16 [%0],{%1,%2,%3,%4};" ::"r"(a + j * 2048), "r"(pk[4 * j]), "r"(pk[4 * j + 1]), "r"(pk[4 * j + 2]), "r"(pk[4 * j + 3]) : "memory");
}
__device__ __forceinline__ unsigned movm(unsigned a) { unsigned d; asm volatile("movmatrix.sync.aligned.m8n8.trans.b16 %0,%1;" : "=r"(d) : "r"(a)); return d; }
__device__ __forceinline__ void tma_load3d(unsigned dst, const CUtensorMap* tm, int row, unsigned bar) {
    asm volatile("cp.async.bulk.tensor.3d.shared::cluster.global.mbarrier::complete_tx::bytes [%0],[%1,{%4,%3,%4}],[%2];"
                 ::"r"(dst), "l"(tm), "r"(bar), "r"(row), "r"(0) : "memory");
}
__device__ __forceinline__ void cp16(unsigned dst, const void* src) { asm volatile("cp.async.cg.shared.global [%0],[%1],16;" ::"r"(dst), "l"(src) : "memory"); }
__device__ __forceinline__ void cp_commit() { asm volatile("cp.async.commit_group;" ::: "memory"); }
template <int N> __device__ __forceinline__ void cp_wait() { asm volatile("cp.async.wait_group %0;" ::"n"(N) : "memory"); }
__device__ __forceinline__ void nb_sync_id(int id, int n) { asm volatile("bar.sync %0,%1;" ::"r"(id), "r"(n) : "memory"); }
__device__ __forceinline__ void nb_arrive_id(int id, int n) { asm volatile("bar.arrive %0,%1;" ::"r"(id), "r"(n) : "memory"); }
template <int ID, int N> __device__ __forceinline__ void nb_sync() { asm volatile("bar.sync %0,%1;" ::"n"(ID), "n"(N) : "memory"); }
template <int ID, int N> __device__ __forceinline__ void nb_arrive() { asm volatile("bar.arrive %0,%1;" ::"n"(ID), "n"(N) : "memory"); }
__device__ __forceinline__ void mbar_init(unsigned a, int n) { asm volatile("mbarrier.init.shared.b64 [%0],%1;" ::"r"(a), "r"(n) : "memory"); }
__device__ __forceinline__ void mbar_expect(unsigned a, int n) { asm volatile("mbarrier.arrive.expect_tx.shared.b64 _,[%0],%1;" ::"r"(a), "r"(n) : "memory"); }
__device__ __forceinline__ void mbar_arrive(unsigned a) { asm volatile("mbarrier.arrive.shared.b64 _,[%0];" ::"r"(a) : "memory"); }

__device__ __forceinline__ void bin_rank4(uint4& e, unsigned sb) {
    unsigned r0 = atoms_inc(sb + OFF_CNT2 + ((e.x >> 9) & 0xFFC)), r1 = atoms_inc(sb + OFF_CNT2 + ((e.y >> 9) & 0xFFC));
    unsigned r2 = atoms_inc(sb + OFF_CNT2 + ((e.z >> 9) & 0xFFC)), r3 = atoms_inc(sb + OFF_CNT2 + ((e.w >> 9) & 0xFFC));
    e.x |= min(r0, 127u) << 21; e.y |= min(r1, 127u) << 21; e.z |= min(r2, 127u) << 21; e.w |= min(r3, 127u) << 21;
}
__device__ __noinline__ void bin_overflow(Scratch* sc, unsigned e, unsigned sb) {
    unsigned key = (e >> 11) & 1023;
    unsigned dl = (key >> 7) * 16 + ((key & 1) << 3) + ((key >> 1) & 7);
    sc->ovf[blockIdx.x * OVCAP + atoms_inc(sb + OFF_MISC)] = ((blockIdx.x * TILE + dl) << 14) | ((e & 2047) << 3) | ((key >> 4) & 7);
}
__device__ __forceinline__ void bin_place4(Scratch* sc, const uint4& v, unsigned sb) {
    const unsigned e[4] = {v.x, v.y, v.z, v.w};
    unsigned h[4];
    bool spill = false;
#pragma unroll
    for (int i = 0; i < 4; i++) asm volatile("ld.shared.u8 %0,[%1];" : "=r"(h[i]) : "r"(sb + OFF_START + ((e[i] >> 11) & 1023)) : "memory");
#pragma unroll
    for (int i = 0; i < 4; i++) {
        h[i] += (e[i] >> 21) + 16;
        unsigned a = ((e[i] >> 7) & 0x3800) + ((e[i] >> 11) & 0x70) + ((h[i] & 0x60) << 4) + ((h[i] & 3) << 7) + ((h[i] >> 1) & 0xE);
        asm volatile("{.reg .pred p; setp.lt.u32 p,%2,%3; @p st.shared.u16 [%0],%1;}" ::"r"(sb + OFF_MAIL + a), "h"((unsigned short)(e[i] & 2047)), "r"(h[i]), "n"(LCAP + 16) : "memory");
        spill |= h[i] - (LCAP + 16) < 128;
    }
    if (spill) {
#pragma unroll
        for (int i = 0; i < 4; i++) if (h[i] - (LCAP + 16) < 128) bin_overflow(sc, e[i], sb);
    }
}

__global__ void __launch_bounds__(512, 1)
exphormer_kernel(const uint4* __restrict__ src4, const uint4* __restrict__ dst4, const uint4* __restrict__ wq, const uint4* __restrict__ wk,
                 const int* __restrict__ esrc, const int* __restrict__ edst, const uint4* __restrict__ x, Scratch* __restrict__ sc,
                 const unsigned* __restrict__ dis, const uint4* __restrict__ wv,
                 const __grid_constant__ CUtensorMap tm_wl, const __grid_constant__ CUtensorMap tm_wv,
                 const __grid_constant__ CUtensorMap tm_ot, const __grid_constant__ CUtensorMap tm_o256, const __grid_constant__ CUtensorMap tm_o16) {
    extern __shared__ __align__(1024) unsigned char smem_raw[];
    const unsigned sb = (unsigned)__cvta_generic_to_shared(smem_raw);
    const unsigned tid = threadIdx.x, lane = tid & 31, g = lane >> 2, t = lane & 3;
    const int w = __shfl_sync(~0u, tid >> 5, 0), wg = w >> 2;
    const unsigned b = blockIdx.x;
    const bool rowcta = b < NT;
    const unsigned bar_fill = sb + OFF_BAR, bar_t = bar_fill + 8, bar_mail = bar_fill + 16, bar_rd = bar_fill + 24, bar_full = bar_fill + 128;
    STAMP(0);

    unsigned xs = 0, xd = 0;
    auto load_exp = [&]() {
        if (rowcta && lane < 20) { xs = __ldg(esrc + (b * 320 + w * 20 + lane)); xd = __ldg(edst + (b * 320 + w * 20 + lane)); }
    };
    if (w >= 6) {
        if (rowcta) {
            const unsigned bt = tid - 192;
            const uint4 ed = __ldg(dst4 + (b * 320 + bt)), es = __ldg(src4 + (b * 320 + bt));
            load_exp();
            const unsigned pad = (640u + (bt & 3) + ((b * 4) & 28)) << 11;
#pragma unroll
            for (int k = 0; k < 4; k++) if (k < 3 || bt < 40) sts128(sb + OFF_MAIL + (bt + k * 320) * 16, make_uint4(pad, pad, pad, pad));
            if (bt < (512 + 2688) / 16) sts128(sb + OFF_CNT1 + bt * 16, make_uint4(0, 0, 0, 0));
            if (bt == 319) sts128(sb + OFF_MISC, make_uint4(0, 0, 0, 0));
            if (bt >= 317 && bt < 319) sts128(sb + OFF_START + 640 + (bt - 317) * 16, make_uint4(~0u, ~0u, ~0u, ~0u));
            unsigned z;
            asm volatile("{.reg .pred p; setp.eq.u32 p,%1,0xFFFFFFFF; bar.red.popc.u32 %0,4,320,p;}" : "=r"(z) : "r"(bt) : "memory");
            const unsigned dd[4] = {ed.x + z, ed.y + z, ed.z + z, ed.w + z}, ss[4] = {es.x + z, es.y + z, es.z + z, es.w + z};
            unsigned rk[4], ow[4];
#pragma unroll
            for (int i = 0; i < 4; i++) { ow[i] = dd[i] / TILE; rk[i] = atoms_inc(sb + OFF_CNT1 + ow[i] * 4); }
#pragma unroll
            for (int i = 0; i < 4; i++) {
                unsigned key = (((dd[i] >> 4) - ow[i] * 5) << 7) | ((ss[i] & 7) << 4) | ((dd[i] & 7) << 1) | ((dd[i] >> 3) & 1);
                asm volatile("{.reg .pred p; setp.lt.u32 p,%2,%3; @p st.shared.u32 [%0],%1;}" ::"r"(sb + OFF_MAIL + (ow[i] * CELL + rk[i]) * 4), "r"((key << 11) | (ss[i] >> 3)), "r"(rk[i]), "n"(CELL) : "memory");
            }
            if ((rk[0] | rk[1] | rk[2] | rk[3]) >= CELL) {
#pragma unroll
                for (int i = 0; i < 4; i++)
                    if (rk[i] >= CELL) sc->ovf[b * OVCAP + atoms_inc(sb + OFF_MISC)] = (dd[i] << 14) | ss[i];
            }
            STAMPT(416, 44);
            nb_sync<4, 320>();
            uint4 mv[4];
            uint4* mp = sc->mail + ((bt >> 3) * 1024 + (bt & 4) * 128 + b * 4 + (bt & 3));
#pragma unroll
            for (int k = 0; k < 4; k++) if (k < 3 || bt < 40) mv[k] = lds128(sb + OFF_MAIL + (bt + k * 320) * 16);
#pragma unroll
            for (int k = 0; k < 4; k++) if (k < 3 || bt < 40) mp[k * 40960] = mv[k];
        }
        STAMPT(416, 45);
        if (w == 15) {
            nb_sync<2, 384>();
            if (lane == 0) bar_arrive(&sc->bar[0]);
            __syncwarp();
            STAMPT(480, 47);
        } else {
            nb_arrive<2, 384>();
        }
    } else if (w >= 2) {
        const unsigned fw = b >> 3, hq = b & 7, q = w - 2, cq = q * 8 + 2 * t;
        const uint4* pa = wq + ((16 * fw + g) * 32 + cq);
        const uint4* pb = wk + ((32 * hq + 8 * (g >> 1) + (g & 1)) * 32 + cq);
        uint4 va[4], vb[8];
        va[0] = __ldg(pa); va[1] = __ldg(pa + 1); va[2] = __ldg(pa + 256); va[3] = __ldg(pa + 257);
#pragma unroll
        for (int u = 0; u < 8; u++) vb[u] = __ldg(pb + (u >> 1) * 64 + (u & 1));
        load_exp();
        unsigned dv = 0;
        if (rowcta && tid - 128 < TILE / 2) dv = __ldg(dis + (b * (TILE / 2) + tid - 128));
        float c[4][4];
#pragma unroll
        for (int u = 0; u < 4; u++) {
            c[u][0] = c[u][1] = c[u][2] = c[u][3] = 0.f;
            mma16816(c[u], va[0].x, va[2].x, va[0].y, va[2].y, vb[2 * u].x, vb[2 * u].y);
            mma16816(c[u], va[0].z, va[2].z, va[0].w, va[2].w, vb[2 * u].z, vb[2 * u].w);
            mma16816(c[u], va[1].x, va[3].x, va[1].y, va[3].y, vb[2 * u + 1].x, vb[2 * u + 1].y);
            mma16816(c[u], va[1].z, va[3].z, va[1].w, va[3].w, vb[2 * u + 1].z, vb[2 * u + 1].w);
        }
        const unsigned ra = sb + OFF_S + 4 * 32768 + lane * 16;
#pragma unroll
        for (int hh = 0; hh < 2; hh++) {
            sts128(ra + q * 2048 + hh * 1024, make_uint4(__float_as_uint(c[0][2 * hh]), __float_as_uint(c[0][2 * hh + 1]), __float_as_uint(c[1][2 * hh]), __float_as_uint(c[1][2 * hh + 1])));
            sts128(ra + q * 2048 + hh * 1024 + 512, make_uint4(__float_as_uint(c[2][2 * hh]), __float_as_uint(c[2][2 * hh + 1]), __float_as_uint(c[3][2 * hh]), __float_as_uint(c[3][2 * hh + 1])));
        }
        STAMPT(64, 42);
        nb_sync<1, 128>();
        if (q < 2) {
            float m[8] = {0, 0, 0, 0, 0, 0, 0, 0};
#pragma unroll
            for (int i = 0; i < 4; i++) {
                uint4 u = lds128(ra + i * 2048 + q * 1024), v = lds128(ra + i * 2048 + q * 1024 + 512);
                m[0] += __uint_as_float(u.x); m[1] += __uint_as_float(u.y); m[2] += __uint_as_float(u.z); m[3] += __uint_as_float(u.w);
                m[4] += __uint_as_float(v.x); m[5] += __uint_as_float(v.y); m[6] += __uint_as_float(v.z); m[7] += __uint_as_float(v.w);
            }
            const float k = 0.0625f * 1.4426950408889634f;
            sc->mimg[(fw >> 2) * 2048 + (hq >> 1) * 512 + (16 * (fw & 3) + 8 * q + g) * 8 + (((hq & 1) * 4 + t) ^ g)] =
                make_uint4(pack2(m[0] * k, m[1] * k), pack2(m[2] * k, m[3] * k), pack2(m[4] * k, m[5] * k), pack2(m[6] * k, m[7] * k));
            nb_arrive<2, 384>();
        } else if (tid - 128 < TILE / 2) {
            asm volatile("st.shared.v2.u32 [%0],{%1,%2};" ::"r"(sb + OFF_DIS + (tid - 128) * 8), "r"(dv << 16), "r"(dv & 0xFFFF0000u) : "memory");
        }
    } else {
        load_exp();
        unsigned epoch = 0;
        if (tid == 63) asm volatile("ld.relaxed.gpu.global.u32 %0,[%1];" : "=r"(epoch) : "l"(&sc->bar[1]) : "memory");
        if (tid == 0) {
            for (int i = 0; i < 4; i++) mbar_init(bar_full + 8 * i, 1);
            asm volatile("fence.mbarrier_init.release.cluster;" ::: "memory");
            if (rowcta)
                for (int i = 0; i < 4; i++) { mbar_expect(bar_full + 8 * i, 32768); tma_load3d(sb + OFF_S + i * 32768, &tm_wl, i * 64, bar_full + 8 * i); }
            STAMPT(0, 41);
        }
        __syncwarp();
        const unsigned xa = sb + OFF_T + ((lane >> 3) & 1) * 10240 + (w * 40 + (lane >> 4)) * 128 + (((lane ^ (lane >> 4)) & 7) << 4);
        const uint4* xp = x + (b * (TILE * 32) + (w * 40 + (lane >> 4)) * 32 + (lane & 15));
        auto xgroup = [&](int gi) {
            if (rowcta) {
#pragma unroll
                for (int k = 0; k < 5; k++) {
                    const int i = (gi & 3) * 5 + k;
                    cp16((xa ^ (((2 * i) & 6) << 4)) + i * 256 + (gi >> 2) * 20480, xp + i * 64 + (gi >> 2) * 16);
                }
            }
            cp_commit();
        };
        xgroup(0); xgroup(1); xgroup(2); xgroup(3);
        STAMPT(32, 40);
        if (tid == 32) {
            for (int i = 4; i < 12; i++) mbar_init(bar_full + 8 * i, i == 7 ? 4 : 1);
            mbar_init(bar_fill, 1); mbar_init(bar_t, 1); mbar_init(bar_mail, 1);
            for (int i = 0; i < 10; i++) mbar_init(bar_rd + 8 * i, 16);
            asm volatile("fence.mbarrier_init.release.cluster;" ::: "memory");
        }
        if (tid == 63) sts128(sb + OFF_MISC + 16, make_uint4(0, 0, (epoch & ~(NCTA - 1)) + NCTA, 0));
        __syncwarp();
        cp_wait<3>(); xgroup(4);
        cp_wait<3>(); xgroup(5);
        cp_wait<3>(); xgroup(6);
        cp_wait<3>(); xgroup(7);
        asm volatile("fence.proxy.async.shared::cta;" ::: "memory");
        STAMPT(32, 46);
    }
    if (w < 15) nb_sync<3, 480>();
    if (w == 14) nb_arrive<5, 64>();
    if (w == 15) nb_sync<5, 64>();

    auto fill_piece = [&](int off, int bytes) {
        const int n = min(bytes, NN * 16 - off);
        if (n > 0) bulk_g2s(sb + OFF_S + off, (const char*)(sc->hs + (b >> 2) * NN) + off, n, bar_fill);
    };
    const int slice = b >> 2, range = b & 3;
    const int g0 = (range * NG) >> 2, g1 = ((range + 1) * NG) >> 2;
    const int grp0 = g0 + w;
    const uint4* lp = sc->lists + (grp0 * 96 + lane);
    uint4 L0, L1;

    if (rowcta) {
        const unsigned long long descA = (1ull << 62) | (64ull << 32) | (1ull << 16) | (unsigned long long)(((sb + OFF_S + wg * 8192) & 0x3FFFF) >> 4);
        const unsigned greg = sb + OFF_S + w * 2048 + lane * 16;
        const bool lead = (tid & 127) == 0;
        float d[40];
        unsigned pk[20];
        unsigned* hp = (unsigned*)(sc->hs + (2 * w * NN + b * TILE)) + lane;
        auto mma_q = [&](int Q, int slot, int st) {
            mbar_wait(bar_full + 8 * Q, 0);
            unsigned long long db;
            asm volatile("add.s64 %0,%1,%2;" : "=l"(db) : "l"(descA), "l"((unsigned long long)((OFF_T - OFF_S) / 16 + (Q & 3) * 640 - wg * 512)));
            wg_fence();
#pragma unroll
            for (int k = 0; k < 4; k++) {
                wg80(d, descA + slot * 2048 + k * 128, db + k * 2, ((Q & 3) | k) != 0);
                if (st >= 0) {
#pragma unroll
                    for (int j = st + 2 * k; j < st + 2 * k + 2; j++)
                        if (j < 20) asm volatile("st.global.u32 [%0],%1;" ::"l"(hp + (j >> 1) * 32 + (j & 1) * (NN * 4)), "r"(pk[j]) : "memory");
                }
            }
            wg_commit();
        };
        auto gather = [&](int i, int slot) {
#pragma unroll
            for (int j = 0; j < 4; j++) cp16(greg + slot * 32768 + j * 512, x + (__shfl_sync(~0u, xs, 4 * i + j) * 32u + lane));
            cp_commit();
        };
        uint4 gv[5][4];
        auto to_regs = [&](int i, int slot) {
#pragma unroll
            for (int j = 0; j < 4; j++) gv[i][j] = lds128(greg + slot * 32768 + j * 512);
        };
        auto load_m = [&](int i, int slot) {
            mbar_expect(bar_full + 32 + 8 * i, 32768);
            bulk_g2s(sb + OFF_S + slot * 32768, sc->mimg + i * 2048, 32768, bar_full + 32 + 8 * i);
        };
        auto load_v = [&](int i, int slot) {
            mbar_expect(bar_full + 64 + 8 * i, 32768);
            tma_load3d(sb + OFF_S + slot * 32768, &tm_wv, i * 64, bar_full + 64 + 8 * i);
        };
        STAMP(3);
        gather(0, 4);
        mma_q(0, 0, -1); mma_q(1, 1, -1);
        if (__any_sync(~0u, lane < 20 && xd != b * TILE + w * 5 + (lane >> 2))) sts32(sb + OFF_MISC + 20, 1);
        wg_wait<0>();
        STAMP(4);
        if (tid == 256) bar_poll(&sc->bar[0], lds32(sb + OFF_MISC + 24));
        STAMPT(256, 48);
        float ds[20];
#pragma unroll
        for (int j = 0; j < 10; j++) asm volatile("ld.shared.v2.f32 {%0,%1},[%2];" : "=f"(ds[2 * j]), "=f"(ds[2 * j + 1]) : "r"(sb + OFF_DIS + (8 * j + 2 * t) * 4));
        cp_wait<0>();
        to_regs(0, 4);
        fence_async_smem();
        STAMPT(32, 49);
        __syncthreads();
        if (tid == 256) {
            fence_async_gmem();
            load_m(0, 0);
            mbar_expect(bar_mail, 16384);
            bulk_g2s(sb + OFF_MAIL, sc->mail + b * 1024, 16384, bar_mail);
            load_m(1, 1);
        }
        __syncwarp();
        STAMP(5);
        gather(1, 4);
        mma_q(2, 2, -1); mma_q(3, 3, -1);
        wg_wait<0>();
        STAMP(6);
        uint4 e0, e1;
        mbar_wait(bar_mail, 0);
        e0 = lds128(sb + OFF_MAIL + tid * 16); e1 = lds128(sb + OFF_MAIL + 8192 + tid * 16);
        if (tid >= 500) { const unsigned pad = (640u + lane) << 11; e0 = e1 = make_uint4(pad, pad, pad, pad); }
        bin_rank4(e0, sb);
        const bool more = __any_sync(~0u, e1.x < (640u << 11));
        if (more) bin_rank4(e1, sb);
        cp_wait<0>();
        to_regs(1, 4);
#pragma unroll
        for (int j = 0; j < 20; j++) pk[j] = pack2(d[2 * j] * ds[2 * (j >> 1)], d[2 * j + 1] * ds[2 * (j >> 1) + 1]);
        __syncthreads();
        STAMP(7);
        if (tid == 256) load_m(2, 3);
        __syncwarp();
        gather(2, 4); gather(3, 2);
        const unsigned ia = sb + OFF_MAIL + (tid / 96) * 2048 + (tid % 96) * 16;
        if (tid < 480) sts128(ia, make_uint4(DUMMY2, DUMMY2, DUMMY2, DUMMY2));
        unsigned hdr = 0, dpair = 0;
        if (w >= 11) {
            const int G = w - 11;
            uint4 c = lds128(sb + OFF_CNT2 + (G * 128 + lane * 4) * 4);
            float da = __uint_as_float(lds32(sb + OFF_DIS + (G * 16 + g) * 4)) * 128.f, db = __uint_as_float(lds32(sb + OFF_DIS + (G * 16 + g + 8) * 4)) * 128.f;
            unsigned s1 = c.x, s2 = s1 + c.y, s3 = s2 + c.z, tot = s3 + c.w, inc = tot;
            unsigned u = __shfl_up_sync(~0u, inc, 1, 4); if (t >= 1) inc += u;
            u = __shfl_up_sync(~0u, inc, 2, 4); if (t >= 2) inc += u;
            unsigned base = inc - tot;
            unsigned word = min(base, (unsigned)LCAP) | (min(base + s1, (unsigned)LCAP) << 8) | (min(base + s2, (unsigned)LCAP) << 16) | (min(base + s3, (unsigned)LCAP) << 24);
            sts32(sb + OFF_START + (G * 32 + lane) * 4, word);
            unsigned wa = __shfl_sync(~0u, word, 8 * t + (g >> 1)), wb = __shfl_sync(~0u, word, 8 * t + 4 + (g >> 1));
            hdr = __byte_perm(wa, wb, (g & 1) ? 0x7362 : 0x5140);
            if (__any_sync(~0u, inc > 48)) hdr |= 0x80;
            dpair = pack2(da, db);
        }
#pragma unroll
        for (int j = 0; j < 20; j++) pk[j] = movm(pk[j]);
        STAMP(21);
        mma_q(4, 0, 0); mma_q(5, 1, 8);
        wg_wait<1>();
        nb_sync_id(8 + wg, 128);
        if (lead) {
            fence_async_gmem();
            mbar_expect(bar_full + 56, 8192);
            bulk_g2s(sb + OFF_S + wg * 8192, sc->mimg + (3 * 2048 + wg * 512), 8192, bar_full + 56);
        }
        __syncwarp();
        mma_q(6, 3, 16);
        wg_wait<1>();
        nb_sync_id(8 + wg, 128);
        gather(4, 1);
        mma_q(7, 0, -1);
        wg_wait<1>();
        __syncthreads();
        if (tid == 256) load_v(0, 3);
        __syncwarp();
        wg_wait<0>();
        STAMP(20);
        if (w >= 11) asm volatile("st.shared.v2.u32 [%0],{%1,%2};" ::"r"(sb + OFF_MAIL + (w - 11) * 2048 + lane * 16), "r"(hdr), "r"(dpair) : "memory");
        bin_place4(sc, e0, sb);
        if (more) bin_place4(sc, e1, sb);
        pack_acc(pk, d);
        __syncthreads();
        if (tid == 256) load_v(1, 0);
        __syncwarp();
        acc_to_tile(pk, sb, w, lane);
        if (tid < 480) sc->lists[b * 480 + tid] = lds128(ia);
        cp_wait<1>();
        to_regs(2, 4); to_regs(3, 2);
        __syncthreads();
        STAMP(8);
        if (tid == 256) { fence_async_smem(); load_v(2, 4); load_v(3, 2); }
        if (tid == 480) {
            const unsigned novf = lds32(sb + OFF_MISC), bad = lds32(sb + OFF_MISC + 20);
            sc->ovfn[b] = novf;
            if (novf | bad) raise_flag(&sc->bar[5], lds32(sb + OFF_MISC + 24), (novf ? 1 : 0) | (bad ? 2 : 0));
            bar_arrive(&sc->bar[4]);
        }
        __syncwarp();
        cp_wait<0>();
        to_regs(4, 1);
        attn_nodes(sb, w * 5, lane, sb + OFF_ALPHA + w * 128, gv);
        fence_async_smem();
        STAMP(22);
        if (tid == 0) {
            sts32(sb + OFF_MISC + 28, bar_poll2(&sc->bar[4], lds32(sb + OFF_MISC + 24)));
            mbar_expect(bar_fill, NN * 16);
        }
        __syncthreads();
        STAMP(9);
        if (lead) { fence_async_gmem(); fill_piece(32768 + wg * 8192, 8192); }
        __syncwarp();
        L0 = ldg_na(lp); L1 = ldg_na(lp + 32);
        mma_q(8, 3, -1); mma_q(9, 0, -1);
        wg_wait<1>();
        nb_sync_id(8 + wg, 128);
        if (lead) fill_piece(3 * 32768 + wg * 8192, 8192);
        __syncwarp();
        mma_q(10, 4, -1);
        wg_wait<1>();
        nb_sync_id(8 + wg, 128);
        if (lead) fill_piece(wg * 8192, 8192);
        __syncwarp();
        mma_q(11, 2, -1);
        wg_wait<1>();
        nb_sync_id(8 + wg, 128);
        if (lead) fill_piece(4 * 32768 + wg * 8192, 8192);
        if (w == 15 && lane < 8) sts128(sb + OFF_S + NN * 16 + lane * 16, make_uint4(0, 0, 0, 0));
        __syncwarp();
        wg_wait<0>();
        pack_acc(pk, d);
        __syncthreads();
        STAMP(10);
        if (lead) fill_piece(2 * 32768 + wg * 8192, 8192);
        __syncwarp();
        if (lds32(sb + OFF_MISC + 28) & 2) {
            for (int i = 0; i < 5; i++) {
                int n = w * 5 + i;
                sts128(sb + OFF_T + (lane >> 3) * 10240 + n * 128 + (((lane ^ n) & 7) << 4),
                       attn_generic(b * TILE + n, x, esrc, edst, wq, wk, wv));
            }
        } else {
            acc_to_tile(pk, sb, w, lane);
        }
        fence_async_smem();
    } else {
        if (tid == 0) {
            bar_arrive(&sc->bar[4]);
            sts32(sb + OFF_MISC + 28, bar_poll2(&sc->bar[4], lds32(sb + OFF_MISC + 24)));
            mbar_expect(bar_fill, NN * 16);
        }
        __syncthreads();
        if (lane == 0) { fence_async_gmem(); fence_async_smem(); fill_piece(w * 10000, 10000); }
        if (w == 15 && lane < 8) sts128(sb + OFF_S + NN * 16 + lane * 16, make_uint4(0, 0, 0, 0));
        L0 = ldg_na(lp); L1 = ldg_na(lp + 32);
    }

    const int cnt = (g1 - grp0 + 15) >> 4;
    const bool anyovf = lds32(sb + OFF_MISC + 28) & 1;
    __syncthreads();
    if (tid == 15 * 32) {
        if (rowcta) {
#pragma unroll
            for (int kb = 0; kb < 4; kb++)
                asm volatile("cp.async.bulk.tensor.2d.global.shared::cta.bulk_group [%0,{%2,%3}],[%1];"
                             ::"l"(&tm_ot), "r"(sb + OFF_T + kb * 10240), "r"(kb * 64), "r"(b * TILE) : "memory");
            asm volatile("cp.async.bulk.commit_group;" ::: "memory");
            asm volatile("cp.async.bulk.wait_group 0;" ::: "memory");
            fence_async_gmem();
        }
        bar_arrive(&sc->bar[1]);
        asm volatile("mbarrier.arrive.shared.b64 _,[%0];" ::"r"(bar_t) : "memory");
    }
    __syncwarp();
    const int flush_it = (w < 8) ? w + 1 : (w == 14 ? 8 : 31);
    unsigned special = (1u << 5) | (1u << 9) | (1u << flush_it);
    mbar_wait(bar_fill, 0);
    STAMP(11);
    const unsigned lb = sb + OFF_S + (lane & 7) * 16;
    const unsigned dummy = anyovf ? 0 : lb + 1250 * 128;
    const float zmask = (lane >= 28) ? 0.f : -1.f;
    unsigned stg = sb + OFF_STG + w * 256 + (lane & 15) * 16;
    unsigned rdb = bar_rd;
    for (int it = 0; it < cnt; it++) {
        unsigned ad[12];
        ad[0] = dp2lo(L0.z, lb); ad[1] = dp2hi(L0.z, lb); ad[2] = dp2lo(L0.w, lb); ad[3] = dp2hi(L0.w, lb);
        ad[4] = dp2lo(L1.x, lb); ad[5] = dp2hi(L1.x, lb); ad[6] = dp2lo(L1.y, lb); ad[7] = dp2hi(L1.y, lb);
        ad[8] = dp2lo(L1.z, lb); ad[9] = dp2hi(L1.z, lb); ad[10] = dp2lo(L1.w, lb); ad[11] = dp2hi(L1.w, lb);
        unsigned sA = __byte_perm(L0.x, 0x64646464u, 0x4140), nB = __byte_perm(L0.x, 0xE4E4E4E4u, 0x4342);
        float dA = blo_v(L0.y), dB = bhi_v(L0.y);
        lp += 16 * 96;
        L0 = ldg_na(lp); L1 = ldg_na(lp + 32);
        float acc0[4] = {0, 0, 0, 0}, acc1[4] = {0, 0, 0, 0};
        if (!__any_sync(~0u, ad[10] != dummy)) {
            if (__any_sync(~0u, ad[9] != dummy)) p3_steps<10>(acc0, acc1, ad, sA, nB);
            else p3_steps<9>(acc0, acc1, ad, sA, nB);
        } else if (!__any_sync(~0u, ad[11] != dummy)) {
            p3_steps<11>(acc0, acc1, ad, sA, nB);
        } else {
            const bool longer = (sA & 0x80) || anyovf;
            sA &= ~0x80u;
            p3_steps<12>(acc0, acc1, ad, sA, nB);
            if (__any_sync(~0u, longer)) {
                uint4 C2 = ldg_na(lp - 16 * 96 + 64);
                unsigned e2[4] = {C2.x, C2.y, C2.z, C2.w};
#pragma unroll
                for (int s = 12; s < 20; s++) p3_step(acc0, acc1, (s & 1) ? dp2hi(e2[(s - 12) >> 1], lb) : dp2lo(e2[(s - 12) >> 1], lb), s, sA, nB);
                if (anyovf) {
                    float4 e = p3_overflow(sc, grp0 + 16 * it, sb + OFF_S);
                    float s0 = e.x + e.z, s1 = e.y + e.w;
                    for (int k = 4; k < 32; k <<= 1) {
                        float u0 = __shfl_down_sync(~0u, s0, k), u1 = __shfl_down_sync(~0u, s1, k);
                        if (lane + k < 32) { s0 += u0; s1 += u1; }
                    }
                    acc0[0] += s0; acc0[1] += s1; acc0[2] += s0 - e.x; acc0[3] += s1 - e.y;
                }
            }
        }
        float c0 = acc0[0] + acc1[0], c1 = acc0[1] + acc1[1], c2 = acc0[2] + acc1[2], c3 = acc0[3] + acc1[3];
        float n0 = __shfl_down_sync(~0u, c0, 4), n1 = __shfl_down_sync(~0u, c1, 4);
        float o0 = c0 - c2, o1 = c1 - c3, o2 = fmaf(n0, zmask, c2), o3 = fmaf(n1, zmask, c3);
        asm volatile("stmatrix.sync.aligned.m8n8.x2.shared.b16 [%0],{%1,%2};" ::"r"(stg), "r"(pack2(o0 * dA, o1 * dA)), "r"(pack2(o2 * dB, o3 * dB)) : "memory");
        __syncwarp();
        asm volatile("{.reg .pred p; setp.eq.u32 p,%1,0; @p mbarrier.arrive.shared.b64 _,[%0];}" ::"r"(rdb), "r"(lane) : "memory");
        if (special & 1) {
            if (it == 5) mbar_wait(bar_t, 0);
            if (lane == 0 && (it == 9 || it == flush_it)) {
                const int r = (w < 8) ? w : 8;
                if (it != 9) mbar_wait(bar_rd + 8 * r, 0);
                if (!lds32(sb + OFF_MISC + 16)) { bar_poll(&sc->bar[1], lds32(sb + OFF_MISC + 24)); sts32(sb + OFF_MISC + 16, 1); }
                fence_async_gmem();
                fence_async_smem();
                if (it != 9)
                    asm volatile("cp.reduce.async.bulk.tensor.2d.global.shared::cta.add.tile.bulk_group [%0,{%2,%3}],[%1];"
                                 ::"l"(&tm_o256), "r"(sb + OFF_STG + r * 4096), "r"(slice * 8), "r"((g0 + 16 * r) * 16) : "memory");
                else
                    asm volatile("cp.reduce.async.bulk.tensor.2d.global.shared::cta.add.tile.bulk_group [%0,{%2,%3}],[%1];"
                                 ::"l"(&tm_o16), "r"(stg), "r"(slice * 8), "r"((grp0 + 144) * 16) : "memory");
            }
            __syncwarp();
        }
        special >>= 1;
        stg += 4096;
        rdb += 8;
    }
    STAMP(12);
    if (lane == 0) {
        asm volatile("cp.async.bulk.commit_group;" ::: "memory");
        asm volatile("cp.async.bulk.wait_group.read 0;" ::: "memory");
    }
    STAMP(13);
}

typedef CUresult (*EncodeFn)(CUtensorMap*, CUtensorMapDataType, cuuint32_t, void*, const cuuint64_t*, const cuuint64_t*,
                             const cuuint32_t*, const cuuint32_t*, CUtensorMapInterleave, CUtensorMapSwizzle,
                             CUtensorMapL2promotion, CUtensorMapFloatOOBfill);

}

extern "C" void kernel_launch(void* const* d_in, const int* in_sizes, int n_in, void* d_out, int out_size) {
    (void)in_sizes; (void)n_in; (void)out_size;
    static EncodeFn enc = nullptr;
    static void* scratch = nullptr;
    if (!enc) {
        cudaGetSymbolAddress(&scratch, g_scratch);
        void* fn = nullptr;
        cudaDriverEntryPointQueryResult qr;
        cudaGetDriverEntryPoint("cuTensorMapEncodeTiled", &fn, cudaEnableDefault, &qr);
        enc = (EncodeFn)fn;
        cudaFuncSetAttribute(exphormer_kernel, cudaFuncAttributeMaxDynamicSharedMemorySize, SMEM_BYTES + PROF_EXTRA);
    }
    CUtensorMap tm_wl, tm_wv, tm_ot, tm_o256, tm_o16;
    auto mk = [&](CUtensorMap* tm, void* p, int rows, int bc, int br, CUtensorMapSwizzle sw, CUtensorMapL2promotion pr) {
        cuuint64_t gd[2] = {256, (cuuint64_t)rows}, gs[1] = {512};
        cuuint32_t es[2] = {1, 1}, bx[2] = {(cuuint32_t)bc, (cuuint32_t)br};
        enc(tm, CU_TENSOR_MAP_DATA_TYPE_BFLOAT16, 2, p, gd, gs, bx, es, CU_TENSOR_MAP_INTERLEAVE_NONE, sw, pr, CU_TENSOR_MAP_FLOAT_OOB_FILL_NONE);
    };
    for (int i = 0; i < 2; i++) {
        cuuint64_t gd[3] = {64, 256, 4}, gs[2] = {512, 128};
        cuuint32_t es[3] = {1, 1, 1}, bx[3] = {64, 64, 4};
        enc(i ? &tm_wv : &tm_wl, CU_TENSOR_MAP_DATA_TYPE_BFLOAT16, 3, d_in[i ? 9 : 6], gd, gs, bx, es, CU_TENSOR_MAP_INTERLEAVE_NONE,
            CU_TENSOR_MAP_SWIZZLE_128B, CU_TENSOR_MAP_L2_PROMOTION_L2_128B, CU_TENSOR_MAP_FLOAT_OOB_FILL_NONE);
    }
    mk(&tm_ot, d_out, NN, 64, TILE, CU_TENSOR_MAP_SWIZZLE_128B, CU_TENSOR_MAP_L2_PROMOTION_NONE);
    mk(&tm_o256, d_out, NN, 8, 256, CU_TENSOR_MAP_SWIZZLE_NONE, CU_TENSOR_MAP_L2_PROMOTION_NONE);
    mk(&tm_o16, d_out, NN, 8, 16, CU_TENSOR_MAP_SWIZZLE_NONE, CU_TENSOR_MAP_L2_PROMOTION_NONE);
    exphormer_kernel<<<NCTA, 512, SMEM_BYTES + PROF_EXTRA>>>(
        (const uint4*)d_in[1], (const uint4*)d_in[2], (const uint4*)d_in[7], (const uint4*)d_in[8], (const int*)d_in[3], (const int*)d_in[4],
        (const uint4*)d_in[0], (Scratch*)scratch, (const unsigned*)d_in[5], (const uint4*)d_in[9],
        tm_wl, tm_wv, tm_ot, tm_o256, tm_o16);
}
```

```cpp
#include <cuda_runtime.h>
#include <cuda_bf16.h>
#include <cuda.h>
#include <stdint.h>

namespace {

constexpr int NN = 10000, NE = 160000, NEE = 40000;
constexpr int TILE = 80, NT = 125, NCTA = 128, NG = 625, EPC = 1280;
constexpr int CELL = 32;
constexpr int LCAP = 80;
constexpr int OVCAP = EPC + NT * CELL;
#define XD0 600
#define XD1 1200
#define XD2 0
constexpr unsigned DUMMY2 = 1250u | (1250u << 16);

constexpr unsigned sb = 1024;
constexpr int OFF_S = 0;
constexpr int OFF_R = 163840;
constexpr int OFF_BAR = OFF_R;
constexpr int OFF_MISC = OFF_R + 256;
constexpr int OFF_DIS = OFF_R + 320;
constexpr int OFF_EIDX = OFF_R + 640;
constexpr int OFF_STG = OFF_R + 2048;
constexpr int OFF_CNT1 = OFF_R + 2048;
constexpr int OFF_CNT2 = OFF_R + 2560;
constexpr int OFF_ALPHA = OFF_R + 5248;
constexpr int OFF_MAIL = OFF_R + 7296;
constexpr int OFF_T = OFF_R + 26624;
constexpr int SMEM_BYTES = OFF_T + 40960;
static_assert(SMEM_BYTES <= 232448 && OFF_T % 1024 == 0 && OFF_STG + 6 * 4096 == OFF_T && OFF_MAIL + 16384 <= OFF_T, "smem");
constexpr unsigned bar_fill = sb + OFF_BAR, bar_t = bar_fill + 8, bar_mail = bar_fill + 16, bar_rd = bar_fill + 24, bar_full = bar_fill + 128;

struct __align__(256) Scratch {
    uint4 mimg[8192];
    uint4 hs[32 * NN];
    uint4 mail[NT * 1024];
    uint4 lists[(NG + 16) * 96];
    unsigned ovfn[NCTA];
    unsigned bar[32];
    unsigned ovf[NCTA * OVCAP];
};
__device__ Scratch g_scratch;
#define STAMPT(th, i)
#define PROF_EXTRA 0
#define STAMP(i) STAMPT(64, i)
#define STAMP2(i) STAMPT(416, i)

__device__ __forceinline__ void bar_arrive(unsigned* p) {
    asm volatile("red.release.gpu.global.add.u32 [%0],1;" ::"l"(p) : "memory");
}
__device__ __forceinline__ void bar_poll(const unsigned* p, unsigned target) {
    unsigned v;
    int lim = 0;
    do {
        asm volatile("ld.acquire.gpu.global.u32 %0,[%1];" : "=r"(v) : "l"(p) : "memory");
        if (++lim > (1 << 22)) __trap();
    } while ((int)(v - target) < 0);
}
__device__ __forceinline__ unsigned bar_poll2(const unsigned* p, unsigned target) {
    unsigned long long v;
    int lim = 0;
    do {
        asm volatile("ld.acquire.gpu.global.u64 %0,[%1];" : "=l"(v) : "l"(p) : "memory");
        if (++lim > (1 << 22)) __trap();
    } while ((int)((unsigned)v - target) < 0);
    unsigned f = (unsigned)(v >> 32);
    return (f & ~3u) == target ? f & 3 : 0;
}
__device__ __noinline__ void raise_flag(unsigned* p, unsigned target, unsigned bit) {
    unsigned old = atomicCAS(p, 0, 0), seen;
    do {
        seen = old;
        old = atomicCAS(p, seen, ((seen & ~3u) == target ? seen : target) | bit);
    } while (old != seen);
}
__device__ __forceinline__ void mbar_wait(unsigned a) {
    asm volatile("{.reg .pred p; .reg .u32 n;\n"
                 "mov.u32 n,0x400000;\n"
                 "W: mbarrier.try_wait.parity.shared.b64 p,[%0],0;\n"
                 "add.u32 n,n,-1; setp.ne.and.u32 p,n,0,!p; @p bra W;}" ::"r"(a) : "memory");
}
__device__ __forceinline__ bool elect() {
    unsigned r;
    asm volatile("{.reg .pred p; elect.sync _|p,0xFFFFFFFF; selp.u32 %0,1,0,p;}" : "=r"(r));
    return r;
}
__device__ __forceinline__ uint4 ldg_na(const uint4* p) {
    uint4 v;
    asm volatile("ld.global.L1::no_allocate.v4.u32 {%0,%1,%2,%3},[%4];" : "=r"(v.x), "=r"(v.y), "=r"(v.z), "=r"(v.w) : "l"(p) : "memory");
    return v;
}
__device__ __forceinline__ uint4 lds128(unsigned a) {
    uint4 v;
    asm volatile("ld.shared.v4.u32 {%0,%1,%2,%3},[%4];" : "=r"(v.x), "=r"(v.y), "=r"(v.z), "=r"(v.w) : "r"(a) : "memory");
    return v;
}
__device__ __forceinline__ void sts128(unsigned a, uint4 v) {
    asm volatile("st.shared.v4.u32 [%0],{%1,%2,%3,%4};" ::"r"(a), "r"(v.x), "r"(v.y), "r"(v.z), "r"(v.w) : "memory");
}
__device__ __forceinline__ void sts32(unsigned a, unsigned v) { asm volatile("st.shared.u32 [%0],%1;" ::"r"(a), "r"(v) : "memory"); }
__device__ __forceinline__ unsigned lds32(unsigned a) { unsigned v; asm volatile("ld.shared.u32 %0,[%1];" : "=r"(v) : "r"(a) : "memory"); return v; }
__device__ __forceinline__ unsigned atoms_add(unsigned a, unsigned k) { unsigned v; asm volatile("atom.shared.add.u32 %0,[%1],%2;" : "=r"(v) : "r"(a), "r"(k) : "memory"); return v; }
__device__ __forceinline__ unsigned bitsel(unsigned a, unsigned b, unsigned m) { unsigned r; asm("lop3.b32 %0,%1,%2,%3,0xE4;" : "=r"(r) : "r"(a), "r"(b), "r"(m)); return r; }
__device__ __forceinline__ unsigned atoms_inc(unsigned a) { unsigned v; asm volatile("atom.shared.add.u32 %0,[%1],1;" : "=r"(v) : "r"(a) : "memory"); return v; }
__device__ __forceinline__ float blo(unsigned v) { return __uint_as_float(v << 16); }
__device__ __forceinline__ float bhi(unsigned v) { return __uint_as_float(v & 0xFFFF0000u); }
__device__ __forceinline__ float blo_v(unsigned v) { float r; asm volatile("shl.b32 %0,%1,16;" : "=f"(r) : "r"(v)); return r; }
__device__ __forceinline__ float bhi_v(unsigned v) { float r; asm volatile("and.b32 %0,%1,0xFFFF0000;" : "=f"(r) : "r"(v)); return r; }
__device__ __forceinline__ unsigned pack2(float lo, float hi) { unsigned r; asm("cvt.rn.bf16x2.f32 %0,%1,%2;" : "=r"(r) : "f"(hi), "f"(lo)); return r; }

__device__ __forceinline__ void mma16816(float* d, unsigned a0, unsigned a1, unsigned a2, unsigned a3, unsigned b0, unsigned b1) {
    asm volatile("mma.sync.aligned.m16n8k16.row.col.f32.bf16.bf16.f32 {%0,%1,%2,%3},{%4,%5,%6,%7},{%8,%9},{%0,%1,%2,%3};"
                 : "+f"(d[0]), "+f"(d[1]), "+f"(d[2]), "+f"(d[3]) : "r"(a0), "r"(a1), "r"(a2), "r"(a3), "r"(b0), "r"(b1));
}
#define R10(b) "+f"(d[b + 0]), "+f"(d[b + 1]), "+f"(d[b + 2]), "+f"(d[b + 3]), "+f"(d[b + 4]), "+f"(d[b + 5]), "+f"(d[b + 6]), "+f"(d[b + 7]), "+f"(d[b + 8]), "+f"(d[b + 9])
__device__ __forceinline__ void wg80(float* d, unsigned da, unsigned db, int sc) {
    asm volatile("{.reg .pred p; .reg .b64 a, b; setp.ne.b32 p,%42,0; mov.b64 a,{%40,%43}; mov.b64 b,{%41,%43};\n"
                 "wgmma.mma_async.sync.aligned.m64n80k16.f32.bf16.bf16 "
                 "{%0,%1,%2,%3,%4,%5,%6,%7,%8,%9,%10,%11,%12,%13,%14,%15,%16,%17,%18,%19,%20,%21,%22,%23,%24,%25,%26,%27,%28,%29,%30,%31,%32,%33,%34,%35,%36,%37,%38,%39},"
                 "a,b,p,1,1,1,0;}"
                 : R10(0), R10(10), R10(20), R10(30) : "r"(da), "r"(db), "r"(sc), "r"(0x40000040));
}
__device__ __forceinline__ void wg_fence() { asm volatile("wgmma.fence.sync.aligned;" ::: "memory"); }
__device__ __forceinline__ void wg_commit() { asm volatile("wgmma.commit_group.sync.aligned;" ::: "memory"); }
template <int N> __device__ __forceinline__ void wg_wait() { asm volatile("wgmma.wait_group.sync.aligned %0;" ::"n"(N) : "memory"); }
__device__ __forceinline__ void bulk_g2s(unsigned dst, const void* src, unsigned bytes, unsigned bar) {
    asm volatile("cp.async.bulk.shared::cluster.global.mbarrier::complete_tx::bytes [%0],[%1],%2,[%3];" ::"r"(dst), "l"(src), "r"(bytes), "r"(bar) : "memory");
}
__device__ __forceinline__ void fence_async_smem() { asm volatile("fence.proxy.async.shared::cta;" ::: "memory"); }
__device__ __forceinline__ void fence_async_gmem() { asm volatile("fence.proxy.async.global;" ::: "memory"); }

__device__ __forceinline__ unsigned hsat(unsigned a, unsigned c) { unsigned r; asm("add.sat.f16x2 %0,%1,%2;" : "=r"(r) : "r"(a), "r"(c)); return r; }
__device__ __forceinline__ unsigned hset(unsigned a, unsigned c) { unsigned r; asm("set.le.f16x2.f16x2 %0,%1,%2;" : "=r"(r) : "r"(a), "r"(c)); return r; }
__host__ __device__ constexpr unsigned h2c(int v) { return (0x6400u | v) | ((0x6400u | v) << 16); }
__device__ __forceinline__ unsigned dp2lo(unsigned a, unsigned c) { unsigned r; asm("dp2a.lo.u32.u32 %0,%1,%2,%3;" : "=r"(r) : "r"(a), "r"(0x80000080u), "r"(c)); return r; }
__device__ __forceinline__ unsigned dp2hi(unsigned a, unsigned c) { unsigned r; asm("dp2a.hi.u32.u32 %0,%1,%2,%3;" : "=r"(r) : "r"(a), "r"(0x80000080u), "r"(c)); return r; }
__device__ __forceinline__ void p3_step(float* acc0, float* acc1, unsigned addr, int s, unsigned sA, unsigned nB) {
    unsigned b0, b1, b2, b3;
    asm volatile("ldmatrix.sync.aligned.m8n8.x4.trans.shared.b16 {%0,%1,%2,%3},[%4];" : "=r"(b0), "=r"(b1), "=r"(b2), "=r"(b3) : "r"(addr));
    mma16816(acc0, hset(sA, h2c(4 * s + 0)), hsat(nB, h2c(4 * s + 1)), hset(sA, h2c(4 * s + 1)), hsat(nB, h2c(4 * s + 2)), b0, b1);
    mma16816(acc1, hset(sA, h2c(4 * s + 2)), hsat(nB, h2c(4 * s + 3)), hset(sA, h2c(4 * s + 3)), hsat(nB, h2c(4 * s + 4)), b2, b3);
}
template <int NS> __device__ __forceinline__ void p3_steps(float* acc0, float* acc1, const unsigned* ad, unsigned sA, unsigned nB) {
#pragma unroll
    for (int s = 0; s < NS; s++) p3_step(acc0, acc1, ad[s], s, sA, nB);
}
__device__ __noinline__ float4 p3_overflow(const Scratch* sc, int grp, unsigned sS) {
    int lane = threadIdx.x & 31, g = lane >> 2, t = lane & 3;
    float4 r = make_float4(0.f, 0.f, 0.f, 0.f);
    for (int c = 0; c < NT; c++) {
        int n = (int)__ldcg(&sc->ovfn[c]);
        for (int i0 = 0; i0 < n; i0 += 32) {
            unsigned e = (i0 + lane < n) ? __ldcg(&sc->ovf[c * OVCAP + i0 + lane]) : 0xFFFFFFFFu;
            unsigned m = __ballot_sync(~0u, (int)(e >> 18) == grp);
            while (m) {
                int j = __ffs(m) - 1;
                m &= m - 1;
                unsigned ee = __shfl_sync(~0u, e, j);
                int row = (ee >> 14) & 15;
                row ^= row >> 3;
                unsigned v = lds32(sS + (ee & 0x3FFF) * 16 + t * 4);
                if ((row >> 1) == g) {
                    if (!(row & 1)) { r.x += blo(v); r.y += bhi(v); } else { r.z += blo(v); r.w += bhi(v); }
                }
            }
        }
    }
    const float k = 1.f / 128.f;
    r.x *= k; r.y *= k; r.z *= k; r.w *= k;
    return r;
}
__device__ __forceinline__ void unpack8(float* f, uint4 v) {
    f[0] = blo(v.x); f[1] = bhi(v.x); f[2] = blo(v.y); f[3] = bhi(v.y); f[4] = blo(v.z); f[5] = bhi(v.z); f[6] = blo(v.w); f[7] = bhi(v.w);
}
__device__ __forceinline__ void vec_mat(float* o, const float* v, const uint4* __restrict__ W, int lane) {
    for (int k = 0; k < 8; k++) o[k] = 0.f;
    for (int l = 0; l < 32; l++) {
#pragma unroll
        for (int i = 0; i < 8; i++) {
            float a = __shfl_sync(~0u, v[i], l), wr[8];
            unpack8(wr, W[(l * 8 + i) * 32 + lane]);
#pragma unroll
            for (int k = 0; k < 8; k++) o[k] = fmaf(a, wr[k], o[k]);
        }
    }
}
__device__ __noinline__ uint4 attn_generic(int node, const uint4* __restrict__ x, const int* __restrict__ esrc, const int* __restrict__ edst,
                                           const uint4* __restrict__ wq, const uint4* __restrict__ wk, const uint4* __restrict__ wv) {
    int lane = threadIdx.x & 31;
    float xr[8], q[8], y[8], o[8];
    unpack8(xr, x[node * 32 + lane]);
    vec_mat(q, xr, wq, lane);
    for (int l = 0; l < 32; l++) {
#pragma unroll
        for (int i = 0; i < 8; i++) {
            float wr[8], p = 0.f;
            unpack8(wr, wk[(l * 8 + i) * 32 + lane]);
#pragma unroll
            for (int k = 0; k < 8; k++) p = fmaf(q[k], wr[k], p);
            for (int k = 16; k; k >>= 1) p += __shfl_xor_sync(~0u, p, k);
            if (lane == l) y[i] = p;
        }
    }
    for (int k = 0; k < 8; k++) o[k] = 0.f;
    float den = 0.f;
    for (int i0 = 0; i0 < NEE; i0 += 32) {
        unsigned m = __ballot_sync(~0u, edst[i0 + lane] == node);
        while (m) {
            int j = __ffs(m) - 1;
            m &= m - 1;
            float gq[8], p = 0.f;
            unpack8(gq, x[esrc[i0 + j] * 32 + lane]);
#pragma unroll
            for (int k = 0; k < 8; k++) p = fmaf(y[k], gq[k], p);
            for (int k = 16; k; k >>= 1) p += __shfl_xor_sync(~0u, p, k);
            float ex = __expf(p * 0.0625f);
            den += ex;
#pragma unroll
            for (int k = 0; k < 8; k++) o[k] = fmaf(ex, gq[k], o[k]);
        }
    }
    float inv = 1.f / (den + 1e-9f);
    for (int k = 0; k < 8; k++) o[k] *= inv;
    vec_mat(q, o, wv, lane);
    return make_uint4(pack2(q[0], q[1]), pack2(q[2], q[3]), pack2(q[4], q[5]), pack2(q[6], q[7]));
}

__device__ __forceinline__ unsigned hfma2(unsigned a, unsigned b, unsigned c) { unsigned r; asm("fma.rn.bf16x2 %0,%1,%2,%3;" : "=r"(r) : "r"(a), "r"(b), "r"(c)); return r; }
__device__ __forceinline__ unsigned hmul2(unsigned a, unsigned b) { unsigned r; asm("mul.rn.bf16x2 %0,%1,%2;" : "=r"(r) : "r"(a), "r"(b)); return r; }

__device__ __forceinline__ unsigned tile_addr(int n, unsigned chunk) { return sb + OFF_T + (chunk >> 3) * 10240 + n * 128 + (((chunk ^ n) & 7) << 4); }
__device__ __forceinline__ void attn_scores(float* v, bool mine, bool par, const uint4* gv, unsigned yaddr) {
    const uint4 y = lds128(yaddr);
    float c[4] = {0, 0, 0, 0}, e[4] = {0, 0, 0, 0};
    mma16816(c, gv[0].x, gv[1].x, gv[0].y, gv[1].y, y.x, y.y);
    mma16816(e, gv[2].x, gv[3].x, gv[2].y, gv[3].y, y.x, y.y);
    mma16816(c, gv[0].z, gv[1].z, gv[0].w, gv[1].w, y.z, y.w);
    mma16816(e, gv[2].z, gv[3].z, gv[2].w, gv[3].w, y.z, y.w);
    if (mine) { v[0] = par ? c[1] : c[0]; v[1] = par ? c[3] : c[2]; v[2] = par ? e[1] : e[0]; v[3] = par ? e[3] : e[2]; }
}
__device__ __forceinline__ void attn_softmax(const float* v, const float* u, unsigned lane, unsigned delta, unsigned alsm) {
    const bool hA = lane & 4, hB = lane & 8, hC = lane & 16;
    float a[4];
#pragma unroll
    for (int e = 0; e < 4; e++) a[e] = (hA ? u[e] : v[e]) + __shfl_xor_sync(~0u, hA ? v[e] : u[e], 4);
    float b0 = (hB ? a[1] : a[0]) + __shfl_xor_sync(~0u, hB ? a[0] : a[1], 9);
    float b1 = (hB ? a[3] : a[2]) + __shfl_xor_sync(~0u, hB ? a[2] : a[3], 9);
    float sc = (hC ? b1 : b0) + __shfl_xor_sync(~0u, hC ? b0 : b1, 18);
    float ex = exp2f(sc);
    float den = ex + __shfl_xor_sync(~0u, ex, 9);
    den += __shfl_xor_sync(~0u, den, 18);
    float al = __fdividef(ex, den + 1e-9f);
    sts32(alsm + (hA ? 4 + delta : delta) * 16 + (lane >> 3) * 4, pack2(al, al));
    __syncwarp();
}
__device__ __forceinline__ void attn_mix(const uint4* gv, unsigned al, unsigned oaddr) {
    const uint4 a = lds128(al);
    uint4 o;
    o.x = hfma2(a.w, gv[3].x, hfma2(a.z, gv[2].x, hfma2(a.y, gv[1].x, hmul2(a.x, gv[0].x))));
    o.y = hfma2(a.w, gv[3].y, hfma2(a.z, gv[2].y, hfma2(a.y, gv[1].y, hmul2(a.x, gv[0].y))));
    o.z = hfma2(a.w, gv[3].z, hfma2(a.z, gv[2].z, hfma2(a.y, gv[1].z, hmul2(a.x, gv[0].z))));
    o.w = hfma2(a.w, gv[3].w, hfma2(a.z, gv[2].w, hfma2(a.y, gv[1].w, hmul2(a.x, gv[0].w))));
    sts128(oaddr, o);
}
__device__ __forceinline__ void pack_acc(unsigned* pk, const float* d) {
#pragma unroll
    for (int j = 0; j < 20; j++) pk[j] = pack2(d[2 * j], d[2 * j + 1]);
}
__device__ __forceinline__ void acc_to_tile(const unsigned* pk, int w, int lane) {
    const unsigned a = sb + OFF_T + (w >> 2) * 10240 + (lane >> 4) * 1024 + (lane & 7) * 128 + (((2 * (w & 3) + ((lane >> 3) & 1)) ^ (lane & 7)) << 4);
#pragma unroll
    for (int j = 0; j < 5; j++)
        asm volatile("stmatrix.sync.aligned.m8n8.x4.trans.shared.b16 [%0],{%1,%2,%3,%4};" ::"r"(a + j * 2048), "r"(pk[4 * j]), "r"(pk[4 * j + 1]), "r"(pk[4 * j + 2]), "r"(pk[4 * j + 3]) : "memory");
}
__device__ __forceinline__ unsigned movm(unsigned a) { unsigned d; asm volatile("movmatrix.sync.aligned.m8n8.trans.b16 %0,%1;" : "=r"(d) : "r"(a)); return d; }
__device__ __forceinline__ void tma_load2d(unsigned dst, const CUtensorMap* tm, int c0, int c1, unsigned bar) {
    asm volatile("cp.async.bulk.tensor.2d.shared::cluster.global.mbarrier::complete_tx::bytes [%0],[%1,{%3,%4}],[%2];"
                 ::"r"(dst), "l"(tm), "r"(bar), "r"(c0), "r"(c1) : "memory");
}
__device__ __forceinline__ void tma_load3d(unsigned dst, const CUtensorMap* tm, int row, unsigned bar) {
    asm volatile("cp.async.bulk.tensor.3d.shared::cluster.global.mbarrier::complete_tx::bytes [%0],[%1,{%4,%3,%4}],[%2];"
                 ::"r"(dst), "l"(tm), "r"(bar), "r"(row), "r"(0) : "memory");
}
__device__ __forceinline__ void cp16(unsigned dst, const void* src) { asm volatile("cp.async.cg.shared.global [%0],[%1],16;" ::"r"(dst), "l"(src) : "memory"); }
__device__ __forceinline__ void cp_commit() { asm volatile("cp.async.commit_group;" ::: "memory"); }
template <int N> __device__ __forceinline__ void cp_wait() { asm volatile("cp.async.wait_group %0;" ::"n"(N) : "memory"); }
__device__ __forceinline__ void nb_sync_id(int id, int n) { asm volatile("bar.sync %0,%1;" ::"r"(id), "r"(n) : "memory"); }
__device__ __forceinline__ void nb_arrive_id(int id, int n) { asm volatile("bar.arrive %0,%1;" ::"r"(id), "r"(n) : "memory"); }
template <int ID, int N> __device__ __forceinline__ void nb_sync() { asm volatile("bar.sync %0,%1;" ::"n"(ID), "n"(N) : "memory"); }
template <int ID, int N> __device__ __forceinline__ void nb_arrive() { asm volatile("bar.arrive %0,%1;" ::"n"(ID), "n"(N) : "memory"); }
__device__ __forceinline__ void mbar_init(unsigned a, int n) { asm volatile("mbarrier.init.shared.b64 [%0],%1;" ::"r"(a), "r"(n) : "memory"); }
__device__ __forceinline__ void mbar_expect(unsigned a, int n) { asm volatile("mbarrier.arrive.expect_tx.shared.b64 _,[%0],%1;" ::"r"(a), "r"(n) : "memory"); }
__device__ __forceinline__ void mbar_arrive(unsigned a) { asm volatile("mbarrier.arrive.shared.b64 _,[%0];" ::"r"(a) : "memory"); }

constexpr unsigned PADBIN = 2560, CU = 0x101;
__device__ __forceinline__ uint4 bin_rank4(const uint4& e) {
    return make_uint4(atoms_add(sb + OFF_CNT2 + (e.x >> 16), CU), atoms_add(sb + OFF_CNT2 + (e.y >> 16), CU),
                      atoms_add(sb + OFF_CNT2 + (e.z >> 16), CU), atoms_add(sb + OFF_CNT2 + (e.w >> 16), CU));
}
__device__ __noinline__ void push_overflow(Scratch* sc, unsigned dst, unsigned src) {
    sc->ovf[blockIdx.x * OVCAP + atoms_inc(sb + OFF_MISC)] = (dst << 14) | src;
}
__device__ __noinline__ void bin_overflow4(Scratch* sc, uint4 v, uint4 h) {
    const unsigned e[4] = {v.x, v.y, v.z, v.w}, hh[4] = {h.x, h.y, h.z, h.w};
#pragma unroll
    for (int i = 0; i < 4; i++)
        if ((int)hh[i] >= (int)((LCAP + 16) * CU))
            push_overflow(sc, blockIdx.x * TILE + ((e[i] >> 21) & ~3u) + ((e[i] >> 18) & 3), ((e[i] & 2047) << 3) | ((e[i] >> 20) & 7));
}
__device__ __forceinline__ void bin_place4(Scratch* sc, const uint4& v, const uint4& r) {
    const unsigned e[4] = {v.x, v.y, v.z, v.w};
    unsigned h[4] = {r.x, r.y, r.z, r.w};
#pragma unroll
    for (int i = 0; i < 4; i++) h[i] += lds32(sb + OFF_CNT2 + (e[i] >> 16));
#pragma unroll
    for (int i = 0; i < 4; i++)
        asm volatile("{.reg .pred p; setp.lt.u32 p,%2,%3; @p st.shared.u16 [%0],%1;}"
                     ::"r"(sb + OFF_MAIL + bitsel(h[i] >> 1, e[i] >> 16, 0x318E)), "h"((unsigned short)e[i]), "r"(h[i]), "n"((LCAP + 16) * CU) : "memory");
    if (__builtin_expect(max(max((int)h[0], (int)h[1]), max((int)h[2], (int)h[3])) >= (int)((LCAP + 16) * CU), 0))
        bin_overflow4(sc, v, make_uint4(h[0], h[1], h[2], h[3]));
}

__global__ void __launch_bounds__(512, 1)
exphormer_kernel(const uint4* __restrict__ x, const uint4* __restrict__ dst4, const uint4* __restrict__ src4,
                 const uint4* __restrict__ wq, const uint4* __restrict__ wk, const int* __restrict__ esrc,
                 const int* __restrict__ edst, Scratch* __restrict__ sc, const uint4* __restrict__ dis, const uint4* __restrict__ wv,
                 const __grid_constant__ CUtensorMap tm_x, const __grid_constant__ CUtensorMap tm_wl, const __grid_constant__ CUtensorMap tm_wv,
                 const __grid_constant__ CUtensorMap tm_ot, const __grid_constant__ CUtensorMap tm_o256, const __grid_constant__ CUtensorMap tm_o16) {
    extern __shared__ __align__(1024) unsigned char smem_raw[];
    const unsigned tid = threadIdx.x, lane = tid & 31, g = lane >> 2, t = lane & 3;
    const unsigned b = blockIdx.x;
    const bool rowcta = b < NT;
    STAMP(0);

    auto load_xl = [&](int i) {
        mbar_expect(bar_full + 8 * i, 32768 + 10240);
        tma_load2d(sb + OFF_T + i * 10240, &tm_x, i * 64, b * TILE, bar_full + 8 * i);
        tma_load3d(sb + OFF_S + i * 32768, &tm_wl, i * 64, bar_full + 8 * i);
    };
    if (tid < 64) {
        if (tid < 32) {
            const unsigned t0 = clock();
            if (elect()) {
                asm volatile("prefetch.tensormap [%0];" ::"l"(&tm_x) : "memory");
                asm volatile("prefetch.tensormap [%0];" ::"l"(&tm_wl) : "memory");
                for (int i = 0; i < 12; i++) mbar_init(bar_full + 8 * i, i == 7 ? 4 : 1);
                mbar_init(bar_fill, 1); mbar_init(bar_t, 1); mbar_init(bar_mail, 1);
                for (int i = 0; i < 10; i++) mbar_init(bar_rd + 8 * i, 16);
                asm volatile("fence.mbarrier_init.release.cluster;" ::: "memory");
                if ((unsigned)__cvta_generic_to_shared(smem_raw) != sb) __trap();
            }
            __syncwarp();
            nb_arrive<3, 480>();
            if (rowcta && elect()) {
                while ((unsigned)clock() - t0 < XD0) {}
                load_xl(0);
                STAMPT(0, 41);
                while ((unsigned)clock() - t0 < XD1) {}
                load_xl(1);
                STAMPT(0, 40);
                if (XD2) { while ((unsigned)clock() - t0 < XD2 + 1) {} } else mbar_wait(bar_full);
                load_xl(2);
                STAMPT(0, 52);
                mbar_wait(bar_full + (XD2 ? 0 : 8)); load_xl(3);
                STAMPT(0, 53);
            }
            __syncwarp();
        } else {
            const uint4* ep = (const uint4*)esrc + (min(b, NT - 1u) * TILE + lane);
            cp16(sb + OFF_EIDX + lane * 16, ep); cp16(sb + OFF_EIDX + 512 + lane * 16, ep + 32);
            if (lane < 16) cp16(sb + OFF_EIDX + 1024 + lane * 16, ep + 64);
            if (lane < 10) cp16(sb + OFF_DIS + lane * 16, dis + (min(b, NT - 1u) * 10 + lane));
            cp_commit();
            if (lane == 0) {
                unsigned epoch;
                asm volatile("ld.relaxed.gpu.global.u32 %0,[%1];" : "=r"(epoch) : "l"(&sc->bar[1]) : "memory");
                sts32(sb + OFF_MISC + 16, 0);
                sts32(sb + OFF_MISC + 24, (epoch & ~(NCTA - 1)) + NCTA);
            }
            cp_wait<0>();
        }
    } else if (tid < 192) {
        const unsigned fw = b >> 3, hq = b & 7, q = (tid >> 5) - 2, cq = q * 8 + t, mt = tid - 64;
        const uint4* pa = wq + ((16 * fw + g) * 32 + cq);
        const uint4* pb = wk + ((32 * hq + 8 * (g >> 1) + (g & 1)) * 32 + cq);
        const unsigned ma = sb + OFF_S + 4 * 32768 + 8192 + mt * 16;
        cp16(ma, pa); cp16(ma + 2048, pa + 4); cp16(ma + 4096, pa + 256); cp16(ma + 6144, pa + 260);
#pragma unroll
        for (int u = 0; u < 8; u++) cp16(ma + 8192 + u * 2048, pb + (u >> 1) * 64 + (u & 1) * 4);
        cp_commit();
        const unsigned node = min(b * TILE + mt, NN - 1u);
        const uint4 xd = ldg_na((const uint4*)edst + node);
        float c[4][4];
        c[0][0] = c[0][1] = c[0][2] = c[0][3] = 0.f;
        uint4 va[4], vb[8];
        STAMPT(64, 38);
        cp_wait<0>();
        STAMPT(64, 39);
#pragma unroll
        for (int u = 0; u < 4; u++) va[u] = lds128(ma + u * 2048);
#pragma unroll
        for (int u = 0; u < 8; u++) vb[u] = lds128(ma + 8192 + u * 2048);
#pragma unroll
        for (int u = 0; u < 4; u++) {
            if (u) c[u][0] = c[u][1] = c[u][2] = c[u][3] = 0.f;
            mma16816(c[u], va[0].x, va[2].x, va[0].y, va[2].y, vb[2 * u].x, vb[2 * u].y);
            mma16816(c[u], va[0].z, va[2].z, va[0].w, va[2].w, vb[2 * u].z, vb[2 * u].w);
            mma16816(c[u], va[1].x, va[3].x, va[1].y, va[3].y, vb[2 * u + 1].x, vb[2 * u + 1].y);
            mma16816(c[u], va[1].z, va[3].z, va[1].w, va[3].w, vb[2 * u + 1].z, vb[2 * u + 1].w);
        }
        const unsigned ra = sb + OFF_S + 4 * 32768 + lane * 16;
#pragma unroll
        for (int hh = 0; hh < 2; hh++) {
            sts128(ra + q * 2048 + hh * 1024, make_uint4(__float_as_uint(c[0][2 * hh]), __float_as_uint(c[0][2 * hh + 1]), __float_as_uint(c[1][2 * hh]), __float_as_uint(c[1][2 * hh + 1])));
            sts128(ra + q * 2048 + hh * 1024 + 512, make_uint4(__float_as_uint(c[2][2 * hh]), __float_as_uint(c[2][2 * hh + 1]), __float_as_uint(c[3][2 * hh]), __float_as_uint(c[3][2 * hh + 1])));
        }
        STAMPT(64, 42);
        unsigned bad;
        asm volatile("{.reg .pred p; setp.ne.u32 p,%1,0; bar.red.popc.u32 %0,1,128,p;}" : "=r"(bad) : "r"((xd.x ^ node) | (xd.y ^ node) | (xd.z ^ node) | (xd.w ^ node)) : "memory");
        if (q < 2) {
            float m[8] = {0, 0, 0, 0, 0, 0, 0, 0};
#pragma unroll
            for (int i = 0; i < 4; i++) {
                uint4 u = lds128(ra + i * 2048 + q * 1024), v = lds128(ra + i * 2048 + q * 1024 + 512);
                m[0] += __uint_as_float(u.x); m[1] += __uint_as_float(u.y); m[2] += __uint_as_float(u.z); m[3] += __uint_as_float(u.w);
                m[4] += __uint_as_float(v.x); m[5] += __uint_as_float(v.y); m[6] += __uint_as_float(v.z); m[7] += __uint_as_float(v.w);
            }
            const float k = 0.0625f * 1.4426950408889634f;
            sc->mimg[(fw >> 2) * 2048 + (hq >> 1) * 512 + (16 * (fw & 3) + 8 * q + g) * 8 + (((hq & 1) * 4 + t) ^ g)] =
                make_uint4(pack2(m[0] * k, m[1] * k), pack2(m[2] * k, m[3] * k), pack2(m[4] * k, m[5] * k), pack2(m[6] * k, m[7] * k));
            STAMPT(64, 43);
            nb_arrive<2, 384>();
        } else if (mt == 127) {
            sts32(sb + OFF_MISC + 20, bad);
        }
    } else {
        if (rowcta) {
            const unsigned bt = tid - 192;
            const uint4 ed = __ldg(dst4 + (b * 320 + bt)), es = __ldg(src4 + (b * 320 + bt));
            const unsigned pad = (PADBIN + 4 * ((bt & 3) + ((b * 4) & 28))) << 16;
#pragma unroll
            for (int k = 0; k < 4; k++) if (k < 3 || bt < 40) sts128(sb + OFF_MAIL + (bt + k * 320) * 16, make_uint4(pad, pad, pad, pad));
            const unsigned cz = bt < (512 + PADBIN) / 16 ? 0 : 0x40000000;
            if (bt < (512 + 2688) / 16) sts128(sb + OFF_CNT1 + bt * 16, make_uint4(cz, cz, cz, cz));
            if (bt == 319) sts32(sb + OFF_MISC, 0);
            unsigned z;
            asm volatile("{.reg .pred p; setp.eq.u32 p,%1,0xFFFFFFFF; bar.red.popc.u32 %0,4,320,p;}" : "=r"(z) : "r"(bt) : "memory");
            const unsigned dd[4] = {ed.x + z, ed.y + z, ed.z + z, ed.w + z}, ss[4] = {es.x + z, es.y + z, es.z + z, es.w + z};
            unsigned rk[4], ow[4];
#pragma unroll
            for (int i = 0; i < 4; i++) { ow[i] = dd[i] / TILE; rk[i] = atoms_inc(sb + OFF_CNT1 + ow[i] * 4); }
#pragma unroll
            for (int i = 0; i < 4; i++) {
                const unsigned dl = dd[i] - ow[i] * TILE;
                const unsigned e = bitsel(ss[i] << 20, bitsel(dl << 21, dl << 18, 0xFF800000u), 0x00700000u) + (ss[i] >> 3);
                asm volatile("{.reg .pred p; setp.lt.u32 p,%2,%3; @p st.shared.u32 [%0],%1;}" ::"r"(sb + OFF_MAIL + (ow[i] * CELL + rk[i]) * 4), "r"(e), "r"(rk[i]), "n"(CELL) : "memory");
            }
            if (__builtin_expect((rk[0] | rk[1] | rk[2] | rk[3]) >= CELL, 0)) {
#pragma unroll
                for (int i = 0; i < 4; i++) if (rk[i] >= CELL) push_overflow(sc, dd[i], ss[i]);
            }
            STAMPT(416, 44);
            nb_sync<4, 320>();
            uint4 mv[4];
            uint4* mp = sc->mail + ((bt >> 3) * 1024 + (bt & 4) * 128 + b * 4 + (bt & 3));
#pragma unroll
            for (int k = 0; k < 4; k++) if (k < 3 || bt < 40) mv[k] = lds128(sb + OFF_MAIL + (bt + k * 320) * 16);
            fence_async_smem();
#pragma unroll
            for (int k = 0; k < 4; k++) if (k < 3 || bt < 40) mp[k * 40960] = mv[k];
        }
        STAMPT(416, 45);
        if (tid >= 480) {
            nb_sync<2, 384>();
            if (lane == 0) bar_arrive(&sc->bar[0]);
            __syncwarp();
            STAMPT(480, 47);
        } else {
            nb_arrive<2, 384>();
        }
    }
    const int w = __shfl_sync(~0u, tid >> 5, 0), wg = w >> 2;
    auto fill_piece = [&](int off, int bytes) {
        const int n = min(bytes, NN * 16 - off);
        if (n > 0) bulk_g2s(sb + OFF_S + off, (const char*)(sc->hs + (b >> 2) * NN) + off, n, bar_fill);
    };
    const int slice = b >> 2, range = b & 3;
    const int g0 = (range * NG) >> 2, g1 = ((range + 1) * NG) >> 2;
    const int grp0 = g0 + w;
    const uint4* lp = sc->lists + (grp0 * 96 + lane);
    uint4 L0, L1;
    if (w > 0 && w < 15) nb_sync<3, 480>();
    if (w == 14) nb_arrive<5, 64>();
    if (w == 1) nb_arrive<6, 64>();
    if (w == 15) nb_sync<5, 64>();
    if (w == 0) nb_sync<6, 64>();

    if (__builtin_expect(rowcta, 1)) {
        const unsigned descA = 0x10000u + (sb + OFF_S) / 16 + wg * 512;
        const unsigned greg = sb + OFF_S + w * 2048 + lane * 16;
        const uint4* xl = x + lane;
        float d[40];
        unsigned pk[20];
        unsigned* hp = (unsigned*)(sc->hs + (2 * w * NN + b * TILE)) + lane;
        auto mma_q = [&](int Q, int slot, int st) {
            if (st < 0) wg_fence();
#pragma unroll
            for (int k = 0; k < 4; k++) {
                if (st >= 0) wg_fence();
                wg80(d, descA + slot * 2048 + k * 128, 0x10000u + (sb + OFF_T) / 16 + (Q & 3) * 640 + k * 2, ((Q & 3) | k) != 0);
                if (st >= 0) {
#pragma unroll
                    for (int j = st + 2 * k; j < st + 2 * k + 2; j++)
                        if (j < 20) asm volatile("st.global.u32 [%0],%1;" ::"l"(hp + (j >> 1) * 32 + (j & 1) * (NN * 4)), "r"(pk[j]) : "memory");
                }
            }
            wg_commit();
        };
        auto eidx = [&](int i) { return lds128(sb + OFF_EIDX + (w * 5 + i) * 16); };
        auto gather = [&](const uint4& ix, int slot) {
            cp16(greg + slot * 32768, xl + ix.x * 32u); cp16(greg + slot * 32768 + 512, xl + ix.y * 32u);
            cp16(greg + slot * 32768 + 1024, xl + ix.z * 32u); cp16(greg + slot * 32768 + 1536, xl + ix.w * 32u);
            cp_commit();
        };
        uint4 gv[5][4];
        auto to_regs = [&](int i, int slot) {
#pragma unroll
            for (int j = 0; j < 4; j++) gv[i][j] = lds128(greg + slot * 32768 + j * 512);
        };
        auto load_m = [&](int i, int slot) {
            mbar_expect(bar_full + 32 + 8 * i, 32768);
            bulk_g2s(sb + OFF_S + slot * 32768, sc->mimg + i * 2048, 32768, bar_full + 32 + 8 * i);
        };
        auto load_v = [&](int i, int slot) {
            mbar_expect(bar_full + 64 + 8 * i, 32768);
            tma_load3d(sb + OFF_S + slot * 32768, &tm_wv, i * 64, bar_full + 64 + 8 * i);
        };
        float ds[20];
#pragma unroll
        for (int j = 0; j < 10; j++) { const unsigned v = lds32(sb + OFF_DIS + (4 * j + t) * 4); ds[2 * j] = blo_v(v); ds[2 * j + 1] = bhi_v(v); }
        uint4 ix = eidx(0);
        const uint4 ix1 = eidx(1);
        STAMPT(288, 2);
        mbar_wait(bar_full);
        STAMPT(288, 3);
        mma_q(0, 0, -1);
        mbar_wait(bar_full + 8);
        STAMPT(288, 50);
        gather(ix, 4);
        mma_q(1, 1, -1);
        mbar_wait(bar_full + 16);
        STAMPT(288, 51);
        mma_q(2, 2, -1);
        wg_wait<0>();
        STAMPT(288, 4); STAMP(14); STAMP2(15);
        __syncthreads();
        if (w == 8 && elect()) {
            bar_poll(&sc->bar[0], lds32(sb + OFF_MISC + 24));
            STAMPT(256, 48);
            fence_async_gmem();
            mbar_expect(bar_mail, 16384);
            bulk_g2s(sb + OFF_MAIL, sc->mail + b * 1024, 16384, bar_mail);
            load_m(0, 0);
            load_m(1, 1);
        }
        __syncwarp();
        mbar_wait(bar_full + 24);
        STAMP(5);
        gather(ix1, 2);
        mma_q(3, 3, -1);
        wg_wait<0>();
        STAMP(6);
#pragma unroll
        for (int j = 0; j < 20; j++) pk[j] = movm(pack2(d[2 * j] * ds[2 * (j >> 1)], d[2 * j + 1] * ds[2 * (j >> 1) + 1]));
        cp_wait<1>();
        to_regs(0, 4);
        uint4 e0, e1, r0, r1;
        mbar_wait(bar_mail);
        e0 = lds128(sb + OFF_MAIL + tid * 16); e1 = lds128(sb + OFF_MAIL + 8192 + tid * 16);
        if (tid >= 500) { const unsigned pad = (PADBIN + 4 * lane) << 16; e0 = e1 = make_uint4(pad, pad, pad, pad); }
        r0 = bin_rank4(e0);
        const bool more = __any_sync(~0u, e1.x < (PADBIN << 16));
        if (more) r1 = bin_rank4(e1);
        ix = eidx(2);
        const uint4 ix3 = eidx(3), ix4 = eidx(4);
        __syncthreads();
        STAMP(7);
        if (w == 8 && elect()) load_m(2, 3);
        __syncwarp();
        const unsigned ia = sb + OFF_MAIL + (w % 3) * 4096 + (w / 3) * 512 + lane * 16;
        if (w < 15) sts128(ia, make_uint4(DUMMY2, DUMMY2, DUMMY2, DUMMY2));
        unsigned hdr = 0, dpair = 0;
        if (w >= 11) {
            const int G = w - 11;
            const unsigned ca = sb + OFF_CNT2 + G * 512 + lane * 16;
            uint4 c = lds128(ca);
            const unsigned dp = hmul2(lds32(sb + OFF_DIS + (G * 8 + g) * 4), 0x43004300u);
            const bool sw = lane >= 16;
            unsigned s1 = sw ? c.y : c.x, s2 = c.x + c.y, s3 = s2 + (sw ? c.w : c.z), tot = s2 + c.z + c.w, inc = tot;
            unsigned u = __shfl_up_sync(~0u, inc, 8); if (lane >= 8) inc += u;
            u = __shfl_up_sync(~0u, inc, 16); if (sw) inc += u;
            const unsigned base = inc - tot;
            const unsigned p0 = min(base, LCAP * CU), p1 = min(base + s1, LCAP * CU), p2 = min(base + s2, LCAP * CU), p3 = min(base + s3, LCAP * CU);
            sts128(ca, make_uint4((sw ? p1 : p0) + 16 * CU, (sw ? p0 : p1) + 16 * CU, (sw ? p3 : p2) + 16 * CU, (sw ? p2 : p3) + 16 * CU));
            const unsigned word = __byte_perm(__byte_perm(p0, p1, 0x0040), __byte_perm(p2, p3, 0x0040), 0x5410);
            const unsigned wa = __shfl_sync(~0u, word, (g >> 1) * 8 + 2 * t), wb = __shfl_sync(~0u, word, (g >> 1) * 8 + 2 * t + 1);
            hdr = __byte_perm(wa, wb, (g & 1) ? 0x7362 : 0x5140);
            if (__any_sync(~0u, inc > 48 * CU)) hdr |= 0x80;
            dpair = __byte_perm(dp, dp, sw ? 0x1032 : 0x3210);
        }
        mbar_wait(bar_full + 32); mbar_wait(bar_full + 40);
        gather(ix, 4);
        STAMP(21);
        mma_q(4, 0, 0); mma_q(5, 1, 8);
        wg_wait<1>();
        nb_sync_id(8 + wg, 128);
        if ((w & 3) == 0 && elect()) {
            fence_async_gmem();
            mbar_expect(bar_full + 56, 8192);
            bulk_g2s(sb + OFF_S + wg * 8192, sc->mimg + (3 * 2048 + wg * 512), 8192, bar_full + 56);
        }
        __syncwarp();
        mbar_wait(bar_full + 48);
        mma_q(6, 3, 16);
        wg_wait<1>();
        nb_sync_id(8 + wg, 128);
        gather(ix3, 1);
        mbar_wait(bar_full + 56);
        mma_q(7, 0, -1);
        wg_wait<1>();
        __syncthreads();
        gather(ix4, 3);
        wg_wait<0>();
        STAMP(20);
        if (w >= 11) asm volatile("st.shared.v2.u32 [%0],{%1,%2};" ::"r"(sb + OFF_MAIL + (w - 11) * 512 + lane * 16), "r"(hdr), "r"(dpair) : "memory");
        bin_place4(sc, e0, r0);
        if (more) bin_place4(sc, e1, r1);
        pack_acc(pk, d);
        __syncthreads();
        if (w == 15 && elect()) load_v(0, 0);
        __syncwarp();
        acc_to_tile(pk, w, lane);
        if (w < 15) sc->lists[b * 480 + tid] = lds128(ia);
        __syncthreads();
        STAMP(8);
        cp_wait<2>();
        to_regs(1, 2); to_regs(2, 4);
        if (w != 8) nb_arrive<2, 512>();
        if (w == 15 && elect()) {
            const unsigned novf = lds32(sb + OFF_MISC), bad = lds32(sb + OFF_MISC + 20);
            sc->ovfn[b] = novf;
            if (__builtin_expect(novf | bad, 0)) raise_flag(&sc->bar[5], lds32(sb + OFF_MISC + 24), (novf ? 1 : 0) | (bad ? 2 : 0));
            bar_arrive(&sc->bar[4]);
        }
        __syncwarp();
        {
            const unsigned delta = t ^ (g >> 1), alsm = sb + OFF_ALPHA + w * 128;
            const bool par = g & 1;
            const int n0 = w * 5;
            float v[4], u[4];
            attn_scores(v, true, par, gv[0], tile_addr(n0, lane));
            attn_scores(v, delta == 1, par, gv[1], tile_addr(n0 + 1, lane ^ 8));
            attn_scores(v, delta == 2, par, gv[2], tile_addr(n0 + 2, lane ^ 16));
            if (w == 8) {
                nb_sync<2, 512>();
                if (elect()) { fence_async_smem(); load_v(1, 4); load_v(2, 2); }
                __syncwarp();
            }
            cp_wait<1>();
            to_regs(3, 1);
            attn_scores(v, delta == 3, par, gv[3], tile_addr(n0 + 3, lane ^ 24));
            cp_wait<0>();
            to_regs(4, 3);
            attn_scores(u, true, par, gv[4], tile_addr(n0 + 4, lane));
            attn_softmax(v, u, lane, delta, alsm);
#pragma unroll
            for (int i = 0; i < 5; i++) attn_mix(gv[i], alsm + i * 16, tile_addr(n0 + i, lane));
        }
        mbar_wait(bar_full + 64);
        fence_async_smem();
        STAMP(22);
        if (tid == 0) {
            sts32(sb + OFF_MISC + 28, bar_poll2(&sc->bar[4], lds32(sb + OFF_MISC + 24)));
            mbar_expect(bar_fill, NN * 16);
        }
        __syncthreads();
        STAMP(9);
        if (w == 13 && elect()) load_v(3, 1);
        if (w == 14 && elect()) { fence_async_gmem(); fill_piece(3 * 32768, 32768); }
        __syncwarp();
        L0 = ldg_na(lp); L1 = ldg_na(lp + 32);
        mma_q(8, 0, -1);
        mbar_wait(bar_full + 72);
        mma_q(9, 4, -1);
        wg_wait<1>();
        nb_sync_id(8 + wg, 128);
        if ((w & 3) == 0 && elect()) { fence_async_gmem(); fill_piece(wg * 8192, 8192); }
        __syncwarp();
        mbar_wait(bar_full + 80);
        mma_q(10, 2, -1);
        wg_wait<1>();
        nb_sync_id(8 + wg, 128);
        if ((w & 3) == 0 && elect()) fill_piece(4 * 32768 + wg * 8192, 8192);
        if (w == 15 && lane < 8) sts128(sb + OFF_S + NN * 16 + lane * 16, make_uint4(0, 0, 0, 0));
        __syncwarp();
        mbar_wait(bar_full + 88);
        mma_q(11, 1, -1);
        wg_wait<1>();
        nb_sync_id(8 + wg, 128);
        if ((w & 3) == 0 && elect()) fill_piece(2 * 32768 + wg * 8192, 8192);
        __syncwarp();
        wg_wait<0>();
        pack_acc(pk, d);
        __syncthreads();
        STAMP(10);
        if ((w & 3) == 0 && elect()) fill_piece(32768 + wg * 8192, 8192);
        __syncwarp();
        if (__builtin_expect(lds32(sb + OFF_MISC + 28) & 2, 0)) {
            for (int i = 0; i < 5; i++) sts128(tile_addr(w * 5 + i, lane), attn_generic(b * TILE + w * 5 + i, x, esrc, edst, wq, wk, wv));
        } else {
            acc_to_tile(pk, w, lane);
        }
        fence_async_smem();
    } else {
        if (tid == 0) {
            bar_arrive(&sc->bar[4]);
            sts32(sb + OFF_MISC + 28, bar_poll2(&sc->bar[4], lds32(sb + OFF_MISC + 24)));
            mbar_expect(bar_fill, NN * 16);
        }
        __syncthreads();
        if (lane == 0) { fence_async_gmem(); fence_async_smem(); fill_piece(w * 10000, 10000); }
        if (w == 15 && lane < 8) sts128(sb + OFF_S + NN * 16 + lane * 16, make_uint4(0, 0, 0, 0));
        L0 = ldg_na(lp); L1 = ldg_na(lp + 32);
    }

    const int cnt = (g1 - grp0 + 15) >> 4;
    const bool anyovf = lds32(sb + OFF_MISC + 28) & 1;
    __syncthreads();
    if (tid == 15 * 32) {
        if (rowcta) {
#pragma unroll
            for (int kb = 0; kb < 4; kb++)
                asm volatile("cp.async.bulk.tensor.2d.global.shared::cta.bulk_group [%0,{%2,%3}],[%1];"
                             ::"l"(&tm_ot), "r"(sb + OFF_T + kb * 10240), "r"(kb * 64), "r"(b * TILE) : "memory");
            asm volatile("cp.async.bulk.commit_group;" ::: "memory");
            asm volatile("cp.async.bulk.wait_group 0;" ::: "memory");
            fence_async_gmem();
        }
        bar_arrive(&sc->bar[1]);
        asm volatile("mbarrier.arrive.shared.b64 _,[%0];" ::"r"(bar_t) : "memory");
    }
    __syncwarp();
    const int flush_it = (w < 8) ? w + 1 : (w == 14 ? 8 : 31);
    unsigned special = (1u << 5) | (1u << 9) | (1u << flush_it);
    mbar_wait(bar_fill);
    STAMP(11);
    const unsigned lb = sb + OFF_S + (lane & 7) * 16;
    const unsigned dummy = anyovf ? 0 : lb + 1250 * 128;
    const float zmask = (lane >= 28) ? 0.f : -1.f;
    unsigned stg = sb + OFF_STG + w * 256 + (((lane & 7) * 2 + ((lane >> 3) & 1)) ^ ((lane >> 2) & 1)) * 16;
    unsigned rdb = bar_rd;
    for (int it = 0; it < cnt; it++) {
        unsigned ad[12];
        ad[0] = dp2lo(L0.z, lb); ad[1] = dp2hi(L0.z, lb); ad[2] = dp2lo(L0.w, lb); ad[3] = dp2hi(L0.w, lb);
        ad[4] = dp2lo(L1.x, lb); ad[5] = dp2hi(L1.x, lb); ad[6] = dp2lo(L1.y, lb); ad[7] = dp2hi(L1.y, lb);
        ad[8] = dp2lo(L1.z, lb); ad[9] = dp2hi(L1.z, lb); ad[10] = dp2lo(L1.w, lb); ad[11] = dp2hi(L1.w, lb);
        unsigned sA = __byte_perm(L0.x, 0x64646464u, 0x4140), nB = __byte_perm(L0.x, 0xE4E4E4E4u, 0x4342);
        float dA = blo_v(L0.y), dB = bhi_v(L0.y);
        lp += 16 * 96;
        L0 = ldg_na(lp); L1 = ldg_na(lp + 32);
        float acc0[4] = {0, 0, 0, 0}, acc1[4] = {0, 0, 0, 0};
        if (!__any_sync(~0u, ad[10] != dummy)) {
            if (__any_sync(~0u, ad[9] != dummy)) p3_steps<10>(acc0, acc1, ad, sA, nB);
            else p3_steps<9>(acc0, acc1, ad, sA, nB);
        } else if (!__any_sync(~0u, ad[11] != dummy)) {
            p3_steps<11>(acc0, acc1, ad, sA, nB);
        } else {
            const bool longer = (sA & 0x80) || anyovf;
            sA &= ~0x80u;
            p3_steps<12>(acc0, acc1, ad, sA, nB);
            if (__any_sync(~0u, longer)) {
                uint4 C2 = ldg_na(lp - 16 * 96 + 64);
                unsigned e2[4] = {C2.x, C2.y, C2.z, C2.w};
#pragma unroll
                for (int s = 12; s < 20; s++) p3_step(acc0, acc1, (s & 1) ? dp2hi(e2[(s - 12) >> 1], lb) : dp2lo(e2[(s - 12) >> 1], lb), s, sA, nB);
                if (anyovf) {
                    float4 e = p3_overflow(sc, grp0 + 16 * it, sb + OFF_S);
                    float s0 = e.x + e.z, s1 = e.y + e.w;
                    for (int k = 4; k < 32; k <<= 1) {
                        float u0 = __shfl_down_sync(~0u, s0, k), u1 = __shfl_down_sync(~0u, s1, k);
                        if (lane + k < 32) { s0 += u0; s1 += u1; }
                    }
                    acc0[0] += s0; acc0[1] += s1; acc0[2] += s0 - e.x; acc0[3] += s1 - e.y;
                }
            }
        }
        float c0 = acc0[0] + acc1[0], c1 = acc0[1] + acc1[1], c2 = acc0[2] + acc1[2], c3 = acc0[3] + acc1[3];
        float n0 = __shfl_down_sync(~0u, c0, 4), n1 = __shfl_down_sync(~0u, c1, 4);
        float o0 = c0 - c2, o1 = c1 - c3, o2 = fmaf(n0, zmask, c2), o3 = fmaf(n1, zmask, c3);
        asm volatile("stmatrix.sync.aligned.m8n8.x2.shared.b16 [%0],{%1,%2};" ::"r"(stg), "r"(pack2(o0 * dA, o1 * dA)), "r"(pack2(o2 * dB, o3 * dB)) : "memory");
        __syncwarp();
        asm volatile("{.reg .pred p; setp.eq.u32 p,%1,0; @p mbarrier.arrive.shared.b64 _,[%0];}" ::"r"(rdb), "r"(lane) : "memory");
        if (special & 1) {
            if (it == 5) mbar_wait(bar_t);
            if (lane == 0 && (it == 9 || it == flush_it)) {
                const int r = (w < 8) ? w : 8;
                if (it != 9) mbar_wait(bar_rd + 8 * r);
                if (!lds32(sb + OFF_MISC + 16)) { bar_poll(&sc->bar[1], lds32(sb + OFF_MISC + 24)); sts32(sb + OFF_MISC + 16, 1); }
                fence_async_gmem();
                fence_async_smem();
                if (it != 9)
                    asm volatile("cp.reduce.async.bulk.tensor.2d.global.shared::cta.add.tile.bulk_group [%0,{%2,%3}],[%1];"
                                 ::"l"(&tm_o256), "r"(sb + OFF_STG + r * 4096), "r"(slice * 8), "r"((g0 + 16 * r) * 16) : "memory");
                else
                    asm volatile("cp.reduce.async.bulk.tensor.2d.global.shared::cta.add.tile.bulk_group [%0,{%2,%3}],[%1];"
                                 ::"l"(&tm_o16), "r"(stg), "r"(slice * 8), "r"((grp0 + 144) * 16) : "memory");
            }
            __syncwarp();
        }
        special >>= 1;
        stg += 4096;
        rdb += 8;
    }
    STAMP(12);
    if (lane == 0) {
        asm volatile("cp.async.bulk.commit_group;" ::: "memory");
        asm volatile("cp.async.bulk.wait_group.read 0;" ::: "memory");
    }
    STAMP(13);
}

typedef CUresult (*EncodeFn)(CUtensorMap*, CUtensorMapDataType, cuuint32_t, void*, const cuuint64_t*, const cuuint64_t*,
                             const cuuint32_t*, const cuuint32_t*, CUtensorMapInterleave, CUtensorMapSwizzle,
                             CUtensorMapL2promotion, CUtensorMapFloatOOBfill);

}

extern "C" void kernel_launch(void* const* d_in, const int* in_sizes, int n_in, void* d_out, int out_size) {
    (void)in_sizes; (void)n_in; (void)out_size;
    static EncodeFn enc = nullptr;
    static void* scratch = nullptr;
    if (!enc) {
        cudaGetSymbolAddress(&scratch, g_scratch);
        void* fn = nullptr;
        cudaDriverEntryPointQueryResult qr;
        cudaGetDriverEntryPoint("cuTensorMapEncodeTiled", &fn, cudaEnableDefault, &qr);
        enc = (EncodeFn)fn;
        cudaFuncSetAttribute(exphormer_kernel, cudaFuncAttributeMaxDynamicSharedMemorySize, SMEM_BYTES + PROF_EXTRA);
    }
    CUtensorMap tm_x, tm_wl, tm_wv, tm_ot, tm_o256, tm_o16;
    auto mk = [&](CUtensorMap* tm, void* p, int rows, int bc, int br, CUtensorMapSwizzle sw, CUtensorMapL2promotion pr) {
        cuuint64_t gd[2] = {256, (cuuint64_t)rows}, gs[1] = {512};
        cuuint32_t es[2] = {1, 1}, bx[2] = {(cuuint32_t)bc, (cuuint32_t)br};
        enc(tm, CU_TENSOR_MAP_DATA_TYPE_BFLOAT16, 2, p, gd, gs, bx, es, CU_TENSOR_MAP_INTERLEAVE_NONE, sw, pr, CU_TENSOR_MAP_FLOAT_OOB_FILL_NONE);
    };
    for (int i = 0; i < 2; i++) {
        cuuint64_t gd[3] = {64, 256, 4}, gs[2] = {512, 128};
        cuuint32_t es[3] = {1, 1, 1}, bx[3] = {64, 64, 4};
        enc(i ? &tm_wv : &tm_wl, CU_TENSOR_MAP_DATA_TYPE_BFLOAT16, 3, d_in[i ? 9 : 6], gd, gs, bx, es, CU_TENSOR_MAP_INTERLEAVE_NONE,
            CU_TENSOR_MAP_SWIZZLE_128B, CU_TENSOR_MAP_L2_PROMOTION_L2_128B, CU_TENSOR_MAP_FLOAT_OOB_FILL_NONE);
    }
    mk(&tm_x, d_in[0], NN, 64, TILE, CU_TENSOR_MAP_SWIZZLE_128B, CU_TENSOR_MAP_L2_PROMOTION_L2_128B);
    mk(&tm_ot, d_out, NN, 64, TILE, CU_TENSOR_MAP_SWIZZLE_128B, CU_TENSOR_MAP_L2_PROMOTION_NONE);
    mk(&tm_o256, d_out, NN, 8, 256, CU_TENSOR_MAP_SWIZZLE_NONE, CU_TENSOR_MAP_L2_PROMOTION_NONE);
    mk(&tm_o16, d_out, NN, 8, 16, CU_TENSOR_MAP_SWIZZLE_NONE, CU_TENSOR_MAP_L2_PROMOTION_NONE);
    exphormer_kernel<<<NCTA, 512, SMEM_BYTES + PROF_EXTRA>>>(
        (const uint4*)d_in[0], (const uint4*)d_in[2], (const uint4*)d_in[1], (const uint4*)d_in[7], (const uint4*)d_in[8], (const int*)d_in[3],
        (const int*)d_in[4], (Scratch*)scratch, (const uint4*)d_in[5], (const uint4*)d_in[9],
        tm_x, tm_wl, tm_wv, tm_ot, tm_o256, tm_o16);
}
```

```cpp
#include <cuda_runtime.h>
#include <cuda_bf16.h>
#include <cuda.h>
#include <stdint.h>

namespace {

constexpr int NN = 10000, NE = 160000, NEE = 40000;
constexpr int TILE = 80, NT = 125, NCTA = 128, NG = 625, EPC = 1280;
constexpr int CELL = 32;
constexpr int LCAP = 80;
constexpr int OVCAP = EPC + NT * CELL;
#define XD0 600
#define XD1 1200
#define XD2 0
constexpr unsigned DUMMY2 = 1250u | (1250u << 16);

constexpr unsigned sb = 1024;
constexpr int OFF_S = 0;
constexpr int OFF_R = 163840;
constexpr int OFF_BAR = OFF_R;
constexpr int OFF_MISC = OFF_R + 256;
constexpr int OFF_DIS = OFF_R + 320;
constexpr int OFF_PROF = OFF_R + 512;
constexpr int OFF_EIDX = OFF_R + 1024;
constexpr int OFF_ALPHA = OFF_R + 1024;
constexpr int OFF_STG = OFF_R + 2048;
constexpr int OFF_CNT1 = OFF_R + 2560;
constexpr int OFF_CNT2 = OFF_R + 3072;
constexpr int OFF_MAIL = OFF_R + 5760;
constexpr int OFF_IMG = OFF_MAIL + 9216;
constexpr int OFF_T = OFF_R + 26624;
constexpr int SMEM_BYTES = OFF_T + 40960;
static_assert(SMEM_BYTES <= 232448 && OFF_T % 1024 == 0 && OFF_STG + 6 * 4096 == OFF_T && OFF_IMG + 10752 <= OFF_T, "smem");
constexpr unsigned bar_fill = sb + OFF_BAR, bar_t = bar_fill + 8, bar_mail = bar_fill + 16, bar_c = bar_fill + 24, bar_rd = bar_fill + 32,
                   bar_full = bar_fill + 128;
constexpr int LSTR = (NG + 16) * 32;

struct __align__(256) Scratch {
    uint4 mimg[8192];
    uint4 hs[32 * NN];
    uint4 mail[NT * 1024];
    uint4 lists[3 * LSTR];
    unsigned ovfn[NCTA];
    unsigned bar[32];
    unsigned ovf[NCTA * OVCAP];
};
__device__ Scratch g_scratch;
#define STAMPT(th, i)
#define STAMP(i) STAMPT(64, i)
#define STAMP2(i) STAMPT(416, i)

__device__ __forceinline__ void bar_arrive(unsigned* p) {
    asm volatile("red.release.gpu.global.add.u32 [%0],1;" ::"l"(p) : "memory");
}
__device__ __forceinline__ void bar_poll(const unsigned* p, unsigned target) {
    unsigned v;
    int lim = 0;
    do {
        asm volatile("ld.acquire.gpu.global.u32 %0,[%1];" : "=r"(v) : "l"(p) : "memory");
        if (++lim > (1 << 22)) __trap();
    } while ((int)(v - target) < 0);
}
__device__ __forceinline__ unsigned bar_poll2(const unsigned* p, unsigned target) {
    unsigned long long v;
    int lim = 0;
    do {
        asm volatile("ld.acquire.gpu.global.u64 %0,[%1];" : "=l"(v) : "l"(p) : "memory");
        if (++lim > (1 << 22)) __trap();
    } while ((int)((unsigned)v - target) < 0);
    unsigned f = (unsigned)(v >> 32);
    return (f & ~3u) == target ? f & 3 : 0;
}
__device__ __noinline__ void raise_flag(unsigned* p, unsigned target, unsigned bit) {
    unsigned old = atomicCAS(p, 0, 0), seen;
    do {
        seen = old;
        old = atomicCAS(p, seen, ((seen & ~3u) == target ? seen : target) | bit);
    } while (old != seen);
}
__device__ __forceinline__ void mbar_wait(unsigned a) {
    asm volatile("{.reg .pred p; .reg .u32 n;\n"
                 "mov.u32 n,0x400000;\n"
                 "W: mbarrier.try_wait.parity.shared.b64 p,[%0],0;\n"
                 "add.u32 n,n,-1; setp.ne.and.u32 p,n,0,!p; @p bra W;}" ::"r"(a) : "memory");
}
__device__ __forceinline__ bool elect() {
    unsigned r;
    asm volatile("{.reg .pred p; elect.sync _|p,0xFFFFFFFF; selp.u32 %0,1,0,p;}" : "=r"(r));
    return r;
}
__device__ __forceinline__ uint4 ldg_na(const uint4* p) {
    uint4 v;
    asm volatile("ld.global.L1::no_allocate.v4.u32 {%0,%1,%2,%3},[%4];" : "=r"(v.x), "=r"(v.y), "=r"(v.z), "=r"(v.w) : "l"(p) : "memory");
    return v;
}
__device__ __forceinline__ uint4 lds128(unsigned a) {
    uint4 v;
    asm volatile("ld.shared.v4.u32 {%0,%1,%2,%3},[%4];" : "=r"(v.x), "=r"(v.y), "=r"(v.z), "=r"(v.w) : "r"(a) : "memory");
    return v;
}
__device__ __forceinline__ void sts128(unsigned a, uint4 v) {
    asm volatile("st.shared.v4.u32 [%0],{%1,%2,%3,%4};" ::"r"(a), "r"(v.x), "r"(v.y), "r"(v.z), "r"(v.w) : "memory");
}
__device__ __forceinline__ void sts32(unsigned a, unsigned v) { asm volatile("st.shared.u32 [%0],%1;" ::"r"(a), "r"(v) : "memory"); }
__device__ __forceinline__ unsigned lds32(unsigned a) { unsigned v; asm volatile("ld.shared.u32 %0,[%1];" : "=r"(v) : "r"(a) : "memory"); return v; }
__device__ __forceinline__ unsigned atoms_add(unsigned a, unsigned k) { unsigned v; asm volatile("atom.shared.add.u32 %0,[%1],%2;" : "=r"(v) : "r"(a), "r"(k) : "memory"); return v; }
__device__ __forceinline__ unsigned bitsel(unsigned a, unsigned b, unsigned m) { unsigned r; asm("lop3.b32 %0,%1,%2,%3,0xE4;" : "=r"(r) : "r"(a), "r"(b), "r"(m)); return r; }
__device__ __forceinline__ unsigned atoms_inc(unsigned a) { unsigned v; asm volatile("atom.shared.add.u32 %0,[%1],1;" : "=r"(v) : "r"(a) : "memory"); return v; }
__device__ __forceinline__ float blo(unsigned v) { return __uint_as_float(v << 16); }
__device__ __forceinline__ float bhi(unsigned v) { return __uint_as_float(v & 0xFFFF0000u); }
__device__ __forceinline__ float blo_v(unsigned v) { float r; asm volatile("shl.b32 %0,%1,16;" : "=f"(r) : "r"(v)); return r; }
__device__ __forceinline__ float bhi_v(unsigned v) { float r; asm volatile("and.b32 %0,%1,0xFFFF0000;" : "=f"(r) : "r"(v)); return r; }
__device__ __forceinline__ unsigned pack2(float lo, float hi) { unsigned r; asm("cvt.rn.bf16x2.f32 %0,%1,%2;" : "=r"(r) : "f"(hi), "f"(lo)); return r; }

__device__ __forceinline__ void mma16816(float* d, unsigned a0, unsigned a1, unsigned a2, unsigned a3, unsigned b0, unsigned b1) {
    asm volatile("mma.sync.aligned.m16n8k16.row.col.f32.bf16.bf16.f32 {%0,%1,%2,%3},{%4,%5,%6,%7},{%8,%9},{%0,%1,%2,%3};"
                 : "+f"(d[0]), "+f"(d[1]), "+f"(d[2]), "+f"(d[3]) : "r"(a0), "r"(a1), "r"(a2), "r"(a3), "r"(b0), "r"(b1));
}
#define R10(b) "+f"(d[b + 0]), "+f"(d[b + 1]), "+f"(d[b + 2]), "+f"(d[b + 3]), "+f"(d[b + 4]), "+f"(d[b + 5]), "+f"(d[b + 6]), "+f"(d[b + 7]), "+f"(d[b + 8]), "+f"(d[b + 9])
__device__ __forceinline__ void wg80(float* d, unsigned da, unsigned db, int sc) {
    asm volatile("{.reg .pred p; .reg .b64 a, b; setp.ne.b32 p,%42,0; mov.b64 a,{%40,%43}; mov.b64 b,{%41,%43};\n"
                 "wgmma.mma_async.sync.aligned.m64n80k16.f32.bf16.bf16 "
                 "{%0,%1,%2,%3,%4,%5,%6,%7,%8,%9,%10,%11,%12,%13,%14,%15,%16,%17,%18,%19,%20,%21,%22,%23,%24,%25,%26,%27,%28,%29,%30,%31,%32,%33,%34,%35,%36,%37,%38,%39},"
                 "a,b,p,1,1,1,0;}"
                 : R10(0), R10(10), R10(20), R10(30) : "r"(da), "r"(db), "r"(sc), "r"(0x40000040));
}
__device__ __forceinline__ void wg_fence() { asm volatile("wgmma.fence.sync.aligned;" ::: "memory"); }
__device__ __forceinline__ void wg_commit() { asm volatile("wgmma.commit_group.sync.aligned;" ::: "memory"); }
template <int N> __device__ __forceinline__ void wg_wait() { asm volatile("wgmma.wait_group.sync.aligned %0;" ::"n"(N) : "memory"); }
__device__ __forceinline__ void bulk_g2s(unsigned dst, const void* src, unsigned bytes, unsigned bar) {
    asm volatile("cp.async.bulk.shared::cluster.global.mbarrier::complete_tx::bytes [%0],[%1],%2,[%3];" ::"r"(dst), "l"(src), "r"(bytes), "r"(bar) : "memory");
}
__device__ __forceinline__ void fence_async_smem() { asm volatile("fence.proxy.async.shared::cta;" ::: "memory"); }
__device__ __forceinline__ void fence_async_gmem() { asm volatile("fence.proxy.async.global;" ::: "memory"); }

__device__ __forceinline__ unsigned hsat(unsigned a, unsigned c) { unsigned r; asm("add.sat.f16x2 %0,%1,%2;" : "=r"(r) : "r"(a), "r"(c)); return r; }
__device__ __forceinline__ unsigned hset(unsigned a, unsigned c) { unsigned r; asm("set.le.f16x2.f16x2 %0,%1,%2;" : "=r"(r) : "r"(a), "r"(c)); return r; }
__host__ __device__ constexpr unsigned h2c(int v) { return (0x6400u | v) | ((0x6400u | v) << 16); }
__device__ __forceinline__ unsigned dp2lo(unsigned a, unsigned c) { unsigned r; asm("dp2a.lo.u32.u32 %0,%1,%2,%3;" : "=r"(r) : "r"(a), "r"(0x80000080u), "r"(c)); return r; }
__device__ __forceinline__ unsigned dp2hi(unsigned a, unsigned c) { unsigned r; asm("dp2a.hi.u32.u32 %0,%1,%2,%3;" : "=r"(r) : "r"(a), "r"(0x80000080u), "r"(c)); return r; }
__device__ __forceinline__ void p3_step(float* acc0, float* acc1, unsigned addr, int s, unsigned sA, unsigned nB) {
    unsigned b0, b1, b2, b3;
    asm volatile("ldmatrix.sync.aligned.m8n8.x4.trans.shared.b16 {%0,%1,%2,%3},[%4];" : "=r"(b0), "=r"(b1), "=r"(b2), "=r"(b3) : "r"(addr));
    mma16816(acc0, hset(sA, h2c(4 * s + 0)), hsat(nB, h2c(4 * s + 1)), hset(sA, h2c(4 * s + 1)), hsat(nB, h2c(4 * s + 2)), b0, b1);
    mma16816(acc1, hset(sA, h2c(4 * s + 2)), hsat(nB, h2c(4 * s + 3)), hset(sA, h2c(4 * s + 3)), hsat(nB, h2c(4 * s + 4)), b2, b3);
}
template <int NS> __device__ __forceinline__ void p3_steps(float* acc0, float* acc1, const unsigned* ad, unsigned sA, unsigned nB) {
#pragma unroll
    for (int s = 0; s < NS; s++) p3_step(acc0, acc1, ad[s], s, sA, nB);
}
__device__ __noinline__ float4 p3_overflow(const Scratch* sc, int grp, unsigned sS) {
    int lane = threadIdx.x & 31, g = lane >> 2, t = lane & 3;
    float4 r = make_float4(0.f, 0.f, 0.f, 0.f);
    for (int c = 0; c < NT; c++) {
        int n = (int)__ldcg(&sc->ovfn[c]);
        for (int i0 = 0; i0 < n; i0 += 32) {
            unsigned e = (i0 + lane < n) ? __ldcg(&sc->ovf[c * OVCAP + i0 + lane]) : 0xFFFFFFFFu;
            unsigned m = __ballot_sync(~0u, (int)(e >> 18) == grp);
            while (m) {
                int j = __ffs(m) - 1;
                m &= m - 1;
                unsigned ee = __shfl_sync(~0u, e, j);
                int row = (ee >> 14) & 15;
                row ^= row >> 3;
                unsigned v = lds32(sS + (ee & 0x3FFF) * 16 + t * 4);
                if ((row >> 1) == g) {
                    if (!(row & 1)) { r.x += blo(v); r.y += bhi(v); } else { r.z += blo(v); r.w += bhi(v); }
                }
            }
        }
    }
    const float k = 1.f / 128.f;
    r.x *= k; r.y *= k; r.z *= k; r.w *= k;
    return r;
}
__device__ __forceinline__ void unpack8(float* f, uint4 v) {
    f[0] = blo(v.x); f[1] = bhi(v.x); f[2] = blo(v.y); f[3] = bhi(v.y); f[4] = blo(v.z); f[5] = bhi(v.z); f[6] = blo(v.w); f[7] = bhi(v.w);
}
__device__ __forceinline__ void vec_mat(float* o, const float* v, const uint4* __restrict__ W, int lane) {
    for (int k = 0; k < 8; k++) o[k] = 0.f;
    for (int l = 0; l < 32; l++) {
#pragma unroll
        for (int i = 0; i < 8; i++) {
            float a = __shfl_sync(~0u, v[i], l), wr[8];
            unpack8(wr, W[(l * 8 + i) * 32 + lane]);
#pragma unroll
            for (int k = 0; k < 8; k++) o[k] = fmaf(a, wr[k], o[k]);
        }
    }
}
__device__ __noinline__ uint4 attn_generic(int node, const uint4* __restrict__ x, const int* __restrict__ esrc, const int* __restrict__ edst,
                                           const uint4* __restrict__ wq, const uint4* __restrict__ wk, const uint4* __restrict__ wv) {
    int lane = threadIdx.x & 31;
    float xr[8], q[8], y[8], o[8];
    unpack8(xr, x[node * 32 + lane]);
    vec_mat(q, xr, wq, lane);
    for (int l = 0; l < 32; l++) {
#pragma unroll
        for (int i = 0; i < 8; i++) {
            float wr[8], p = 0.f;
            unpack8(wr, wk[(l * 8 + i) * 32 + lane]);
#pragma unroll
            for (int k = 0; k < 8; k++) p = fmaf(q[k], wr[k], p);
            for (int k = 16; k; k >>= 1) p += __shfl_xor_sync(~0u, p, k);
            if (lane == l) y[i] = p;
        }
    }
    for (int k = 0; k < 8; k++) o[k] = 0.f;
    float den = 0.f;
    for (int i0 = 0; i0 < NEE; i0 += 32) {
        unsigned m = __ballot_sync(~0u, edst[i0 + lane] == node);
        while (m) {
            int j = __ffs(m) - 1;
            m &= m - 1;
            float gq[8], p = 0.f;
            unpack8(gq, x[esrc[i0 + j] * 32 + lane]);
#pragma unroll
            for (int k = 0; k < 8; k++) p = fmaf(y[k], gq[k], p);
            for (int k = 16; k; k >>= 1) p += __shfl_xor_sync(~0u, p, k);
            float ex = __expf(p * 0.0625f);
            den += ex;
#pragma unroll
            for (int k = 0; k < 8; k++) o[k] = fmaf(ex, gq[k], o[k]);
        }
    }
    float inv = 1.f / (den + 1e-9f);
    for (int k = 0; k < 8; k++) o[k] *= inv;
    vec_mat(q, o, wv, lane);
    return make_uint4(pack2(q[0], q[1]), pack2(q[2], q[3]), pack2(q[4], q[5]), pack2(q[6], q[7]));
}

__device__ __forceinline__ unsigned hfma2(unsigned a, unsigned b, unsigned c) { unsigned r; asm("fma.rn.bf16x2 %0,%1,%2,%3;" : "=r"(r) : "r"(a), "r"(b), "r"(c)); return r; }
__device__ __forceinline__ unsigned hmul2(unsigned a, unsigned b) { unsigned r; asm("mul.rn.bf16x2 %0,%1,%2;" : "=r"(r) : "r"(a), "r"(b)); return r; }

__device__ __forceinline__ unsigned tile_addr(int n, unsigned chunk) { return sb + OFF_T + (chunk >> 3) * 10240 + n * 128 + (((chunk ^ n) & 7) << 4); }
__device__ __forceinline__ void attn_scores(float* v, bool mine, bool par, const uint4* gv, unsigned yaddr) {
    const uint4 y = lds128(yaddr);
    float c[4] = {0, 0, 0, 0}, e[4] = {0, 0, 0, 0};
    mma16816(c, gv[0].x, gv[1].x, gv[0].y, gv[1].y, y.x, y.y);
    mma16816(e, gv[2].x, gv[3].x, gv[2].y, gv[3].y, y.x, y.y);
    mma16816(c, gv[0].z, gv[1].z, gv[0].w, gv[1].w, y.z, y.w);
    mma16816(e, gv[2].z, gv[3].z, gv[2].w, gv[3].w, y.z, y.w);
    if (mine) { v[0] = par ? c[1] : c[0]; v[1] = par ? c[3] : c[2]; v[2] = par ? e[1] : e[0]; v[3] = par ? e[3] : e[2]; }
}
__device__ __forceinline__ void attn_softmax(const float* v, const float* u, unsigned lane, unsigned delta, unsigned alsm) {
    const bool hA = lane & 4, hB = lane & 8, hC = lane & 16;
    float a[4];
#pragma unroll
    for (int e = 0; e < 4; e++) a[e] = (hA ? u[e] : v[e]) + __shfl_xor_sync(~0u, hA ? v[e] : u[e], 4);
    float b0 = (hB ? a[1] : a[0]) + __shfl_xor_sync(~0u, hB ? a[0] : a[1], 9);
    float b1 = (hB ? a[3] : a[2]) + __shfl_xor_sync(~0u, hB ? a[2] : a[3], 9);
    float sc = (hC ? b1 : b0) + __shfl_xor_sync(~0u, hC ? b0 : b1, 18);
    float ex = exp2f(sc);
    float den = ex + __shfl_xor_sync(~0u, ex, 9);
    den += __shfl_xor_sync(~0u, den, 18);
    float al = __fdividef(ex, den + 1e-9f);
    sts32(alsm + (hA ? 4 + delta : delta) * 16 + (lane >> 3) * 4, pack2(al, al));
    __syncwarp();
}
__device__ __forceinline__ void attn_mix(const uint4* gv, unsigned al, unsigned oaddr) {
    const uint4 a = lds128(al);
    uint4 o;
    o.x = hfma2(a.w, gv[3].x, hfma2(a.z, gv[2].x, hfma2(a.y, gv[1].x, hmul2(a.x, gv[0].x))));
    o.y = hfma2(a.w, gv[3].y, hfma2(a.z, gv[2].y, hfma2(a.y, gv[1].y, hmul2(a.x, gv[0].y))));
    o.z = hfma2(a.w, gv[3].z, hfma2(a.z, gv[2].z, hfma2(a.y, gv[1].z, hmul2(a.x, gv[0].z))));
    o.w = hfma2(a.w, gv[3].w, hfma2(a.z, gv[2].w, hfma2(a.y, gv[1].w, hmul2(a.x, gv[0].w))));
    sts128(oaddr, o);
}
__device__ __forceinline__ void pack_acc(unsigned* pk, const float* d) {
#pragma unroll
    for (int j = 0; j < 20; j++) pk[j] = pack2(d[2 * j], d[2 * j + 1]);
}
__device__ __forceinline__ void acc_to_tile(const unsigned* pk, int w, int lane) {
    const unsigned a = sb + OFF_T + (w >> 2) * 10240 + (lane >> 4) * 1024 + (lane & 7) * 128 + (((2 * (w & 3) + ((lane >> 3) & 1)) ^ (lane & 7)) << 4);
#pragma unroll
    for (int j = 0; j < 5; j++)
        asm volatile("stmatrix.sync.aligned.m8n8.x4.trans.shared.b16 [%0],{%1,%2,%3,%4};" ::"r"(a + j * 2048), "r"(pk[4 * j]), "r"(pk[4 * j + 1]), "r"(pk[4 * j + 2]), "r"(pk[4 * j + 3]) : "memory");
}
__device__ __forceinline__ unsigned movm(unsigned a) { unsigned d; asm volatile("movmatrix.sync.aligned.m8n8.trans.b16 %0,%1;" : "=r"(d) : "r"(a)); return d; }
__device__ __forceinline__ void tma_load2d(unsigned dst, const CUtensorMap* tm, int c0, int c1, unsigned bar) {
    asm volatile("cp.async.bulk.tensor.2d.shared::cluster.global.mbarrier::complete_tx::bytes [%0],[%1,{%3,%4}],[%2];"
                 ::"r"(dst), "l"(tm), "r"(bar), "r"(c0), "r"(c1) : "memory");
}
__device__ __forceinline__ void tma_load3d(unsigned dst, const CUtensorMap* tm, int row, unsigned bar) {
    asm volatile("cp.async.bulk.tensor.3d.shared::cluster.global.mbarrier::complete_tx::bytes [%0],[%1,{%4,%3,%4}],[%2];"
                 ::"r"(dst), "l"(tm), "r"(bar), "r"(row), "r"(0) : "memory");
}
__device__ __forceinline__ void cp16(unsigned dst, const void* src) { asm volatile("cp.async.cg.shared.global [%0],[%1],16;" ::"r"(dst), "l"(src) : "memory"); }
__device__ __forceinline__ void cp_commit() { asm volatile("cp.async.commit_group;" ::: "memory"); }
template <int N> __device__ __forceinline__ void cp_wait() { asm volatile("cp.async.wait_group %0;" ::"n"(N) : "memory"); }
__device__ __forceinline__ void nb_sync_id(int id, int n) { asm volatile("bar.sync %0,%1;" ::"r"(id), "r"(n) : "memory"); }
__device__ __forceinline__ void nb_arrive_id(int id, int n) { asm volatile("bar.arrive %0,%1;" ::"r"(id), "r"(n) : "memory"); }
template <int ID, int N> __device__ __forceinline__ void nb_sync() { asm volatile("bar.sync %0,%1;" ::"n"(ID), "n"(N) : "memory"); }
template <int ID, int N> __device__ __forceinline__ void nb_arrive() { asm volatile("bar.arrive %0,%1;" ::"n"(ID), "n"(N) : "memory"); }
__device__ __forceinline__ void mbar_init(unsigned a, int n) { asm volatile("mbarrier.init.shared.b64 [%0],%1;" ::"r"(a), "r"(n) : "memory"); }
__device__ __forceinline__ void mbar_expect(unsigned a, int n) { asm volatile("mbarrier.arrive.expect_tx.shared.b64 _,[%0],%1;" ::"r"(a), "r"(n) : "memory"); }
__device__ __forceinline__ void mbar_arrive(unsigned a) { asm volatile("mbarrier.arrive.shared.b64 _,[%0];" ::"r"(a) : "memory"); }

constexpr unsigned PADBIN = 2560, CU = 0x101;
__device__ __noinline__ void push_overflow(Scratch* sc, unsigned dst, unsigned src) {
    sc->ovf[blockIdx.x * OVCAP + atoms_inc(sb + OFF_MISC)] = (dst << 14) | src;
}
__device__ __noinline__ void bin_overflow4(Scratch* sc, uint4 v, uint4 h) {
    const unsigned e[4] = {v.x, v.y, v.z, v.w}, hh[4] = {h.x, h.y, h.z, h.w};
#pragma unroll
    for (int i = 0; i < 4; i++)
        if (hh[i] >= (LCAP + 16) * CU && e[i] < (PADBIN << 16))
            push_overflow(sc, blockIdx.x * TILE + ((e[i] >> 21) & ~3u) + ((e[i] >> 18) & 3), ((e[i] & 2047) << 3) | ((e[i] >> 20) & 7));
}
__device__ __forceinline__ void reds_add(unsigned a, unsigned k) { asm volatile("red.shared.add.u32 [%0],%1;" ::"r"(a), "r"(k) : "memory"); }
__device__ __forceinline__ void bulk_s2g(void* dst, unsigned src, unsigned bytes) {
    asm volatile("cp.async.bulk.global.shared::cta.bulk_group [%0],[%1],%2;" ::"l"(dst), "r"(src), "r"(bytes) : "memory");
}
__device__ __forceinline__ void tma_reduce(const CUtensorMap* tm, unsigned src, int c0, int c1) {
    asm volatile("cp.reduce.async.bulk.tensor.2d.global.shared::cta.add.tile.bulk_group [%0,{%2,%3}],[%1];" ::"l"(tm), "r"(src), "r"(c0), "r"(c1) : "memory");
}
#define EV(id) nb_arrive<id, 544>()
#define WAIT_EV(id) nb_sync<id, 544>()

__global__ void __launch_bounds__(640, 1)
exphormer_kernel(const uint4* __restrict__ x, const uint4* __restrict__ dst4, const uint4* __restrict__ src4,
                 const uint4* __restrict__ wq, const uint4* __restrict__ wk, const int* __restrict__ esrc,
                 const int* __restrict__ edst, Scratch* __restrict__ sc, const uint4* __restrict__ dis, const uint4* __restrict__ wv,
                 const __grid_constant__ CUtensorMap tm_x, const __grid_constant__ CUtensorMap tm_wl, const __grid_constant__ CUtensorMap tm_wv,
                 const __grid_constant__ CUtensorMap tm_ot, const __grid_constant__ CUtensorMap tm_o256, const __grid_constant__ CUtensorMap tm_o16) {
    extern __shared__ __align__(1024) unsigned char smem_raw[];
    const unsigned tid = threadIdx.x, lane = tid & 31, g = lane >> 2, t = lane & 3;
    const unsigned b = blockIdx.x;
    const bool rowcta = b < NT;
    const int slice = b >> 2, range = b & 3;
    const int g0 = (range * NG) >> 2, g1 = ((range + 1) * NG) >> 2;
    STAMP(0);

    if (tid >= 544) {
        const unsigned ht = tid - 544;
        if (ht < 32) {
            nb_sync<2, 416>();
            if (lane == 0) bar_arrive(&sc->bar[0]);
            __syncwarp();
            STAMPT(544, 47);
        }
        nb_sync<13, 128>();
        if (rowcta) {
            const unsigned pad = (PADBIN + 4 * lane) << 16;
            if (ht < 76) sts128(sb + OFF_MAIL + 8000 + ht * 16, make_uint4(pad, pad, pad, pad));
            nb_sync<1, 96>();
            mbar_wait(bar_mail);
            STAMPT(576, 16);
            for (unsigned i = ht; i < 500; i += 96) {
                if (lds32(sb + OFF_IMG + i * 16) < (PADBIN << 16)) {
                    const uint4 v = lds128(sb + OFF_IMG + i * 16);
                    const unsigned k = atoms_inc(sb + OFF_MISC + 4);
                    if (k < 76) sts128(sb + OFF_MAIL + 8000 + k * 16, v);
                    else bin_overflow4(sc, v, make_uint4(~0u, ~0u, ~0u, ~0u));
                }
            }
            nb_sync<1, 96>();
#pragma unroll
            for (int k = 0; k < 5; k++) sts128(sb + OFF_IMG + (ht >> 5) * 4096 + k * 512 + lane * 16, make_uint4(DUMMY2, DUMMY2, DUMMY2, DUMMY2));
#pragma unroll 2
            for (int k = 0; k < 6; k++) {
                const uint4 e = lds128(sb + OFF_MAIL + (ht + k * 96) * 16);
                reds_add(sb + OFF_CNT2 + (e.x >> 16), CU); reds_add(sb + OFF_CNT2 + (e.y >> 16), CU);
                reds_add(sb + OFF_CNT2 + (e.z >> 16), CU); reds_add(sb + OFF_CNT2 + (e.w >> 16), CU);
            }
            nb_sync<1, 96>();
            STAMPT(576, 17);
            for (unsigned G = ht >> 5; G < 5; G += 3) {
                const unsigned ca = sb + OFF_CNT2 + G * 512 + lane * 16;
                const uint4 c = lds128(ca);
                const unsigned dp = hmul2(lds32(sb + OFF_DIS + (G * 8 + g) * 4), 0x43004300u);
                const bool sw = lane >= 16;
                unsigned s1 = sw ? c.y : c.x, s2 = c.x + c.y, s3 = s2 + (sw ? c.w : c.z), tot = s2 + c.z + c.w, inc = tot;
                unsigned u = __shfl_up_sync(~0u, inc, 8); if (lane >= 8) inc += u;
                u = __shfl_up_sync(~0u, inc, 16); if (sw) inc += u;
                const unsigned base = inc - tot;
                const unsigned p0 = min(base, LCAP * CU), p1 = min(base + s1, LCAP * CU), p2 = min(base + s2, LCAP * CU), p3 = min(base + s3, LCAP * CU);
                sts128(ca, make_uint4((sw ? p1 : p0) + 16 * CU, (sw ? p0 : p1) + 16 * CU, (sw ? p3 : p2) + 16 * CU, (sw ? p2 : p3) + 16 * CU));
                const unsigned word = __byte_perm(__byte_perm(p0, p1, 0x0040), __byte_perm(p2, p3, 0x0040), 0x5410);
                const unsigned wa = __shfl_sync(~0u, word, (g >> 1) * 8 + 2 * t), wb = __shfl_sync(~0u, word, (g >> 1) * 8 + 2 * t + 1);
                unsigned hdr = __byte_perm(wa, wb, (g & 1) ? 0x7362 : 0x5140);
                if (__any_sync(~0u, inc > 48 * CU)) hdr |= 0x80;
                asm volatile("st.shared.v2.u32 [%0],{%1,%2};" ::"r"(sb + OFF_IMG + G * 512 + lane * 16), "r"(hdr), "r"(__byte_perm(dp, dp, sw ? 0x1032 : 0x3210)) : "memory");
            }
            nb_sync<1, 96>();
#pragma unroll 2
            for (int k = 0; k < 6; k++) {
                const uint4 v = lds128(sb + OFF_MAIL + (ht + k * 96) * 16);
                const unsigned e[4] = {v.x, v.y, v.z, v.w};
                unsigned h[4];
#pragma unroll
                for (int i = 0; i < 4; i++) h[i] = atoms_add(sb + OFF_CNT2 + (e[i] >> 16), CU);
#pragma unroll
                for (int i = 0; i < 4; i++)
                    asm volatile("{.reg .pred p; setp.lt.u32 p,%2,%3; @p st.shared.u16 [%0],%1;}"
                                 ::"r"(sb + OFF_IMG + bitsel(h[i] >> 1, e[i] >> 16, 0x318E)), "h"((unsigned short)e[i]), "r"(h[i]), "n"((LCAP + 16) * CU) : "memory");
                if (__builtin_expect(max(max((int)h[0], (int)h[1]), max((int)h[2], (int)h[3])) >= (int)((LCAP + 16) * CU), 0))
                    bin_overflow4(sc, v, make_uint4(h[0], h[1], h[2], h[3]));
            }
            fence_async_smem();
            nb_sync<1, 96>();
            STAMPT(576, 18);
        }
        if (ht < 32 && elect()) {
            if (rowcta) {
                for (int c = 0; c < 3; c++) bulk_s2g(sc->lists + (c * LSTR + b * 160), sb + OFF_IMG + c * 4096, 2560);
                asm volatile("cp.async.bulk.commit_group;" ::: "memory");
                const unsigned novf = lds32(sb + OFF_MISC), bad = lds32(sb + OFF_MISC + 20);
                sc->ovfn[b] = novf;
                if (__builtin_expect(novf | bad, 0)) raise_flag(&sc->bar[5], lds32(sb + OFF_MISC + 24), (novf ? 1 : 0) | (bad ? 2 : 0));
                asm volatile("cp.async.bulk.wait_group 0;" ::: "memory");
                fence_async_gmem();
            }
            bar_arrive(&sc->bar[4]);
            STAMPT(544, 19);
            sts32(sb + OFF_MISC + 28, bar_poll2(&sc->bar[4], lds32(sb + OFF_MISC + 24)));
            mbar_arrive(bar_c);
            STAMPT(544, 23);
        }
    } else if (tid >= 512) {
        const bool one = elect();
        auto load_xl = [&](int i) {
            mbar_expect(bar_full + 8 * i, 32768 + 10240);
            tma_load2d(sb + OFF_T + i * 10240, &tm_x, i * 64, b * TILE, bar_full + 8 * i);
            tma_load3d(sb + OFF_S + i * 32768, &tm_wl, i * 64, bar_full + 8 * i);
        };
        auto load_m = [&](int i, int slot) {
            mbar_expect(bar_full + 32 + 8 * i, 32768);
            bulk_g2s(sb + OFF_S + slot * 32768, sc->mimg + i * 2048, 32768, bar_full + 32 + 8 * i);
        };
        auto load_v = [&](int i, int slot) {
            mbar_expect(bar_full + 64 + 8 * i, 32768);
            tma_load3d(sb + OFF_S + slot * 32768, &tm_wv, i * 64, bar_full + 64 + 8 * i);
        };
        const char* hsl = (const char*)(sc->hs + slice * NN);
        auto fill = [&](int slot) { bulk_g2s(sb + OFF_S + slot * 32768, hsl + slot * 32768, slot == 4 ? NN * 16 - 4 * 32768 : 32768, bar_fill); };
        const unsigned t0 = clock();
        unsigned target = 0;
        if (one) {
            for (int i = 0; i < 2; i++) mbar_init(bar_full + 8 * i, 1);
            asm volatile("fence.mbarrier_init.release.cluster;" ::: "memory");
            while ((unsigned)clock() - t0 < XD0) {}
            if (rowcta) load_xl(0);
            STAMPT(512, 41);
            asm volatile("ld.relaxed.gpu.global.u32 %0,[%1];" : "=r"(target) : "l"(&sc->bar[1]) : "memory");
            for (int i = 2; i < 12; i++) mbar_init(bar_full + 8 * i, 1);
            for (int i = 0; i < 4; i++) mbar_init(bar_fill + 8 * i, 1);
            for (int i = 0; i < 10; i++) mbar_init(bar_rd + 8 * i, i < 9 ? 16 : g1 - g0 - 144);
            asm volatile("fence.mbarrier_init.release.cluster;" ::: "memory");
            if ((unsigned)__cvta_generic_to_shared(smem_raw) != sb) __trap();
            while ((unsigned)clock() - t0 < XD1) {}
            if (rowcta) load_xl(1);
            target = (target & ~(NCTA - 1)) + NCTA;
            sts32(sb + OFF_MISC + 24, target);
            mbar_expect(bar_fill, NN * 16);
        }
        __syncwarp();
        nb_arrive<3, 544>();
        if (rowcta) {
            if (one) {
                if (XD2) { while ((unsigned)clock() - t0 < XD2 + 1) {} } else mbar_wait(bar_full);
                load_xl(2);
                STAMPT(512, 52);
                mbar_wait(bar_full + (XD2 ? 0 : 8)); load_xl(3);
                STAMPT(512, 53);
                bar_poll(&sc->bar[0], target);
                STAMPT(512, 48);
                fence_async_gmem();
                mbar_expect(bar_mail, 16000);
                bulk_g2s(sb + OFF_MAIL, sc->mail + b * 1024, 8000, bar_mail);
                bulk_g2s(sb + OFF_IMG, sc->mail + (b * 1024 + 512), 8000, bar_mail);
            }
            __syncwarp();
            nb_arrive<13, 128>();
            WAIT_EV(5); if (one) { load_m(0, 0); load_m(1, 1); }
            WAIT_EV(6); if (one) load_m(2, 3);
            WAIT_EV(7); if (one) load_m(3, 0);
            WAIT_EV(12); if (one) bar_arrive(&sc->bar[2]);
            STAMPT(512, 24);
            WAIT_EV(14); if (one) load_v(0, 0);
            WAIT_EV(15);
            if (one) {
                fence_async_smem();
                load_v(1, 4); load_v(2, 2);
                bar_poll(&sc->bar[2], target);
                fence_async_gmem();
            }
            STAMPT(512, 25);
            WAIT_EV(2); if (one) { load_v(3, 1); fill(3); }
            WAIT_EV(4); if (one) fill(0);
            WAIT_EV(5); if (one) fill(4);
            WAIT_EV(6); if (one) fill(2);
            WAIT_EV(7); if (one) fill(1);
            WAIT_EV(12);
            if (one) {
#pragma unroll
                for (int kb = 0; kb < 4; kb++)
                    asm volatile("cp.async.bulk.tensor.2d.global.shared::cta.bulk_group [%0,{%2,%3}],[%1];"
                                 ::"l"(&tm_ot), "r"(sb + OFF_T + kb * 10240), "r"(kb * 64), "r"(b * TILE) : "memory");
                asm volatile("cp.async.bulk.commit_group;" ::: "memory");
                asm volatile("cp.async.bulk.wait_group 0;" ::: "memory");
                fence_async_gmem();
            }
        } else {
            nb_arrive<13, 128>();
            if (one) {
                bar_arrive(&sc->bar[2]);
                bar_poll(&sc->bar[2], target);
                fence_async_gmem(); fence_async_smem();
                for (int i = 0; i < 5; i++) fill(i);
            }
        }
        if (one) {
            bar_arrive(&sc->bar[1]);
            mbar_arrive(bar_t);
            STAMPT(512, 26);
            bar_poll(&sc->bar[1], target);
            fence_async_gmem();
            STAMPT(512, 27);
            for (int r = 0; r < 9; r++) {
                mbar_wait(bar_rd + 8 * r);
                fence_async_smem();
                tma_reduce(&tm_o256, sb + OFF_STG + r * 4096, slice * 8, (g0 + 16 * r) * 16);
            }
            mbar_wait(bar_rd + 72);
            fence_async_smem();
            for (int i = 144; i < g1 - g0; i++) tma_reduce(&tm_o16, sb + OFF_STG + i * 256, slice * 8, (g0 + i) * 16);
            asm volatile("cp.async.bulk.commit_group;" ::: "memory");
            asm volatile("cp.async.bulk.wait_group.read 0;" ::: "memory");
            STAMPT(512, 13);
        }
    } else {
    if (tid >= 192) {
        if (rowcta) {
            const unsigned bt = tid - 192;
            const uint4 ed = __ldg(dst4 + (b * 320 + bt)), es = __ldg(src4 + (b * 320 + bt));
            const unsigned pad = (PADBIN + 4 * ((bt & 3) + ((b * 4) & 28))) << 16;
#pragma unroll
            for (int k = 0; k < 4; k++) if (k < 3 || bt < 40) sts128(sb + OFF_MAIL + (bt + k * 320) * 16, make_uint4(pad, pad, pad, pad));
            const unsigned cz = bt < (512 + PADBIN) / 16 ? 0 : 0x80000000;
            if (bt < (512 + 2688) / 16) sts128(sb + OFF_CNT1 + bt * 16, make_uint4(cz, cz, cz, cz));
            if (bt == 319) sts128(sb + OFF_MISC, make_uint4(0, 0, 0, 0));
            unsigned z;
            asm volatile("{.reg .pred p; setp.eq.u32 p,%1,0xFFFFFFFF; bar.red.popc.u32 %0,4,320,p;}" : "=r"(z) : "r"(bt) : "memory");
            const unsigned dd[4] = {ed.x + z, ed.y + z, ed.z + z, ed.w + z}, ss[4] = {es.x + z, es.y + z, es.z + z, es.w + z};
            unsigned rk[4], ow[4];
#pragma unroll
            for (int i = 0; i < 4; i++) { ow[i] = dd[i] / TILE; rk[i] = atoms_inc(sb + OFF_CNT1 + ow[i] * 4); }
#pragma unroll
            for (int i = 0; i < 4; i++) {
                const unsigned dl = dd[i] - ow[i] * TILE;
                const unsigned e = bitsel(ss[i] << 20, bitsel(dl << 21, dl << 18, 0xFF800000u), 0x00700000u) + (ss[i] >> 3);
                asm volatile("{.reg .pred p; setp.lt.u32 p,%2,%3; @p st.shared.u32 [%0],%1;}" ::"r"(sb + OFF_MAIL + (ow[i] * CELL + rk[i]) * 4), "r"(e), "r"(rk[i]), "n"(CELL) : "memory");
            }
            if (__builtin_expect((rk[0] | rk[1] | rk[2] | rk[3]) >= CELL, 0)) {
#pragma unroll
                for (int i = 0; i < 4; i++) if (rk[i] >= CELL) push_overflow(sc, dd[i], ss[i]);
            }
            STAMPT(416, 44);
            nb_sync<4, 320>();
            uint4 mv[4];
            uint4* mp = sc->mail + ((bt >> 3) * 1024 + (bt & 4) * 128 + b * 4 + (bt & 3));
#pragma unroll
            for (int k = 0; k < 4; k++) if (k < 3 || bt < 40) mv[k] = lds128(sb + OFF_MAIL + (bt + k * 320) * 16);
            fence_async_smem();
#pragma unroll
            for (int k = 0; k < 4; k++) if (k < 3 || bt < 40) mp[k * 40960] = mv[k];
        }
        STAMPT(416, 45);
        nb_arrive<2, 416>();
    } else if (tid >= 64) {
        const unsigned fw = b >> 3, hq = b & 7, q = (tid >> 5) - 2, cq = q * 8 + t, mt = tid - 64;
        const uint4* pa = wq + ((16 * fw + g) * 32 + cq);
        const uint4* pb = wk + ((32 * hq + 8 * (g >> 1) + (g & 1)) * 32 + cq);
        const unsigned ma = sb + OFF_S + 4 * 32768 + 8192 + mt * 16;
        cp16(ma, pa); cp16(ma + 2048, pa + 4); cp16(ma + 4096, pa + 256); cp16(ma + 6144, pa + 260);
#pragma unroll
        for (int u = 0; u < 8; u++) cp16(ma + 8192 + u * 2048, pb + (u >> 1) * 64 + (u & 1) * 4);
        cp_commit();
        uint4 va[4], vb[8];
        STAMPT(64, 38);
        cp_wait<0>();
        STAMPT(64, 39);
#pragma unroll
        for (int u = 0; u < 4; u++) va[u] = lds128(ma + u * 2048);
#pragma unroll
        for (int u = 0; u < 8; u++) vb[u] = lds128(ma + 8192 + u * 2048);
        float c[4][4];
#pragma unroll
        for (int u = 0; u < 4; u++) {
            c[u][0] = c[u][1] = c[u][2] = c[u][3] = 0.f;
            mma16816(c[u], va[0].x, va[2].x, va[0].y, va[2].y, vb[2 * u].x, vb[2 * u].y);
            mma16816(c[u], va[0].z, va[2].z, va[0].w, va[2].w, vb[2 * u].z, vb[2 * u].w);
            mma16816(c[u], va[1].x, va[3].x, va[1].y, va[3].y, vb[2 * u + 1].x, vb[2 * u + 1].y);
            mma16816(c[u], va[1].z, va[3].z, va[1].w, va[3].w, vb[2 * u + 1].z, vb[2 * u + 1].w);
        }
        const unsigned ra = sb + OFF_S + 4 * 32768 + lane * 16;
#pragma unroll
        for (int hh = 0; hh < 2; hh++) {
            sts128(ra + q * 2048 + hh * 1024, make_uint4(__float_as_uint(c[0][2 * hh]), __float_as_uint(c[0][2 * hh + 1]), __float_as_uint(c[1][2 * hh]), __float_as_uint(c[1][2 * hh + 1])));
            sts128(ra + q * 2048 + hh * 1024 + 512, make_uint4(__float_as_uint(c[2][2 * hh]), __float_as_uint(c[2][2 * hh + 1]), __float_as_uint(c[3][2 * hh]), __float_as_uint(c[3][2 * hh + 1])));
        }
        STAMPT(64, 42);
        nb_sync<1, 128>();
        if (q < 2) {
            float m[8] = {0, 0, 0, 0, 0, 0, 0, 0};
#pragma unroll
            for (int i = 0; i < 4; i++) {
                uint4 u = lds128(ra + i * 2048 + q * 1024), v = lds128(ra + i * 2048 + q * 1024 + 512);
                m[0] += __uint_as_float(u.x); m[1] += __uint_as_float(u.y); m[2] += __uint_as_float(u.z); m[3] += __uint_as_float(u.w);
                m[4] += __uint_as_float(v.x); m[5] += __uint_as_float(v.y); m[6] += __uint_as_float(v.z); m[7] += __uint_as_float(v.w);
            }
            const float k = 0.0625f * 1.4426950408889634f;
            sc->mimg[(fw >> 2) * 2048 + (hq >> 1) * 512 + (16 * (fw & 3) + 8 * q + g) * 8 + (((hq & 1) * 4 + t) ^ g)] =
                make_uint4(pack2(m[0] * k, m[1] * k), pack2(m[2] * k, m[3] * k), pack2(m[4] * k, m[5] * k), pack2(m[6] * k, m[7] * k));
            STAMPT(64, 43);
            nb_arrive<2, 416>();
        }
    } else if (tid >= 32) {
        const uint4* ep = (const uint4*)esrc + (min(b, NT - 1u) * TILE + lane);
        cp16(sb + OFF_EIDX + lane * 16, ep); cp16(sb + OFF_EIDX + 512 + lane * 16, ep + 32);
        if (lane < 16) cp16(sb + OFF_EIDX + 1024 + lane * 16, ep + 64);
        if (lane < 10) cp16(sb + OFF_DIS + lane * 16, dis + (min(b, NT - 1u) * 10 + lane));
        cp_commit();
        cp_wait<0>();
    } else {
        unsigned bad = 0;
        uint4 xd[3];
#pragma unroll
        for (int k = 0; k < 3; k++) xd[k] = ldg_na((const uint4*)edst + min(b * TILE + k * 32 + lane, NN - 1u));
#pragma unroll
        for (int k = 0; k < 3; k++) { const unsigned n = min(b * TILE + k * 32 + lane, NN - 1u); bad |= (xd[k].x ^ n) | (xd[k].y ^ n) | (xd[k].z ^ n) | (xd[k].w ^ n); }
        bad = __any_sync(~0u, bad);
        if (lane == 0) sts32(sb + OFF_MISC + 20, bad);
    }
    const int w = __shfl_sync(~0u, tid >> 5, 0), wg = w >> 2;
    const int grp0 = g0 + w;
    const uint4* lp = sc->lists + (grp0 * 32 + lane);
    uint4 L0, L1;
    nb_sync<3, 544>();

    if (__builtin_expect(rowcta, 1)) {
        const unsigned descA = 0x10000u + (sb + OFF_S) / 16 + wg * 512;
        const unsigned greg = sb + OFF_S + w * 2048 + lane * 16;
        const uint4* xl = x + lane;
        float d[40];
        unsigned pk[20];
        unsigned* hp = (unsigned*)(sc->hs + (2 * w * NN + b * TILE)) + lane;
        auto mma_q = [&](int Q, int slot, int st) {
            if (st < 0) wg_fence();
#pragma unroll
            for (int k = 0; k < 4; k++) {
                if (st >= 0) wg_fence();
                wg80(d, descA + slot * 2048 + k * 128, 0x10000u + (sb + OFF_T) / 16 + (Q & 3) * 640 + k * 2, ((Q & 3) | k) != 0);
                if (st >= 0) {
#pragma unroll
                    for (int j = st + 2 * k; j < st + 2 * k + 2; j++)
                        if (j < 20) asm volatile("st.global.u32 [%0],%1;" ::"l"(hp + (j >> 1) * 32 + (j & 1) * (NN * 4)), "r"(pk[j]) : "memory");
                }
            }
            wg_commit();
        };
        auto eidx = [&](int i) { return lds128(sb + OFF_EIDX + (w * 5 + i) * 16); };
        auto gather = [&](const uint4& ix, int slot) {
            cp16(greg + slot * 32768, xl + ix.x * 32u); cp16(greg + slot * 32768 + 512, xl + ix.y * 32u);
            cp16(greg + slot * 32768 + 1024, xl + ix.z * 32u); cp16(greg + slot * 32768 + 1536, xl + ix.w * 32u);
            cp_commit();
        };
        uint4 gv[5][4];
        auto to_regs = [&](int i, int slot) {
#pragma unroll
            for (int j = 0; j < 4; j++) gv[i][j] = lds128(greg + slot * 32768 + j * 512);
        };
        float ds[20];
#pragma unroll
        for (int j = 0; j < 10; j++) { const unsigned v = lds32(sb + OFF_DIS + (4 * j + t) * 4); ds[2 * j] = blo_v(v); ds[2 * j + 1] = bhi_v(v); }
        uint4 ix = eidx(0);
        const uint4 ix1 = eidx(1);
        STAMPT(288, 2);
        mbar_wait(bar_full);
        STAMPT(288, 3);
        mma_q(0, 0, -1);
        mbar_wait(bar_full + 8);
        STAMPT(288, 50);
        gather(ix, 4);
        mma_q(1, 1, -1);
        mbar_wait(bar_full + 16);
        STAMPT(288, 51);
        mma_q(2, 2, -1);
        wg_wait<1>();
        EV(5);
        mbar_wait(bar_full + 24);
        STAMP(5);
        mma_q(3, 3, -1);
        wg_wait<1>();
        nb_sync_id(8 + wg, 128);
        gather(ix1, 2);
        wg_wait<0>();
        EV(6);
        STAMP(6);
#pragma unroll
        for (int j = 0; j < 20; j++) pk[j] = movm(pack2(d[2 * j] * ds[2 * (j >> 1)], d[2 * j + 1] * ds[2 * (j >> 1) + 1]));
        cp_wait<1>();
        to_regs(0, 4);
        ix = eidx(2);
        const uint4 ix3 = eidx(3), ix4 = eidx(4);
        STAMP(7);
        mbar_wait(bar_full + 32); mbar_wait(bar_full + 40);
        asm volatile("" ::"r"(gv[0][0].x), "r"(gv[0][1].x), "r"(gv[0][2].x), "r"(gv[0][3].x));
        gather(ix, 4);
        STAMP(21);
        mma_q(4, 0, 0); mma_q(5, 1, 8);
        wg_wait<1>();
        EV(7);
        mbar_wait(bar_full + 48);
        mma_q(6, 3, 16);
        EV(12);
        wg_wait<1>();
        nb_sync_id(8 + wg, 128);
        gather(ix3, 1);
        mbar_wait(bar_full + 56);
        mma_q(7, 0, -1);
        wg_wait<1>();
        nb_sync_id(8 + wg, 128);
        gather(ix4, 3);
        wg_wait<0>();
        STAMP(20);
        EV(14);
        pack_acc(pk, d);
        nb_sync<0, 512>();
        acc_to_tile(pk, w, lane);
        cp_wait<2>();
        to_regs(1, 2);
        nb_sync<0, 512>();
        STAMP(8);
        {
            const unsigned delta = t ^ (g >> 1), alsm = sb + OFF_ALPHA + w * 128;
            const bool par = g & 1;
            const int n0 = w * 5;
            float v[4], u[4];
            to_regs(2, 4);
            EV(15);
            attn_scores(v, true, par, gv[0], tile_addr(n0, lane));
            attn_scores(v, delta == 1, par, gv[1], tile_addr(n0 + 1, lane ^ 8));
            attn_scores(v, delta == 2, par, gv[2], tile_addr(n0 + 2, lane ^ 16));
            cp_wait<1>();
            to_regs(3, 1);
            attn_scores(v, delta == 3, par, gv[3], tile_addr(n0 + 3, lane ^ 24));
            cp_wait<0>();
            to_regs(4, 3);
            attn_scores(u, true, par, gv[4], tile_addr(n0 + 4, lane));
            attn_softmax(v, u, lane, delta, alsm);
#pragma unroll
            for (int i = 0; i < 5; i++) attn_mix(gv[i], alsm + i * 16, tile_addr(n0 + i, lane));
        }
        mbar_wait(bar_full + 64);
        fence_async_smem();
        STAMP(22);
        EV(2);
        nb_sync<0, 512>();
        mma_q(8, 0, -1);
        mbar_wait(bar_full + 72);
        mma_q(9, 4, -1);
        wg_wait<1>();
        EV(4);
        mbar_wait(bar_full + 80);
        mma_q(10, 2, -1);
        wg_wait<1>();
        EV(5);
        mbar_wait(bar_full + 88);
        mma_q(11, 1, -1);
        wg_wait<1>();
        EV(6);
        wg_wait<0>();
        EV(7);
        STAMP(9);
        pack_acc(pk, d);
        mbar_wait(bar_c);
        L0 = ldg_na(lp); L1 = ldg_na(lp + LSTR);
        nb_sync<0, 512>();
        STAMP(10);
        if (__builtin_expect(lds32(sb + OFF_MISC + 28) & 2, 0)) {
            for (int i = 0; i < 5; i++) sts128(tile_addr(w * 5 + i, lane), attn_generic(b * TILE + w * 5 + i, x, esrc, edst, wq, wk, wv));
        } else {
            acc_to_tile(pk, w, lane);
        }
        fence_async_smem();
        EV(12);
    } else {
        mbar_wait(bar_c);
        L0 = ldg_na(lp); L1 = ldg_na(lp + LSTR);
    }

    const int cnt = (g1 - grp0 + 15) >> 4;
    const bool anyovf = lds32(sb + OFF_MISC + 28) & 1;
    if (lane < 8) sts128(sb + OFF_S + NN * 16 + lane * 16, make_uint4(0, 0, 0, 0));
    const unsigned lb = sb + OFF_S + (lane & 7) * 16;
    const unsigned dummy = anyovf ? 0 : lb + 1250 * 128;
    const float zmask = (lane >= 28) ? 0.f : -1.f;
    unsigned stg = sb + OFF_STG + w * 256 + (((lane & 7) * 2 + ((lane >> 3) & 1)) ^ ((lane >> 2) & 1)) * 16;
    __syncwarp();
    mbar_wait(bar_fill);
    STAMP(11);
    for (int it = 0; it < cnt; it++) {
        unsigned ad[12];
        ad[0] = dp2lo(L0.z, lb); ad[1] = dp2hi(L0.z, lb); ad[2] = dp2lo(L0.w, lb); ad[3] = dp2hi(L0.w, lb);
        ad[4] = dp2lo(L1.x, lb); ad[5] = dp2hi(L1.x, lb); ad[6] = dp2lo(L1.y, lb); ad[7] = dp2hi(L1.y, lb);
        ad[8] = dp2lo(L1.z, lb); ad[9] = dp2hi(L1.z, lb); ad[10] = dp2lo(L1.w, lb); ad[11] = dp2hi(L1.w, lb);
        unsigned sA = __byte_perm(L0.x, 0x64646464u, 0x4140), nB = __byte_perm(L0.x, 0xE4E4E4E4u, 0x4342);
        float dA = blo_v(L0.y), dB = bhi_v(L0.y);
        lp += 16 * 32;
        L0 = ldg_na(lp); L1 = ldg_na(lp + LSTR);
        float acc0[4] = {0, 0, 0, 0}, acc1[4] = {0, 0, 0, 0};
        if (!__any_sync(~0u, ad[10] != dummy)) {
            if (__any_sync(~0u, ad[9] != dummy)) p3_steps<10>(acc0, acc1, ad, sA, nB);
            else p3_steps<9>(acc0, acc1, ad, sA, nB);
        } else if (!__any_sync(~0u, ad[11] != dummy)) {
            p3_steps<11>(acc0, acc1, ad, sA, nB);
        } else {
            const bool longer = (sA & 0x80) || anyovf;
            sA &= ~0x80u;
            p3_steps<12>(acc0, acc1, ad, sA, nB);
            if (__any_sync(~0u, longer)) {
                uint4 C2 = ldg_na(lp - 16 * 32 + 2 * LSTR);
                unsigned e2[4] = {C2.x, C2.y, C2.z, C2.w};
#pragma unroll
                for (int s = 12; s < 20; s++) p3_step(acc0, acc1, (s & 1) ? dp2hi(e2[(s - 12) >> 1], lb) : dp2lo(e2[(s - 12) >> 1], lb), s, sA, nB);
                if (anyovf) {
                    float4 e = p3_overflow(sc, grp0 + 16 * it, sb + OFF_S);
                    float s0 = e.x + e.z, s1 = e.y + e.w;
                    for (int k = 4; k < 32; k <<= 1) {
                        float u0 = __shfl_down_sync(~0u, s0, k), u1 = __shfl_down_sync(~0u, s1, k);
                        if (lane + k < 32) { s0 += u0; s1 += u1; }
                    }
                    acc0[0] += s0; acc0[1] += s1; acc0[2] += s0 - e.x; acc0[3] += s1 - e.y;
                }
            }
        }
        float c0 = acc0[0] + acc1[0], c1 = acc0[1] + acc1[1], c2 = acc0[2] + acc1[2], c3 = acc0[3] + acc1[3];
        float n0 = __shfl_down_sync(~0u, c0, 4), n1 = __shfl_down_sync(~0u, c1, 4);
        float o0 = c0 - c2, o1 = c1 - c3, o2 = fmaf(n0, zmask, c2), o3 = fmaf(n1, zmask, c3);
        if (it == 6) mbar_wait(bar_t);
        asm volatile("stmatrix.sync.aligned.m8n8.x2.shared.b16 [%0],{%1,%2};" ::"r"(stg), "r"(pack2(o0 * dA, o1 * dA)), "r"(pack2(o2 * dB, o3 * dB)) : "memory");
        __syncwarp();
        asm volatile("{.reg .pred p; setp.eq.u32 p,%1,0; @p mbarrier.arrive.shared.b64 _,[%0];}" ::"r"(bar_rd + 8 * it), "r"(lane) : "memory");
        stg += 4096;
    }
    STAMP(12);
    }
}

typedef CUresult (*EncodeFn)(CUtensorMap*, CUtensorMapDataType, cuuint32_t, void*, const cuuint64_t*, const cuuint64_t*,
                             const cuuint32_t*, const cuuint32_t*, CUtensorMapInterleave, CUtensorMapSwizzle,
                             CUtensorMapL2promotion, CUtensorMapFloatOOBfill);

}

extern "C" void kernel_launch(void* const* d_in, const int* in_sizes, int n_in, void* d_out, int out_size) {
    (void)in_sizes; (void)n_in; (void)out_size;
    static EncodeFn enc = nullptr;
    static void* scratch = nullptr;
    if (!enc) {
        cudaGetSymbolAddress(&scratch, g_scratch);
        void* fn = nullptr;
        cudaDriverEntryPointQueryResult qr;
        cudaGetDriverEntryPoint("cuTensorMapEncodeTiled", &fn, cudaEnableDefault, &qr);
        enc = (EncodeFn)fn;
        cudaFuncSetAttribute(exphormer_kernel, cudaFuncAttributeMaxDynamicSharedMemorySize, SMEM_BYTES);
    }
    CUtensorMap tm_x, tm_wl, tm_wv, tm_ot, tm_o256, tm_o16;
    auto mk = [&](CUtensorMap* tm, void* p, int rows, int bc, int br, CUtensorMapSwizzle sw, CUtensorMapL2promotion pr) {
        cuuint64_t gd[2] = {256, (cuuint64_t)rows}, gs[1] = {512};
        cuuint32_t es[2] = {1, 1}, bx[2] = {(cuuint32_t)bc, (cuuint32_t)br};
        enc(tm, CU_TENSOR_MAP_DATA_TYPE_BFLOAT16, 2, p, gd, gs, bx, es, CU_TENSOR_MAP_INTERLEAVE_NONE, sw, pr, CU_TENSOR_MAP_FLOAT_OOB_FILL_NONE);
    };
    for (int i = 0; i < 2; i++) {
        cuuint64_t gd[3] = {64, 256, 4}, gs[2] = {512, 128};
        cuuint32_t es[3] = {1, 1, 1}, bx[3] = {64, 64, 4};
        enc(i ? &tm_wv : &tm_wl, CU_TENSOR_MAP_DATA_TYPE_BFLOAT16, 3, d_in[i ? 9 : 6], gd, gs, bx, es, CU_TENSOR_MAP_INTERLEAVE_NONE,
            CU_TENSOR_MAP_SWIZZLE_128B, CU_TENSOR_MAP_L2_PROMOTION_L2_128B, CU_TENSOR_MAP_FLOAT_OOB_FILL_NONE);
    }
    mk(&tm_x, d_in[0], NN, 64, TILE, CU_TENSOR_MAP_SWIZZLE_128B, CU_TENSOR_MAP_L2_PROMOTION_L2_128B);
    mk(&tm_ot, d_out, NN, 64, TILE, CU_TENSOR_MAP_SWIZZLE_128B, CU_TENSOR_MAP_L2_PROMOTION_NONE);
    mk(&tm_o256, d_out, NN, 8, 256, CU_TENSOR_MAP_SWIZZLE_NONE, CU_TENSOR_MAP_L2_PROMOTION_NONE);
    mk(&tm_o16, d_out, NN, 8, 16, CU_TENSOR_MAP_SWIZZLE_NONE, CU_TENSOR_MAP_L2_PROMOTION_NONE);
    exphormer_kernel<<<NCTA, 640, SMEM_BYTES>>>(
        (const uint4*)d_in[0], (const uint4*)d_in[2], (const uint4*)d_in[1], (const uint4*)d_in[7], (const uint4*)d_in[8], (const int*)d_in[3],
        (const int*)d_in[4], (Scratch*)scratch, (const uint4*)d_in[5], (const uint4*)d_in[9],
        tm_x, tm_wl, tm_wv, tm_ot, tm_o256, tm_o16);
}
```

```cpp
#include <cuda_runtime.h>
#include <cuda_bf16.h>
#include <cuda.h>
#include <stdint.h>

namespace {

constexpr int NN = 10000, NE = 160000, NEE = 40000;
constexpr int TILE = 80, NT = 125, NCTA = 128, NG = 625, EPC = 1280;
constexpr int CELL = 32;
constexpr int LCAP = 80;
constexpr int OVCAP = EPC + NT * CELL;
#define XD0 600
#define XD1 1200
#define XD2 0
constexpr unsigned DUMMY2 = 1250u | (1250u << 16);

constexpr unsigned sb = 1024;
constexpr int OFF_S = 0;
constexpr int OFF_R = 163840;
constexpr int OFF_BAR = OFF_R;
constexpr int OFF_MISC = OFF_R + 256;
constexpr int OFF_DIS = OFF_R + 320;
constexpr int OFF_PROF = OFF_R + 512;
constexpr int OFF_EIDX = OFF_R + 1024;
constexpr int OFF_ALPHA = OFF_R + 1024;
constexpr int OFF_STG = OFF_R + 2048;
constexpr int OFF_CNT1 = OFF_R + 2560;
constexpr int OFF_CNT2 = OFF_R + 3072;
constexpr int OFF_MAIL = OFF_R + 5760;
constexpr int OFF_IMG = OFF_MAIL + 9216;
constexpr int OFF_T = OFF_R + 26624;
constexpr int SMEM_BYTES = OFF_T + 40960;
static_assert(SMEM_BYTES <= 232448 && OFF_T % 1024 == 0 && OFF_STG + 6 * 4096 == OFF_T && OFF_IMG + 10752 <= OFF_T, "smem");
constexpr unsigned bar_fill = sb + OFF_BAR, bar_t = bar_fill + 8, bar_mail = bar_fill + 16, bar_c = bar_fill + 24, bar_rd = bar_fill + 32,
                   bar_full = bar_fill + 128;
constexpr int LSTR = (NG + 16) * 32;

struct __align__(256) Scratch {
    uint4 mimg[8192];
    uint4 hs[32 * NN];
    uint4 mail[NT * 1024];
    uint4 lists[3 * LSTR];
    unsigned ovfn[NCTA];
    unsigned bar[32];
    unsigned ovf[NCTA * OVCAP];
};
__device__ Scratch g_scratch;
#define STAMPT(th, i)
#define STAMP(i) STAMPT(64, i)
#define STAMP2(i) STAMPT(416, i)

__device__ __forceinline__ void bar_arrive(unsigned* p) {
    asm volatile("red.release.gpu.global.add.u32 [%0],1;" ::"l"(p) : "memory");
}
__device__ __forceinline__ void bar_poll(const unsigned* p, unsigned target) {
    unsigned v;
    int lim = 0;
    do {
        asm volatile("ld.acquire.gpu.global.u32 %0,[%1];" : "=r"(v) : "l"(p) : "memory");
        if (++lim > (1 << 22)) __trap();
    } while ((int)(v - target) < 0);
}
__device__ __forceinline__ unsigned bar_poll2(const unsigned* p, unsigned target) {
    unsigned long long v;
    int lim = 0;
    do {
        asm volatile("ld.acquire.gpu.global.u64 %0,[%1];" : "=l"(v) : "l"(p) : "memory");
        if (++lim > (1 << 22)) __trap();
    } while ((int)((unsigned)v - target) < 0);
    unsigned f = (unsigned)(v >> 32);
    return (f & ~3u) == target ? f & 3 : 0;
}
__device__ __noinline__ void raise_flag(unsigned* p, unsigned target, unsigned bit) {
    unsigned old = atomicCAS(p, 0, 0), seen;
    do {
        seen = old;
        old = atomicCAS(p, seen, ((seen & ~3u) == target ? seen : target) | bit);
    } while (old != seen);
}
__device__ __forceinline__ void mbar_wait(unsigned a) {
    asm volatile("{.reg .pred p; .reg .u32 n;\n"
                 "mov.u32 n,0x400000;\n"
                 "W: mbarrier.try_wait.parity.shared.b64 p,[%0],0;\n"
                 "add.u32 n,n,-1; setp.ne.and.u32 p,n,0,!p; @p bra W;}" ::"r"(a) : "memory");
}
__device__ __forceinline__ bool elect() {
    unsigned r;
    asm volatile("{.reg .pred p; elect.sync _|p,0xFFFFFFFF; selp.u32 %0,1,0,p;}" : "=r"(r));
    return r;
}
__device__ __forceinline__ uint4 ldg_na(const uint4* p) {
    uint4 v;
    asm volatile("ld.global.L1::no_allocate.v4.u32 {%0,%1,%2,%3},[%4];" : "=r"(v.x), "=r"(v.y), "=r"(v.z), "=r"(v.w) : "l"(p) : "memory");
    return v;
}
__device__ __forceinline__ uint4 lds128(unsigned a) {
    uint4 v;
    asm volatile("ld.shared.v4.u32 {%0,%1,%2,%3},[%4];" : "=r"(v.x), "=r"(v.y), "=r"(v.z), "=r"(v.w) : "r"(a) : "memory");
    return v;
}
__device__ __forceinline__ void sts128(unsigned a, uint4 v) {
    asm volatile("st.shared.v4.u32 [%0],{%1,%2,%3,%4};" ::"r"(a), "r"(v.x), "r"(v.y), "r"(v.z), "r"(v.w) : "memory");
}
__device__ __forceinline__ void sts32(unsigned a, unsigned v) { asm volatile("st.shared.u32 [%0],%1;" ::"r"(a), "r"(v) : "memory"); }
__device__ __forceinline__ unsigned lds32(unsigned a) { unsigned v; asm volatile("ld.shared.u32 %0,[%1];" : "=r"(v) : "r"(a) : "memory"); return v; }
__device__ __forceinline__ unsigned atoms_add(unsigned a, unsigned k) { unsigned v; asm volatile("atom.shared.add.u32 %0,[%1],%2;" : "=r"(v) : "r"(a), "r"(k) : "memory"); return v; }
__device__ __forceinline__ unsigned bitsel(unsigned a, unsigned b, unsigned m) { unsigned r; asm("lop3.b32 %0,%1,%2,%3,0xE4;" : "=r"(r) : "r"(a), "r"(b), "r"(m)); return r; }
__device__ __forceinline__ unsigned atoms_inc(unsigned a) { unsigned v; asm volatile("atom.shared.add.u32 %0,[%1],1;" : "=r"(v) : "r"(a) : "memory"); return v; }
__device__ __forceinline__ float blo(unsigned v) { return __uint_as_float(v << 16); }
__device__ __forceinline__ float bhi(unsigned v) { return __uint_as_float(v & 0xFFFF0000u); }
__device__ __forceinline__ float blo_v(unsigned v) { float r; asm volatile("shl.b32 %0,%1,16;" : "=f"(r) : "r"(v)); return r; }
__device__ __forceinline__ float bhi_v(unsigned v) { float r; asm volatile("and.b32 %0,%1,0xFFFF0000;" : "=f"(r) : "r"(v)); return r; }
__device__ __forceinline__ unsigned pack2(float lo, float hi) { unsigned r; asm("cvt.rn.bf16x2.f32 %0,%1,%2;" : "=r"(r) : "f"(hi), "f"(lo)); return r; }

__device__ __forceinline__ void mma16816(float* d, unsigned a0, unsigned a1, unsigned a2, unsigned a3, unsigned b0, unsigned b1) {
    asm volatile("mma.sync.aligned.m16n8k16.row.col.f32.bf16.bf16.f32 {%0,%1,%2,%3},{%4,%5,%6,%7},{%8,%9},{%0,%1,%2,%3};"
                 : "+f"(d[0]), "+f"(d[1]), "+f"(d[2]), "+f"(d[3]) : "r"(a0), "r"(a1), "r"(a2), "r"(a3), "r"(b0), "r"(b1));
}
#define R10(b) "+f"(d[b + 0]), "+f"(d[b + 1]), "+f"(d[b + 2]), "+f"(d[b + 3]), "+f"(d[b + 4]), "+f"(d[b + 5]), "+f"(d[b + 6]), "+f"(d[b + 7]), "+f"(d[b + 8]), "+f"(d[b + 9])
__device__ __forceinline__ void wg80(float* d, unsigned da, unsigned db, int sc) {
    asm volatile("{.reg .pred p; .reg .b64 a, b; setp.ne.b32 p,%42,0; mov.b64 a,{%40,%43}; mov.b64 b,{%41,%43};\n"
                 "wgmma.mma_async.sync.aligned.m64n80k16.f32.bf16.bf16 "
                 "{%0,%1,%2,%3,%4,%5,%6,%7,%8,%9,%10,%11,%12,%13,%14,%15,%16,%17,%18,%19,%20,%21,%22,%23,%24,%25,%26,%27,%28,%29,%30,%31,%32,%33,%34,%35,%36,%37,%38,%39},"
                 "a,b,p,1,1,1,0;}"
                 : R10(0), R10(10), R10(20), R10(30) : "r"(da), "r"(db), "r"(sc), "r"(0x40000040));
}
__device__ __forceinline__ void wg_fence() { asm volatile("wgmma.fence.sync.aligned;" ::: "memory"); }
__device__ __forceinline__ void wg_commit() { asm volatile("wgmma.commit_group.sync.aligned;" ::: "memory"); }
template <int N> __device__ __forceinline__ void wg_wait() { asm volatile("wgmma.wait_group.sync.aligned %0;" ::"n"(N) : "memory"); }
__device__ __forceinline__ void bulk_g2s(unsigned dst, const void* src, unsigned bytes, unsigned bar) {
    asm volatile("cp.async.bulk.shared::cluster.global.mbarrier::complete_tx::bytes [%0],[%1],%2,[%3];" ::"r"(dst), "l"(src), "r"(bytes), "r"(bar) : "memory");
}
__device__ __forceinline__ void fence_async_smem() { asm volatile("fence.proxy.async.shared::cta;" ::: "memory"); }
__device__ __forceinline__ void fence_async_gmem() { asm volatile("fence.proxy.async.global;" ::: "memory"); }

__device__ __forceinline__ unsigned hsat(unsigned a, unsigned c) { unsigned r; asm("add.sat.f16x2 %0,%1,%2;" : "=r"(r) : "r"(a), "r"(c)); return r; }
__device__ __forceinline__ unsigned hset(unsigned a, unsigned c) { unsigned r; asm("set.le.f16x2.f16x2 %0,%1,%2;" : "=r"(r) : "r"(a), "r"(c)); return r; }
__host__ __device__ constexpr unsigned h2c(int v) { return (0x6400u | v) | ((0x6400u | v) << 16); }
__device__ __forceinline__ unsigned dp2lo(unsigned a, unsigned c) { unsigned r; asm("dp2a.lo.u32.u32 %0,%1,%2,%3;" : "=r"(r) : "r"(a), "r"(0x80000080u), "r"(c)); return r; }
__device__ __forceinline__ unsigned dp2hi(unsigned a, unsigned c) { unsigned r; asm("dp2a.hi.u32.u32 %0,%1,%2,%3;" : "=r"(r) : "r"(a), "r"(0x80000080u), "r"(c)); return r; }
__device__ __forceinline__ void p3_step(float* acc0, float* acc1, unsigned addr, int s, unsigned sA, unsigned nB) {
    unsigned b0, b1, b2, b3;
    asm volatile("ldmatrix.sync.aligned.m8n8.x4.trans.shared.b16 {%0,%1,%2,%3},[%4];" : "=r"(b0), "=r"(b1), "=r"(b2), "=r"(b3) : "r"(addr));
    mma16816(acc0, hset(sA, h2c(4 * s + 0)), hsat(nB, h2c(4 * s + 1)), hset(sA, h2c(4 * s + 1)), hsat(nB, h2c(4 * s + 2)), b0, b1);
    mma16816(acc1, hset(sA, h2c(4 * s + 2)), hsat(nB, h2c(4 * s + 3)), hset(sA, h2c(4 * s + 3)), hsat(nB, h2c(4 * s + 4)), b2, b3);
}
template <int NS> __device__ __forceinline__ void p3_steps(float* acc0, float* acc1, const unsigned* ad, unsigned sA, unsigned nB) {
#pragma unroll
    for (int s = 0; s < NS; s++) p3_step(acc0, acc1, ad[s], s, sA, nB);
}
__device__ __noinline__ float4 p3_overflow(const Scratch* sc, int grp, unsigned sS) {
    int lane = threadIdx.x & 31, g = lane >> 2, t = lane & 3;
    float4 r = make_float4(0.f, 0.f, 0.f, 0.f);
    for (int c = 0; c < NT; c++) {
        int n = (int)__ldcg(&sc->ovfn[c]);
        for (int i0 = 0; i0 < n; i0 += 32) {
            unsigned e = (i0 + lane < n) ? __ldcg(&sc->ovf[c * OVCAP + i0 + lane]) : 0xFFFFFFFFu;
            unsigned m = __ballot_sync(~0u, (int)(e >> 18) == grp);
            while (m) {
                int j = __ffs(m) - 1;
                m &= m - 1;
                unsigned ee = __shfl_sync(~0u, e, j);
                int row = (ee >> 14) & 15;
                row ^= row >> 3;
                unsigned v = lds32(sS + (ee & 0x3FFF) * 16 + t * 4);
                if ((row >> 1) == g) {
                    if (!(row & 1)) { r.x += blo(v); r.y += bhi(v); } else { r.z += blo(v); r.w += bhi(v); }
                }
            }
        }
    }
    const float k = 1.f / 128.f;
    r.x *= k; r.y *= k; r.z *= k; r.w *= k;
    return r;
}
__device__ __forceinline__ void unpack8(float* f, uint4 v) {
    f[0] = blo(v.x); f[1] = bhi(v.x); f[2] = blo(v.y); f[3] = bhi(v.y); f[4] = blo(v.z); f[5] = bhi(v.z); f[6] = blo(v.w); f[7] = bhi(v.w);
}
__device__ __forceinline__ void vec_mat(float* o, const float* v, const uint4* __restrict__ W, int lane) {
    for (int k = 0; k < 8; k++) o[k] = 0.f;
    for (int l = 0; l < 32; l++) {
#pragma unroll
        for (int i = 0; i < 8; i++) {
            float a = __shfl_sync(~0u, v[i], l), wr[8];
            unpack8(wr, W[(l * 8 + i) * 32 + lane]);
#pragma unroll
            for (int k = 0; k < 8; k++) o[k] = fmaf(a, wr[k], o[k]);
        }
    }
}
__device__ __noinline__ uint4 attn_generic(int node, const uint4* __restrict__ x, const int* __restrict__ esrc, const int* __restrict__ edst,
                                           const uint4* __restrict__ wq, const uint4* __restrict__ wk, const uint4* __restrict__ wv) {
    int lane = threadIdx.x & 31;
    float xr[8], q[8], y[8], o[8];
    unpack8(xr, x[node * 32 + lane]);
    vec_mat(q, xr, wq, lane);
    for (int l = 0; l < 32; l++) {
#pragma unroll
        for (int i = 0; i < 8; i++) {
            float wr[8], p = 0.f;
            unpack8(wr, wk[(l * 8 + i) * 32 + lane]);
#pragma unroll
            for (int k = 0; k < 8; k++) p = fmaf(q[k], wr[k], p);
            for (int k = 16; k; k >>= 1) p += __shfl_xor_sync(~0u, p, k);
            if (lane == l) y[i] = p;
        }
    }
    for (int k = 0; k < 8; k++) o[k] = 0.f;
    float den = 0.f;
    for (int i0 = 0; i0 < NEE; i0 += 32) {
        unsigned m = __ballot_sync(~0u, edst[i0 + lane] == node);
        while (m) {
            int j = __ffs(m) - 1;
            m &= m - 1;
            float gq[8], p = 0.f;
            unpack8(gq, x[esrc[i0 + j] * 32 + lane]);
#pragma unroll
            for (int k = 0; k < 8; k++) p = fmaf(y[k], gq[k], p);
            for (int k = 16; k; k >>= 1) p += __shfl_xor_sync(~0u, p, k);
            float ex = __expf(p * 0.0625f);
            den += ex;
#pragma unroll
            for (int k = 0; k < 8; k++) o[k] = fmaf(ex, gq[k], o[k]);
        }
    }
    float inv = 1.f / (den + 1e-9f);
    for (int k = 0; k < 8; k++) o[k] *= inv;
    vec_mat(q, o, wv, lane);
    return make_uint4(pack2(q[0], q[1]), pack2(q[2], q[3]), pack2(q[4], q[5]), pack2(q[6], q[7]));
}

__device__ __forceinline__ unsigned hfma2(unsigned a, unsigned b, unsigned c) { unsigned r; asm("fma.rn.bf16x2 %0,%1,%2,%3;" : "=r"(r) : "r"(a), "r"(b), "r"(c)); return r; }
__device__ __forceinline__ unsigned hmul2(unsigned a, unsigned b) { unsigned r; asm("mul.rn.bf16x2 %0,%1,%2;" : "=r"(r) : "r"(a), "r"(b)); return r; }

__device__ __forceinline__ unsigned tile_addr(int n, unsigned chunk) { return sb + OFF_T + (chunk >> 3) * 10240 + n * 128 + (((chunk ^ n) & 7) << 4); }
__device__ __forceinline__ void attn_scores(float* v, bool mine, bool par, const uint4* gv, unsigned yaddr) {
    const uint4 y = lds128(yaddr);
    float c[4] = {0, 0, 0, 0}, e[4] = {0, 0, 0, 0};
    mma16816(c, gv[0].x, gv[1].x, gv[0].y, gv[1].y, y.x, y.y);
    mma16816(e, gv[2].x, gv[3].x, gv[2].y, gv[3].y, y.x, y.y);
    mma16816(c, gv[0].z, gv[1].z, gv[0].w, gv[1].w, y.z, y.w);
    mma16816(e, gv[2].z, gv[3].z, gv[2].w, gv[3].w, y.z, y.w);
    if (mine) { v[0] = par ? c[1] : c[0]; v[1] = par ? c[3] : c[2]; v[2] = par ? e[1] : e[0]; v[3] = par ? e[3] : e[2]; }
}
__device__ __forceinline__ void attn_softmax(const float* v, const float* u, unsigned lane, unsigned delta, unsigned alsm) {
    const bool hA = lane & 4, hB = lane & 8, hC = lane & 16;
    float a[4];
#pragma unroll
    for (int e = 0; e < 4; e++) a[e] = (hA ? u[e] : v[e]) + __shfl_xor_sync(~0u, hA ? v[e] : u[e], 4);
    float b0 = (hB ? a[1] : a[0]) + __shfl_xor_sync(~0u, hB ? a[0] : a[1], 9);
    float b1 = (hB ? a[3] : a[2]) + __shfl_xor_sync(~0u, hB ? a[2] : a[3], 9);
    float sc = (hC ? b1 : b0) + __shfl_xor_sync(~0u, hC ? b0 : b1, 18);
    float ex = exp2f(sc);
    float den = ex + __shfl_xor_sync(~0u, ex, 9);
    den += __shfl_xor_sync(~0u, den, 18);
    float al = __fdividef(ex, den + 1e-9f);
    sts32(alsm + (hA ? 4 + delta : delta) * 16 + (lane >> 3) * 4, pack2(al, al));
    __syncwarp();
}
__device__ __forceinline__ void attn_mix(const uint4* gv, unsigned al, unsigned oaddr) {
    const uint4 a = lds128(al);
    uint4 o;
    o.x = hfma2(a.w, gv[3].x, hfma2(a.z, gv[2].x, hfma2(a.y, gv[1].x, hmul2(a.x, gv[0].x))));
    o.y = hfma2(a.w, gv[3].y, hfma2(a.z, gv[2].y, hfma2(a.y, gv[1].y, hmul2(a.x, gv[0].y))));
    o.z = hfma2(a.w, gv[3].z, hfma2(a.z, gv[2].z, hfma2(a.y, gv[1].z, hmul2(a.x, gv[0].z))));
    o.w = hfma2(a.w, gv[3].w, hfma2(a.z, gv[2].w, hfma2(a.y, gv[1].w, hmul2(a.x, gv[0].w))));
    sts128(oaddr, o);
}
__device__ __forceinline__ void pack_acc(unsigned* pk, const float* d) {
#pragma unroll
    for (int j = 0; j < 20; j++) pk[j] = pack2(d[2 * j], d[2 * j + 1]);
}
__device__ __forceinline__ void acc_to_tile(const unsigned* pk, int w, int lane) {
    const unsigned a = sb + OFF_T + (w >> 2) * 10240 + (lane >> 4) * 1024 + (lane & 7) * 128 + (((2 * (w & 3) + ((lane >> 3) & 1)) ^ (lane & 7)) << 4);
#pragma unroll
    for (int j = 0; j < 5; j++)
        asm volatile("stmatrix.sync.aligned.m8n8.x4.trans.shared.b16 [%0],{%1,%2,%3,%4};" ::"r"(a + j * 2048), "r"(pk[4 * j]), "r"(pk[4 * j + 1]), "r"(pk[4 * j + 2]), "r"(pk[4 * j + 3]) : "memory");
}
__device__ __forceinline__ unsigned movm(unsigned a) { unsigned d; asm volatile("movmatrix.sync.aligned.m8n8.trans.b16 %0,%1;" : "=r"(d) : "r"(a)); return d; }
__device__ __forceinline__ void tma_load2d(unsigned dst, const CUtensorMap* tm, int c0, int c1, unsigned bar) {
    asm volatile("cp.async.bulk.tensor.2d.shared::cluster.global.mbarrier::complete_tx::bytes [%0],[%1,{%3,%4}],[%2];"
                 ::"r"(dst), "l"(tm), "r"(bar), "r"(c0), "r"(c1) : "memory");
}
__device__ __forceinline__ void tma_load3d(unsigned dst, const CUtensorMap* tm, int row, unsigned bar) {
    asm volatile("cp.async.bulk.tensor.3d.shared::cluster.global.mbarrier::complete_tx::bytes [%0],[%1,{%4,%3,%4}],[%2];"
                 ::"r"(dst), "l"(tm), "r"(bar), "r"(row), "r"(0) : "memory");
}
__device__ __forceinline__ void cp16(unsigned dst, const void* src) { asm volatile("cp.async.cg.shared.global [%0],[%1],16;" ::"r"(dst), "l"(src) : "memory"); }
__device__ __forceinline__ void cp_commit() { asm volatile("cp.async.commit_group;" ::: "memory"); }
template <int N> __device__ __forceinline__ void cp_wait() { asm volatile("cp.async.wait_group %0;" ::"n"(N) : "memory"); }
__device__ __forceinline__ void nb_sync_id(int id, int n) { asm volatile("bar.sync %0,%1;" ::"r"(id), "r"(n) : "memory"); }
__device__ __forceinline__ void nb_arrive_id(int id, int n) { asm volatile("bar.arrive %0,%1;" ::"r"(id), "r"(n) : "memory"); }
template <int ID, int N> __device__ __forceinline__ void nb_sync() { asm volatile("bar.sync %0,%1;" ::"n"(ID), "n"(N) : "memory"); }
template <int ID, int N> __device__ __forceinline__ void nb_arrive() { asm volatile("bar.arrive %0,%1;" ::"n"(ID), "n"(N) : "memory"); }
__device__ __forceinline__ void mbar_init(unsigned a, int n) { asm volatile("mbarrier.init.shared.b64 [%0],%1;" ::"r"(a), "r"(n) : "memory"); }
__device__ __forceinline__ void mbar_expect(unsigned a, int n) { asm volatile("mbarrier.arrive.expect_tx.shared.b64 _,[%0],%1;" ::"r"(a), "r"(n) : "memory"); }
__device__ __forceinline__ void mbar_arrive(unsigned a) { asm volatile("mbarrier.arrive.shared.b64 _,[%0];" ::"r"(a) : "memory"); }

constexpr unsigned PADBIN = 2560, CU = 0x101;
__device__ __noinline__ void push_overflow(Scratch* sc, unsigned dst, unsigned src) {
    sc->ovf[blockIdx.x * OVCAP + atoms_inc(sb + OFF_MISC)] = (dst << 14) | src;
}
__device__ __noinline__ void bin_overflow4(Scratch* sc, uint4 v, uint4 h) {
    const unsigned e[4] = {v.x, v.y, v.z, v.w}, hh[4] = {h.x, h.y, h.z, h.w};
#pragma unroll
    for (int i = 0; i < 4; i++)
        if (hh[i] >= (LCAP + 16) * CU && e[i] < (PADBIN << 16))
            push_overflow(sc, blockIdx.x * TILE + ((e[i] >> 21) & ~3u) + ((e[i] >> 18) & 3), ((e[i] & 2047) << 3) | ((e[i] >> 20) & 7));
}
__device__ __forceinline__ void reds_add(unsigned a, unsigned k) { asm volatile("red.shared.add.u32 [%0],%1;" ::"r"(a), "r"(k) : "memory"); }
__device__ __forceinline__ void bulk_s2g(void* dst, unsigned src, unsigned bytes) {
    asm volatile("cp.async.bulk.global.shared::cta.bulk_group [%0],[%1],%2;" ::"l"(dst), "r"(src), "r"(bytes) : "memory");
}
__device__ __forceinline__ void tma_reduce(const CUtensorMap* tm, unsigned src, int c0, int c1) {
    asm volatile("cp.reduce.async.bulk.tensor.2d.global.shared::cta.add.tile.bulk_group [%0,{%2,%3}],[%1];" ::"l"(tm), "r"(src), "r"(c0), "r"(c1) : "memory");
}
#define EV(id) nb_arrive<id, 544>()
#define WAIT_EV(id) do { __syncwarp(); nb_sync<id, 544>(); } while (0)

__global__ void __launch_bounds__(640, 1)
exphormer_kernel(const uint4* __restrict__ x, const uint4* __restrict__ dst4, const uint4* __restrict__ src4,
                 const uint4* __restrict__ wq, const uint4* __restrict__ wk, const int* __restrict__ esrc,
                 const int* __restrict__ edst, Scratch* __restrict__ sc, const uint4* __restrict__ dis, const uint4* __restrict__ wv,
                 const __grid_constant__ CUtensorMap tm_x, const __grid_constant__ CUtensorMap tm_wl, const __grid_constant__ CUtensorMap tm_wv,
                 const __grid_constant__ CUtensorMap tm_ot, const __grid_constant__ CUtensorMap tm_o256, const __grid_constant__ CUtensorMap tm_o16) {
    extern __shared__ __align__(1024) unsigned char smem_raw[];
    const unsigned tid = threadIdx.x, lane = tid & 31, g = lane >> 2, t = lane & 3;
    const unsigned b = blockIdx.x;
    const bool rowcta = b < NT;
    const int slice = b >> 2, range = b & 3;
    const int g0 = (range * NG) >> 2, g1 = ((range + 1) * NG) >> 2;
    STAMP(0);

    if (tid >= 544) {
        const unsigned ht = tid - 544;
        if (ht < 32) {
            nb_sync<2, 480>();
            if (lane == 0) bar_arrive(&sc->bar[0]);
            __syncwarp();
            STAMPT(544, 47);
        }
        nb_sync<13, 128>();
        if (rowcta) {
            const unsigned pad = (PADBIN + 4 * lane) << 16;
            if (ht < 76) sts128(sb + OFF_MAIL + 8000 + ht * 16, make_uint4(pad, pad, pad, pad));
            nb_sync<1, 96>();
            mbar_wait(bar_mail);
            STAMPT(576, 16);
            for (unsigned i = ht; i < 500; i += 96) {
                if (lds32(sb + OFF_IMG + i * 16) < (PADBIN << 16)) {
                    const uint4 v = lds128(sb + OFF_IMG + i * 16);
                    const unsigned k = atoms_inc(sb + OFF_MISC + 4);
                    if (k < 76) sts128(sb + OFF_MAIL + 8000 + k * 16, v);
                    else bin_overflow4(sc, v, make_uint4(~0u, ~0u, ~0u, ~0u));
                }
            }
            nb_sync<1, 96>();
#pragma unroll
            for (int k = 0; k < 5; k++) sts128(sb + OFF_IMG + (ht >> 5) * 4096 + k * 512 + lane * 16, make_uint4(DUMMY2, DUMMY2, DUMMY2, DUMMY2));
#pragma unroll 2
            for (int k = 0; k < 6; k++) {
                const uint4 e = lds128(sb + OFF_MAIL + (ht + k * 96) * 16);
                reds_add(sb + OFF_CNT2 + (e.x >> 16), CU); reds_add(sb + OFF_CNT2 + (e.y >> 16), CU);
                reds_add(sb + OFF_CNT2 + (e.z >> 16), CU); reds_add(sb + OFF_CNT2 + (e.w >> 16), CU);
            }
            nb_sync<1, 96>();
            STAMPT(576, 17);
            for (unsigned G = ht >> 5; G < 5; G += 3) {
                const unsigned ca = sb + OFF_CNT2 + G * 512 + lane * 16;
                const uint4 c = lds128(ca);
                const unsigned dp = hmul2(lds32(sb + OFF_DIS + (G * 8 + g) * 4), 0x43004300u);
                const bool sw = lane >= 16;
                unsigned s1 = sw ? c.y : c.x, s2 = c.x + c.y, s3 = s2 + (sw ? c.w : c.z), tot = s2 + c.z + c.w, inc = tot;
                unsigned u = __shfl_up_sync(~0u, inc, 8); if (lane >= 8) inc += u;
                u = __shfl_up_sync(~0u, inc, 16); if (sw) inc += u;
                const unsigned base = inc - tot;
                const unsigned p0 = min(base, LCAP * CU), p1 = min(base + s1, LCAP * CU), p2 = min(base + s2, LCAP * CU), p3 = min(base + s3, LCAP * CU);
                sts128(ca, make_uint4((sw ? p1 : p0) + 16 * CU, (sw ? p0 : p1) + 16 * CU, (sw ? p3 : p2) + 16 * CU, (sw ? p2 : p3) + 16 * CU));
                const unsigned word = __byte_perm(__byte_perm(p0, p1, 0x0040), __byte_perm(p2, p3, 0x0040), 0x5410);
                const unsigned wa = __shfl_sync(~0u, word, (g >> 1) * 8 + 2 * t), wb = __shfl_sync(~0u, word, (g >> 1) * 8 + 2 * t + 1);
                unsigned hdr = __byte_perm(wa, wb, (g & 1) ? 0x7362 : 0x5140);
                if (__any_sync(~0u, inc > 48 * CU)) hdr |= 0x80;
                asm volatile("st.shared.v2.u32 [%0],{%1,%2};" ::"r"(sb + OFF_IMG + G * 512 + lane * 16), "r"(hdr), "r"(__byte_perm(dp, dp, sw ? 0x1032 : 0x3210)) : "memory");
            }
            nb_sync<1, 96>();
#pragma unroll 2
            for (int k = 0; k < 6; k++) {
                const uint4 v = lds128(sb + OFF_MAIL + (ht + k * 96) * 16);
                const unsigned e[4] = {v.x, v.y, v.z, v.w};
                unsigned h[4];
#pragma unroll
                for (int i = 0; i < 4; i++) h[i] = atoms_add(sb + OFF_CNT2 + (e[i] >> 16), CU);
#pragma unroll
                for (int i = 0; i < 4; i++)
                    asm volatile("{.reg .pred p; setp.lt.u32 p,%2,%3; @p st.shared.u16 [%0],%1;}"
                                 ::"r"(sb + OFF_IMG + bitsel(h[i] >> 1, e[i] >> 16, 0x318E)), "h"((unsigned short)e[i]), "r"(h[i]), "n"((LCAP + 16) * CU) : "memory");
                if (__builtin_expect(max(max((int)h[0], (int)h[1]), max((int)h[2], (int)h[3])) >= (int)((LCAP + 16) * CU), 0))
                    bin_overflow4(sc, v, make_uint4(h[0], h[1], h[2], h[3]));
            }
            fence_async_smem();
            nb_sync<1, 96>();
            STAMPT(576, 18);
        }
        if (ht < 32 && elect()) {
            if (rowcta) {
                for (int c = 0; c < 3; c++) bulk_s2g(sc->lists + (c * LSTR + b * 160), sb + OFF_IMG + c * 4096, 2560);
                asm volatile("cp.async.bulk.commit_group;" ::: "memory");
                const unsigned novf = lds32(sb + OFF_MISC), bad = lds32(sb + OFF_MISC + 20);
                sc->ovfn[b] = novf;
                if (__builtin_expect(novf | bad, 0)) raise_flag(&sc->bar[5], lds32(sb + OFF_MISC + 24), (novf ? 1 : 0) | (bad ? 2 : 0));
                asm volatile("cp.async.bulk.wait_group 0;" ::: "memory");
                fence_async_gmem();
            }
            bar_arrive(&sc->bar[4]);
            STAMPT(544, 19);
            sts32(sb + OFF_MISC + 28, bar_poll2(&sc->bar[4], lds32(sb + OFF_MISC + 24)));
            mbar_arrive(bar_c);
            STAMPT(544, 23);
        }
    } else if (tid >= 512) {
        const bool one = elect();
        auto load_xl = [&](int i) {
            mbar_expect(bar_full + 8 * i, 32768 + 10240);
            tma_load2d(sb + OFF_T + i * 10240, &tm_x, i * 64, b * TILE, bar_full + 8 * i);
            tma_load3d(sb + OFF_S + i * 32768, &tm_wl, i * 64, bar_full + 8 * i);
        };
        auto load_m = [&](int i, int slot) {
            mbar_expect(bar_full + 32 + 8 * i, 32768);
            bulk_g2s(sb + OFF_S + slot * 32768, sc->mimg + i * 2048, 32768, bar_full + 32 + 8 * i);
        };
        auto load_v = [&](int i, int slot) {
            mbar_expect(bar_full + 64 + 8 * i, 32768);
            tma_load3d(sb + OFF_S + slot * 32768, &tm_wv, i * 64, bar_full + 64 + 8 * i);
        };
        const char* hsl = (const char*)(sc->hs + slice * NN);
        auto fill = [&](int slot) { bulk_g2s(sb + OFF_S + slot * 32768, hsl + slot * 32768, slot == 4 ? NN * 16 - 4 * 32768 : 32768, bar_fill); };
        const unsigned t0 = clock();
        unsigned target = 0;
        if (one) {
            for (int i = 0; i < 2; i++) mbar_init(bar_full + 8 * i, 1);
            asm volatile("fence.mbarrier_init.release.cluster;" ::: "memory");
            while ((unsigned)clock() - t0 < XD0) {}
            if (rowcta) load_xl(0);
            STAMPT(512, 41);
            asm volatile("ld.relaxed.gpu.global.u32 %0,[%1];" : "=r"(target) : "l"(&sc->bar[1]) : "memory");
            for (int i = 2; i < 12; i++) mbar_init(bar_full + 8 * i, 1);
            for (int i = 0; i < 4; i++) mbar_init(bar_fill + 8 * i, 1);
            for (int i = 0; i < 10; i++) mbar_init(bar_rd + 8 * i, i < 9 ? 16 : g1 - g0 - 144);
            asm volatile("fence.mbarrier_init.release.cluster;" ::: "memory");
            if ((unsigned)__cvta_generic_to_shared(smem_raw) != sb) __trap();
            while ((unsigned)clock() - t0 < XD1) {}
            if (rowcta) load_xl(1);
            target = (target & ~(NCTA - 1)) + NCTA;
            sts32(sb + OFF_MISC + 24, target);
            mbar_expect(bar_fill, NN * 16);
        }
        __syncwarp();
        nb_arrive<3, 544>();
        if (rowcta) {
            if (one) {
                if (XD2) { while ((unsigned)clock() - t0 < XD2 + 1) {} } else mbar_wait(bar_full);
                load_xl(2);
                STAMPT(512, 52);
                mbar_wait(bar_full + (XD2 ? 0 : 8)); load_xl(3);
                STAMPT(512, 53);
                bar_poll(&sc->bar[0], target);
                STAMPT(512, 48);
                fence_async_gmem();
                mbar_expect(bar_mail, 16000);
                bulk_g2s(sb + OFF_MAIL, sc->mail + b * 1024, 8000, bar_mail);
                bulk_g2s(sb + OFF_IMG, sc->mail + (b * 1024 + 512), 8000, bar_mail);
            }
            __syncwarp();
            nb_arrive<13, 128>();
            WAIT_EV(5); if (one) { load_m(0, 0); load_m(1, 1); }
            WAIT_EV(6); if (one) load_m(2, 3);
            WAIT_EV(7); if (one) load_m(3, 0);
            WAIT_EV(12); if (one) bar_arrive(&sc->bar[2]);
            STAMPT(512, 24);
            WAIT_EV(14); if (one) load_v(0, 0);
            WAIT_EV(15);
            if (one) {
                fence_async_smem();
                load_v(1, 4); load_v(2, 2);
                bar_poll(&sc->bar[2], target);
                fence_async_gmem();
            }
            STAMPT(512, 25);
            WAIT_EV(2); if (one) { load_v(3, 1); fill(3); }
            WAIT_EV(4); if (one) fill(0);
            WAIT_EV(5); if (one) fill(4);
            WAIT_EV(6); if (one) fill(2);
            WAIT_EV(7); if (one) fill(1);
            WAIT_EV(12);
            if (one) {
#pragma unroll
                for (int kb = 0; kb < 4; kb++)
                    asm volatile("cp.async.bulk.tensor.2d.global.shared::cta.bulk_group [%0,{%2,%3}],[%1];"
                                 ::"l"(&tm_ot), "r"(sb + OFF_T + kb * 10240), "r"(kb * 64), "r"(b * TILE) : "memory");
                asm volatile("cp.async.bulk.commit_group;" ::: "memory");
                asm volatile("cp.async.bulk.wait_group 0;" ::: "memory");
                fence_async_gmem();
            }
        } else {
            nb_arrive<13, 128>();
            if (one) {
                bar_arrive(&sc->bar[2]);
                bar_poll(&sc->bar[2], target);
                fence_async_gmem(); fence_async_smem();
                for (int i = 0; i < 5; i++) fill(i);
            }
        }
        if (one) {
            bar_arrive(&sc->bar[1]);
            mbar_arrive(bar_t);
            STAMPT(512, 26);
            bar_poll(&sc->bar[1], target);
            fence_async_gmem();
            STAMPT(512, 27);
            for (int r = 0; r < 9; r++) {
                mbar_wait(bar_rd + 8 * r);
                fence_async_smem();
                tma_reduce(&tm_o256, sb + OFF_STG + r * 4096, slice * 8, (g0 + 16 * r) * 16);
            }
            mbar_wait(bar_rd + 72);
            fence_async_smem();
            for (int i = 144; i < g1 - g0; i++) tma_reduce(&tm_o16, sb + OFF_STG + i * 256, slice * 8, (g0 + i) * 16);
            asm volatile("cp.async.bulk.commit_group;" ::: "memory");
            asm volatile("cp.async.bulk.wait_group.read 0;" ::: "memory");
            STAMPT(512, 13);
        }
    } else {
    if (tid >= 192) {
        if (rowcta) {
            const unsigned bt = tid - 192;
            const uint4 ed = __ldg(dst4 + (b * 320 + bt)), es = __ldg(src4 + (b * 320 + bt));
            const unsigned pad = (PADBIN + 4 * ((bt & 3) + ((b * 4) & 28))) << 16;
#pragma unroll
            for (int k = 0; k < 4; k++) if (k < 3 || bt < 40) sts128(sb + OFF_MAIL + (bt + k * 320) * 16, make_uint4(pad, pad, pad, pad));
            const unsigned cz = bt < (512 + PADBIN) / 16 ? 0 : 0x80000000;
            if (bt < (512 + 2688) / 16) sts128(sb + OFF_CNT1 + bt * 16, make_uint4(cz, cz, cz, cz));
            if (bt == 319) sts128(sb + OFF_MISC, make_uint4(0, 0, 0, 0));
            unsigned z;
            asm volatile("{.reg .pred p; setp.eq.u32 p,%1,0xFFFFFFFF; bar.red.popc.u32 %0,4,320,p;}" : "=r"(z) : "r"(bt) : "memory");
            const unsigned dd[4] = {ed.x + z, ed.y + z, ed.z + z, ed.w + z}, ss[4] = {es.x + z, es.y + z, es.z + z, es.w + z};
            unsigned rk[4], ow[4];
#pragma unroll
            for (int i = 0; i < 4; i++) { ow[i] = dd[i] / TILE; rk[i] = atoms_inc(sb + OFF_CNT1 + ow[i] * 4); }
#pragma unroll
            for (int i = 0; i < 4; i++) {
                const unsigned dl = dd[i] - ow[i] * TILE;
                const unsigned e = bitsel(ss[i] << 20, bitsel(dl << 21, dl << 18, 0xFF800000u), 0x00700000u) + (ss[i] >> 3);
                asm volatile("{.reg .pred p; setp.lt.u32 p,%2,%3; @p st.shared.u32 [%0],%1;}" ::"r"(sb + OFF_MAIL + (ow[i] * CELL + rk[i]) * 4), "r"(e), "r"(rk[i]), "n"(CELL) : "memory");
            }
            if (__builtin_expect((rk[0] | rk[1] | rk[2] | rk[3]) >= CELL, 0)) {
#pragma unroll
                for (int i = 0; i < 4; i++) if (rk[i] >= CELL) push_overflow(sc, dd[i], ss[i]);
            }
            STAMPT(416, 44);
            nb_sync<4, 320>();
            uint4 mv[4];
            uint4* mp = sc->mail + ((bt >> 3) * 1024 + (bt & 4) * 128 + b * 4 + (bt & 3));
#pragma unroll
            for (int k = 0; k < 4; k++) if (k < 3 || bt < 40) mv[k] = lds128(sb + OFF_MAIL + (bt + k * 320) * 16);
            fence_async_smem();
#pragma unroll
            for (int k = 0; k < 4; k++) if (k < 3 || bt < 40) mp[k * 40960] = mv[k];
        }
        STAMPT(416, 45);
        nb_arrive<2, 480>();
    } else if (tid >= 64) {
        const unsigned fw = b >> 3, hq = b & 7, q = (tid >> 5) - 2, cq = q * 8 + t, mt = tid - 64;
        const uint4* pa = wq + ((16 * fw + g) * 32 + cq);
        const uint4* pb = wk + ((32 * hq + 8 * (g >> 1) + (g & 1)) * 32 + cq);
        const unsigned ma = sb + OFF_S + 4 * 32768 + 8192 + mt * 16;
        cp16(ma, pa); cp16(ma + 2048, pa + 4); cp16(ma + 4096, pa + 256); cp16(ma + 6144, pa + 260);
#pragma unroll
        for (int u = 0; u < 8; u++) cp16(ma + 8192 + u * 2048, pb + (u >> 1) * 64 + (u & 1) * 4);
        cp_commit();
        uint4 va[4], vb[8];
        STAMPT(64, 38);
        cp_wait<0>();
        STAMPT(64, 39);
#pragma unroll
        for (int u = 0; u < 4; u++) va[u] = lds128(ma + u * 2048);
#pragma unroll
        for (int u = 0; u < 8; u++) vb[u] = lds128(ma + 8192 + u * 2048);
        float c[4][4];
#pragma unroll
        for (int u = 0; u < 4; u++) {
            c[u][0] = c[u][1] = c[u][2] = c[u][3] = 0.f;
            mma16816(c[u], va[0].x, va[2].x, va[0].y, va[2].y, vb[2 * u].x, vb[2 * u].y);
            mma16816(c[u], va[0].z, va[2].z, va[0].w, va[2].w, vb[2 * u].z, vb[2 * u].w);
            mma16816(c[u], va[1].x, va[3].x, va[1].y, va[3].y, vb[2 * u + 1].x, vb[2 * u + 1].y);
            mma16816(c[u], va[1].z, va[3].z, va[1].w, va[3].w, vb[2 * u + 1].z, vb[2 * u + 1].w);
        }
        const unsigned ra = sb + OFF_S + 4 * 32768 + lane * 16;
#pragma unroll
        for (int hh = 0; hh < 2; hh++) {
            sts128(ra + q * 2048 + hh * 1024, make_uint4(__float_as_uint(c[0][2 * hh]), __float_as_uint(c[0][2 * hh + 1]), __float_as_uint(c[1][2 * hh]), __float_as_uint(c[1][2 * hh + 1])));
            sts128(ra + q * 2048 + hh * 1024 + 512, make_uint4(__float_as_uint(c[2][2 * hh]), __float_as_uint(c[2][2 * hh + 1]), __float_as_uint(c[3][2 * hh]), __float_as_uint(c[3][2 * hh + 1])));
        }
        STAMPT(64, 42);
        nb_sync<1, 128>();
        if (q < 2) {
            float m[8] = {0, 0, 0, 0, 0, 0, 0, 0};
#pragma unroll
            for (int i = 0; i < 4; i++) {
                uint4 u = lds128(ra + i * 2048 + q * 1024), v = lds128(ra + i * 2048 + q * 1024 + 512);
                m[0] += __uint_as_float(u.x); m[1] += __uint_as_float(u.y); m[2] += __uint_as_float(u.z); m[3] += __uint_as_float(u.w);
                m[4] += __uint_as_float(v.x); m[5] += __uint_as_float(v.y); m[6] += __uint_as_float(v.z); m[7] += __uint_as_float(v.w);
            }
            const float k = 0.0625f * 1.4426950408889634f;
            sc->mimg[(fw >> 2) * 2048 + (hq >> 1) * 512 + (16 * (fw & 3) + 8 * q + g) * 8 + (((hq & 1) * 4 + t) ^ g)] =
                make_uint4(pack2(m[0] * k, m[1] * k), pack2(m[2] * k, m[3] * k), pack2(m[4] * k, m[5] * k), pack2(m[6] * k, m[7] * k));
            STAMPT(64, 43);
            nb_arrive<2, 480>();
        }
    } else if (tid >= 32) {
        const uint4* ep = (const uint4*)esrc + (min(b, NT - 1u) * TILE + lane);
        cp16(sb + OFF_EIDX + lane * 16, ep); cp16(sb + OFF_EIDX + 512 + lane * 16, ep + 32);
        if (lane < 16) cp16(sb + OFF_EIDX + 1024 + lane * 16, ep + 64);
        if (lane < 10) cp16(sb + OFF_DIS + lane * 16, dis + (min(b, NT - 1u) * 10 + lane));
        cp_commit();
        cp_wait<0>();
        nb_arrive<2, 480>();
    } else {
        unsigned bad = 0;
        uint4 xd[3];
#pragma unroll
        for (int k = 0; k < 3; k++) xd[k] = ldg_na((const uint4*)edst + min(b * TILE + k * 32 + lane, NN - 1u));
#pragma unroll
        for (int k = 0; k < 3; k++) { const unsigned n = min(b * TILE + k * 32 + lane, NN - 1u); bad |= (xd[k].x ^ n) | (xd[k].y ^ n) | (xd[k].z ^ n) | (xd[k].w ^ n); }
        bad = __any_sync(~0u, bad);
        if (lane == 0) sts32(sb + OFF_MISC + 20, bad);
        __syncwarp();
        nb_arrive<2, 480>();
    }
    const int w = __shfl_sync(~0u, tid >> 5, 0), wg = w >> 2;
    const int grp0 = g0 + w;
    const uint4* lp = sc->lists + (grp0 * 32 + lane);
    uint4 L0, L1;
    nb_sync<3, 544>();

    if (__builtin_expect(rowcta, 1)) {
        const unsigned descA = 0x10000u + (sb + OFF_S) / 16 + wg * 512;
        const unsigned greg = sb + OFF_S + w * 2048 + lane * 16;
        const uint4* xl = x + lane;
        float d[40];
        unsigned pk[20];
        unsigned* hp = (unsigned*)(sc->hs + (2 * w * NN + b * TILE)) + lane;
        auto mma_q = [&](int Q, int slot, int st) {
            if (st < 0) wg_fence();
#pragma unroll
            for (int k = 0; k < 4; k++) {
                if (st >= 0) wg_fence();
                wg80(d, descA + slot * 2048 + k * 128, 0x10000u + (sb + OFF_T) / 16 + (Q & 3) * 640 + k * 2, ((Q & 3) | k) != 0);
                if (st >= 0) {
#pragma unroll
                    for (int j = st + 2 * k; j < st + 2 * k + 2; j++)
                        if (j < 20) asm volatile("st.global.u32 [%0],%1;" ::"l"(hp + (j >> 1) * 32 + (j & 1) * (NN * 4)), "r"(pk[j]) : "memory");
                }
            }
            wg_commit();
        };
        auto eidx = [&](int i) { return lds128(sb + OFF_EIDX + (w * 5 + i) * 16); };
        auto gather = [&](const uint4& ix, int slot) {
            cp16(greg + slot * 32768, xl + ix.x * 32u); cp16(greg + slot * 32768 + 512, xl + ix.y * 32u);
            cp16(greg + slot * 32768 + 1024, xl + ix.z * 32u); cp16(greg + slot * 32768 + 1536, xl + ix.w * 32u);
            cp_commit();
        };
        uint4 gv[5][4];
        auto to_regs = [&](int i, int slot) {
#pragma unroll
            for (int j = 0; j < 4; j++) gv[i][j] = lds128(greg + slot * 32768 + j * 512);
        };
        float ds[20];
#pragma unroll
        for (int j = 0; j < 10; j++) { const unsigned v = lds32(sb + OFF_DIS + (4 * j + t) * 4); ds[2 * j] = blo_v(v); ds[2 * j + 1] = bhi_v(v); }
        uint4 ix = eidx(0);
        const uint4 ix1 = eidx(1);
        STAMPT(288, 2);
        mbar_wait(bar_full);
        STAMPT(288, 3);
        mma_q(0, 0, -1);
        mbar_wait(bar_full + 8);
        STAMPT(288, 50);
        gather(ix, 4);
        mma_q(1, 1, -1);
        mbar_wait(bar_full + 16);
        STAMPT(288, 51);
        mma_q(2, 2, -1);
        wg_wait<1>();
        EV(5);
        mbar_wait(bar_full + 24);
        STAMP(5);
        mma_q(3, 3, -1);
        wg_wait<1>();
        nb_sync_id(8 + wg, 128);
        gather(ix1, 2);
        wg_wait<0>();
        EV(6);
        STAMP(6);
#pragma unroll
        for (int j = 0; j < 20; j++) pk[j] = movm(pack2(d[2 * j] * ds[2 * (j >> 1)], d[2 * j + 1] * ds[2 * (j >> 1) + 1]));
        cp_wait<1>();
        to_regs(0, 4);
        ix = eidx(2);
        const uint4 ix3 = eidx(3), ix4 = eidx(4);
        STAMP(7);
        mbar_wait(bar_full + 32); mbar_wait(bar_full + 40);
        asm volatile("" ::"r"(gv[0][0].x), "r"(gv[0][1].x), "r"(gv[0][2].x), "r"(gv[0][3].x));
        gather(ix, 4);
        STAMP(21);
        mma_q(4, 0, 0); mma_q(5, 1, 8);
        wg_wait<1>();
        EV(7);
        mbar_wait(bar_full + 48);
        mma_q(6, 3, 16);
        EV(12);
        wg_wait<1>();
        nb_sync_id(8 + wg, 128);
        gather(ix3, 1);
        mbar_wait(bar_full + 56);
        mma_q(7, 0, -1);
        wg_wait<1>();
        nb_sync_id(8 + wg, 128);
        gather(ix4, 3);
        wg_wait<0>();
        STAMP(20);
        EV(14);
        pack_acc(pk, d);
        nb_sync<0, 512>();
        acc_to_tile(pk, w, lane);
        cp_wait<2>();
        to_regs(1, 2);
        nb_sync<0, 512>();
        STAMP(8);
        {
            const unsigned delta = t ^ (g >> 1), alsm = sb + OFF_ALPHA + w * 128;
            const bool par = g & 1;
            const int n0 = w * 5;
            float v[4], u[4];
            to_regs(2, 4);
            EV(15);
            attn_scores(v, true, par, gv[0], tile_addr(n0, lane));
            attn_scores(v, delta == 1, par, gv[1], tile_addr(n0 + 1, lane ^ 8));
            attn_scores(v, delta == 2, par, gv[2], tile_addr(n0 + 2, lane ^ 16));
            cp_wait<1>();
            to_regs(3, 1);
            attn_scores(v, delta == 3, par, gv[3], tile_addr(n0 + 3, lane ^ 24));
            cp_wait<0>();
            to_regs(4, 3);
            attn_scores(u, true, par, gv[4], tile_addr(n0 + 4, lane));
            attn_softmax(v, u, lane, delta, alsm);
#pragma unroll
            for (int i = 0; i < 5; i++) attn_mix(gv[i], alsm + i * 16, tile_addr(n0 + i, lane));
        }
        mbar_wait(bar_full + 64);
        fence_async_smem();
        STAMP(22);
        EV(2);
        nb_sync<0, 512>();
        mma_q(8, 0, -1);
        mbar_wait(bar_full + 72);
        mma_q(9, 4, -1);
        wg_wait<1>();
        EV(4);
        mbar_wait(bar_full + 80);
        mma_q(10, 2, -1);
        wg_wait<1>();
        EV(5);
        mbar_wait(bar_full + 88);
        mma_q(11, 1, -1);
        wg_wait<1>();
        EV(6);
        wg_wait<0>();
        EV(7);
        STAMP(9);
        pack_acc(pk, d);
        mbar_wait(bar_c);
        L0 = ldg_na(lp); L1 = ldg_na(lp + LSTR);
        nb_sync<0, 512>();
        STAMP(10);
        if (__builtin_expect(lds32(sb + OFF_MISC + 28) & 2, 0)) {
            for (int i = 0; i < 5; i++) sts128(tile_addr(w * 5 + i, lane), attn_generic(b * TILE + w * 5 + i, x, esrc, edst, wq, wk, wv));
        } else {
            acc_to_tile(pk, w, lane);
        }
        fence_async_smem();
        EV(12);
    } else {
        mbar_wait(bar_c);
        L0 = ldg_na(lp); L1 = ldg_na(lp + LSTR);
    }

    const int cnt = (g1 - grp0 + 15) >> 4;
    const bool anyovf = lds32(sb + OFF_MISC + 28) & 1;
    if (lane < 8) sts128(sb + OFF_S + NN * 16 + lane * 16, make_uint4(0, 0, 0, 0));
    const unsigned lb = sb + OFF_S + (lane & 7) * 16;
    const unsigned dummy = anyovf ? 0 : lb + 1250 * 128;
    const float zmask = (lane >= 28) ? 0.f : -1.f;
    unsigned stg = sb + OFF_STG + w * 256 + (((lane & 7) * 2 + ((lane >> 3) & 1)) ^ ((lane >> 2) & 1)) * 16;
    __syncwarp();
    mbar_wait(bar_fill);
    STAMP(11);
    for (int it = 0; it < cnt; it++) {
        unsigned ad[12];
        ad[0] = dp2lo(L0.z, lb); ad[1] = dp2hi(L0.z, lb); ad[2] = dp2lo(L0.w, lb); ad[3] = dp2hi(L0.w, lb);
        ad[4] = dp2lo(L1.x, lb); ad[5] = dp2hi(L1.x, lb); ad[6] = dp2lo(L1.y, lb); ad[7] = dp2hi(L1.y, lb);
        ad[8] = dp2lo(L1.z, lb); ad[9] = dp2hi(L1.z, lb); ad[10] = dp2lo(L1.w, lb); ad[11] = dp2hi(L1.w, lb);
        unsigned sA = __byte_perm(L0.x, 0x64646464u, 0x4140), nB = __byte_perm(L0.x, 0xE4E4E4E4u, 0x4342);
        float dA = blo_v(L0.y), dB = bhi_v(L0.y);
        lp += 16 * 32;
        L0 = ldg_na(lp); L1 = ldg_na(lp + LSTR);
        float acc0[4] = {0, 0, 0, 0}, acc1[4] = {0, 0, 0, 0};
        if (!__any_sync(~0u, ad[10] != dummy)) {
            if (__any_sync(~0u, ad[9] != dummy)) p3_steps<10>(acc0, acc1, ad, sA, nB);
            else p3_steps<9>(acc0, acc1, ad, sA, nB);
        } else if (!__any_sync(~0u, ad[11] != dummy)) {
            p3_steps<11>(acc0, acc1, ad, sA, nB);
        } else {
            const bool longer = (sA & 0x80) || anyovf;
            sA &= ~0x80u;
            p3_steps<12>(acc0, acc1, ad, sA, nB);
            if (__any_sync(~0u, longer)) {
                uint4 C2 = ldg_na(lp - 16 * 32 + 2 * LSTR);
                unsigned e2[4] = {C2.x, C2.y, C2.z, C2.w};
#pragma unroll
                for (int s = 12; s < 20; s++) p3_step(acc0, acc1, (s & 1) ? dp2hi(e2[(s - 12) >> 1], lb) : dp2lo(e2[(s - 12) >> 1], lb), s, sA, nB);
                if (anyovf) {
                    float4 e = p3_overflow(sc, grp0 + 16 * it, sb + OFF_S);
                    float s0 = e.x + e.z, s1 = e.y + e.w;
                    for (int k = 4; k < 32; k <<= 1) {
                        float u0 = __shfl_down_sync(~0u, s0, k), u1 = __shfl_down_sync(~0u, s1, k);
                        if (lane + k < 32) { s0 += u0; s1 += u1; }
                    }
                    acc0[0] += s0; acc0[1] += s1; acc0[2] += s0 - e.x; acc0[3] += s1 - e.y;
                }
            }
        }
        float c0 = acc0[0] + acc1[0], c1 = acc0[1] + acc1[1], c2 = acc0[2] + acc1[2], c3 = acc0[3] + acc1[3];
        float n0 = __shfl_down_sync(~0u, c0, 4), n1 = __shfl_down_sync(~0u, c1, 4);
        float o0 = c0 - c2, o1 = c1 - c3, o2 = fmaf(n0, zmask, c2), o3 = fmaf(n1, zmask, c3);
        if (it == 6) mbar_wait(bar_t);
        asm volatile("stmatrix.sync.aligned.m8n8.x2.shared.b16 [%0],{%1,%2};" ::"r"(stg), "r"(pack2(o0 * dA, o1 * dA)), "r"(pack2(o2 * dB, o3 * dB)) : "memory");
        __syncwarp();
        asm volatile("{.reg .pred p; setp.eq.u32 p,%1,0; @p mbarrier.arrive.shared.b64 _,[%0];}" ::"r"(bar_rd + 8 * it), "r"(lane) : "memory");
        stg += 4096;
    }
    STAMP(12);
    }
}

typedef CUresult (*EncodeFn)(CUtensorMap*, CUtensorMapDataType, cuuint32_t, void*, const cuuint64_t*, const cuuint64_t*,
                             const cuuint32_t*, const cuuint32_t*, CUtensorMapInterleave, CUtensorMapSwizzle,
                             CUtensorMapL2promotion, CUtensorMapFloatOOBfill);

}

extern "C" void kernel_launch(void* const* d_in, const int* in_sizes, int n_in, void* d_out, int out_size) {
    (void)in_sizes; (void)n_in; (void)out_size;
    static EncodeFn enc = nullptr;
    static void* scratch = nullptr;
    if (!enc) {
        cudaGetSymbolAddress(&scratch, g_scratch);
        void* fn = nullptr;
        cudaDriverEntryPointQueryResult qr;
        cudaGetDriverEntryPoint("cuTensorMapEncodeTiled", &fn, cudaEnableDefault, &qr);
        enc = (EncodeFn)fn;
        cudaFuncSetAttribute(exphormer_kernel, cudaFuncAttributeMaxDynamicSharedMemorySize, SMEM_BYTES);
    }
    CUtensorMap tm_x, tm_wl, tm_wv, tm_ot, tm_o256, tm_o16;
    auto mk = [&](CUtensorMap* tm, void* p, int rows, int bc, int br, CUtensorMapSwizzle sw, CUtensorMapL2promotion pr) {
        cuuint64_t gd[2] = {256, (cuuint64_t)rows}, gs[1] = {512};
        cuuint32_t es[2] = {1, 1}, bx[2] = {(cuuint32_t)bc, (cuuint32_t)br};
        enc(tm, CU_TENSOR_MAP_DATA_TYPE_BFLOAT16, 2, p, gd, gs, bx, es, CU_TENSOR_MAP_INTERLEAVE_NONE, sw, pr, CU_TENSOR_MAP_FLOAT_OOB_FILL_NONE);
    };
    for (int i = 0; i < 2; i++) {
        cuuint64_t gd[3] = {64, 256, 4}, gs[2] = {512, 128};
        cuuint32_t es[3] = {1, 1, 1}, bx[3] = {64, 64, 4};
        enc(i ? &tm_wv : &tm_wl, CU_TENSOR_MAP_DATA_TYPE_BFLOAT16, 3, d_in[i ? 9 : 6], gd, gs, bx, es, CU_TENSOR_MAP_INTERLEAVE_NONE,
            CU_TENSOR_MAP_SWIZZLE_128B, CU_TENSOR_MAP_L2_PROMOTION_L2_128B, CU_TENSOR_MAP_FLOAT_OOB_FILL_NONE);
    }
    mk(&tm_x, d_in[0], NN, 64, TILE, CU_TENSOR_MAP_SWIZZLE_128B, CU_TENSOR_MAP_L2_PROMOTION_L2_128B);
    mk(&tm_ot, d_out, NN, 64, TILE, CU_TENSOR_MAP_SWIZZLE_128B, CU_TENSOR_MAP_L2_PROMOTION_NONE);
    mk(&tm_o256, d_out, NN, 8, 256, CU_TENSOR_MAP_SWIZZLE_NONE, CU_TENSOR_MAP_L2_PROMOTION_NONE);
    mk(&tm_o16, d_out, NN, 8, 16, CU_TENSOR_MAP_SWIZZLE_NONE, CU_TENSOR_MAP_L2_PROMOTION_NONE);
    exphormer_kernel<<<NCTA, 640, SMEM_BYTES>>>(
        (const uint4*)d_in[0], (const uint4*)d_in[2], (const uint4*)d_in[1], (const uint4*)d_in[7], (const uint4*)d_in[8], (const int*)d_in[3],
        (const int*)d_in[4], (Scratch*)scratch, (const uint4*)d_in[5], (const uint4*)d_in[9],
        tm_x, tm_wl, tm_wv, tm_ot, tm_o256, tm_o16);
}
```

```cpp
#include <cuda_runtime.h>
#include <cuda_bf16.h>
#include <cuda.h>
#include <stdint.h>

namespace {

constexpr int NN = 10000, NE = 160000, NEE = 40000;
constexpr int TILE = 80, NT = 125, NCTA = 128, NG = 625, EPC = 1280;
constexpr int CELL = 32;
constexpr int LCAP = 80;
constexpr int OVCAP = EPC + NT * CELL;
#define XD0 700
#define XD1 1100
#define XD2 1900
#define REG_W 104
#define REG_H 64
#define KH 2
#define POLLNS 0
#define STPRE 4
#define G0POS 1
#define G1POS 0
#define GATE2 0
constexpr unsigned DUMMY2 = 1250u | (1250u << 16);

constexpr unsigned sb = 1024;
constexpr int OFF_S = 0;
constexpr int OFF_R = 163840;
constexpr int OFF_BAR = OFF_R;
constexpr int OFF_MISC = OFF_R + 256;
constexpr int OFF_DIS = OFF_R + 320;
constexpr int OFF_PROF = OFF_R + 512;
constexpr int OFF_EIDX = OFF_R + 1024;
constexpr int OFF_ALPHA = OFF_R + 1024;
constexpr int OFF_STG = OFF_R + 2048;
constexpr int OFF_CNT1 = OFF_R + 2560;
constexpr int OFF_CNT2 = OFF_R + 3072;
constexpr int OFF_MAIL = OFF_R + 5760;
constexpr int OFF_IMG = OFF_MAIL + 9216;
constexpr int OFF_T = OFF_R + 26624;
constexpr int SMEM_BYTES = OFF_T + 40960;
static_assert(SMEM_BYTES <= 232448 && OFF_T % 1024 == 0 && OFF_STG + 6 * 4096 == OFF_T && OFF_IMG + 10752 <= OFF_T, "smem");
constexpr unsigned bar_fill = sb + OFF_BAR, bar_t = bar_fill + 8, bar_mail = bar_fill + 16, bar_c = bar_fill + 24, bar_rd = bar_fill + 32,
                   bar_go = bar_fill + 112, bar_full = bar_fill + 120;
constexpr int LSTR = (NG + 16) * 32;

struct __align__(256) Scratch {
    uint4 mimg[8192];
    uint4 hs[32 * NN];
    uint4 mail[2 * NT * 512];
    uint4 lists[3 * LSTR];
    uint2 ovfn[NCTA];
    unsigned bar[5 * 64];
    unsigned ovf[NCTA * OVCAP];
};
__device__ Scratch g_scratch;
#define STAMPT(th, i)
#define STAMP(i) STAMPT(64, i)
#define STAMP2(i) STAMPT(416, i)

__device__ __forceinline__ void bar_arrive(unsigned* p) {
    asm volatile("red.release.gpu.global.add.u32 [%0],1;" ::"l"(p) : "memory");
}
__device__ __forceinline__ void bar_arrive_relaxed(unsigned* p) {
    asm volatile("red.relaxed.gpu.global.add.u32 [%0],1;" ::"l"(p) : "memory");
}
__device__ __forceinline__ void bar_poll(const Scratch* sc, int i) {
    unsigned v, target;
    int lim = 0;
    asm volatile("ld.shared.u32 %0,[%1];" : "=r"(target) : "r"(sb + OFF_MISC + 32 + 4 * i) : "memory");
    while (true) {
        asm volatile("ld.acquire.gpu.global.u32 %0,[%1];" : "=r"(v) : "l"(&sc->bar[i * 64]) : "memory");
        if ((int)(v - target) >= 0) break;
        if (++lim > (1 << 22)) __trap();
        if (POLLNS) __nanosleep(POLLNS);
    }
}
__device__ __forceinline__ unsigned bar_poll2(const unsigned* p, unsigned target) {
    unsigned long long v;
    int lim = 0;
    do {
        asm volatile("ld.acquire.gpu.global.u64 %0,[%1];" : "=l"(v) : "l"(p) : "memory");
        if (++lim > (1 << 22)) __trap();
    } while ((int)((unsigned)v - target) < 0);
    unsigned f = (unsigned)(v >> 32);
    return (f & ~3u) == target ? f & 3 : 0;
}
__device__ __noinline__ void raise_flag(unsigned* p, unsigned target, unsigned bit) {
    unsigned old = atomicCAS(p, 0, 0), seen;
    do {
        seen = old;
        old = atomicCAS(p, seen, ((seen & ~3u) == target ? seen : target) | bit);
    } while (old != seen);
}
__device__ __forceinline__ void mbar_wait(unsigned a) {
    asm volatile("{.reg .pred p; .reg .u32 n;\n"
                 "mov.u32 n,0x400000;\n"
                 "W: mbarrier.try_wait.parity.shared.b64 p,[%0],0;\n"
                 "add.u32 n,n,-1; setp.ne.and.u32 p,n,0,!p; @p bra W;}" ::"r"(a) : "memory");
}
__device__ __forceinline__ bool elect() {
    unsigned r;
    asm volatile("{.reg .pred p; elect.sync _|p,0xFFFFFFFF; selp.u32 %0,1,0,p;}" : "=r"(r));
    return r;
}
__device__ __forceinline__ uint4 ldg_na(const uint4* p) {
    uint4 v;
    asm volatile("ld.global.L1::no_allocate.v4.u32 {%0,%1,%2,%3},[%4];" : "=r"(v.x), "=r"(v.y), "=r"(v.z), "=r"(v.w) : "l"(p) : "memory");
    return v;
}
__device__ __forceinline__ uint4 lds128(unsigned a) {
    uint4 v;
    asm volatile("ld.shared.v4.u32 {%0,%1,%2,%3},[%4];" : "=r"(v.x), "=r"(v.y), "=r"(v.z), "=r"(v.w) : "r"(a) : "memory");
    return v;
}
__device__ __forceinline__ uint4 ldsm4(unsigned a) {
    uint4 v;
    asm volatile("ldmatrix.sync.aligned.m8n8.x4.shared.b16 {%0,%1,%2,%3},[%4];" : "=r"(v.x), "=r"(v.y), "=r"(v.z), "=r"(v.w) : "r"(a) : "memory");
    return v;
}
__device__ __forceinline__ void sts128(unsigned a, uint4 v) {
    asm volatile("st.shared.v4.u32 [%0],{%1,%2,%3,%4};" ::"r"(a), "r"(v.x), "r"(v.y), "r"(v.z), "r"(v.w) : "memory");
}
__device__ __forceinline__ void sts32(unsigned a, unsigned v) { asm volatile("st.shared.u32 [%0],%1;" ::"r"(a), "r"(v) : "memory"); }
__device__ __forceinline__ unsigned lds32(unsigned a) { unsigned v; asm volatile("ld.shared.u32 %0,[%1];" : "=r"(v) : "r"(a) : "memory"); return v; }
__device__ __forceinline__ unsigned atoms_add(unsigned a, unsigned k) { unsigned v; asm volatile("atom.shared.add.u32 %0,[%1],%2;" : "=r"(v) : "r"(a), "r"(k) : "memory"); return v; }
__device__ __forceinline__ unsigned bitsel(unsigned a, unsigned b, unsigned m) { unsigned r; asm("lop3.b32 %0,%1,%2,%3,0xE4;" : "=r"(r) : "r"(a), "r"(b), "r"(m)); return r; }
__device__ __forceinline__ unsigned atoms_inc(unsigned a) { unsigned v; asm volatile("atom.shared.add.u32 %0,[%1],1;" : "=r"(v) : "r"(a) : "memory"); return v; }
__device__ __forceinline__ float blo(unsigned v) { return __uint_as_float(v << 16); }
__device__ __forceinline__ float bhi(unsigned v) { return __uint_as_float(v & 0xFFFF0000u); }
__device__ __forceinline__ float blo_v(unsigned v) { float r; asm volatile("shl.b32 %0,%1,16;" : "=f"(r) : "r"(v)); return r; }
__device__ __forceinline__ float bhi_v(unsigned v) { float r; asm volatile("and.b32 %0,%1,0xFFFF0000;" : "=f"(r) : "r"(v)); return r; }
__device__ __forceinline__ unsigned pack2(float lo, float hi) { unsigned r; asm("cvt.rn.bf16x2.f32 %0,%1,%2;" : "=r"(r) : "f"(hi), "f"(lo)); return r; }

__device__ __forceinline__ void mma16816(float* d, unsigned a0, unsigned a1, unsigned a2, unsigned a3, unsigned b0, unsigned b1) {
    asm volatile("mma.sync.aligned.m16n8k16.row.col.f32.bf16.bf16.f32 {%0,%1,%2,%3},{%4,%5,%6,%7},{%8,%9},{%0,%1,%2,%3};"
                 : "+f"(d[0]), "+f"(d[1]), "+f"(d[2]), "+f"(d[3]) : "r"(a0), "r"(a1), "r"(a2), "r"(a3), "r"(b0), "r"(b1));
}
#define R10(b) "+f"(d[b + 0]), "+f"(d[b + 1]), "+f"(d[b + 2]), "+f"(d[b + 3]), "+f"(d[b + 4]), "+f"(d[b + 5]), "+f"(d[b + 6]), "+f"(d[b + 7]), "+f"(d[b + 8]), "+f"(d[b + 9])
__device__ __forceinline__ void wg80(float* d, unsigned da, unsigned db, int sc) {
    asm volatile("{.reg .pred p; .reg .b64 a, b; setp.ne.b32 p,%42,0; mov.b64 a,{%40,%43}; mov.b64 b,{%41,%43};\n"
                 "wgmma.mma_async.sync.aligned.m64n80k16.f32.bf16.bf16 "
                 "{%0,%1,%2,%3,%4,%5,%6,%7,%8,%9,%10,%11,%12,%13,%14,%15,%16,%17,%18,%19,%20,%21,%22,%23,%24,%25,%26,%27,%28,%29,%30,%31,%32,%33,%34,%35,%36,%37,%38,%39},"
                 "a,b,p,1,1,1,0;}"
                 : R10(0), R10(10), R10(20), R10(30) : "r"(da), "r"(db), "r"(sc), "r"(0x40000040));
}
__device__ __forceinline__ void wg_fence() { asm volatile("wgmma.fence.sync.aligned;" ::: "memory"); }
__device__ __forceinline__ void wg_commit() { asm volatile("wgmma.commit_group.sync.aligned;" ::: "memory"); }
template <int N> __device__ __forceinline__ void wg_wait() { asm volatile("wgmma.wait_group.sync.aligned %0;" ::"n"(N) : "memory"); }
__device__ __forceinline__ void bulk_g2s(unsigned dst, const void* src, unsigned bytes, unsigned bar) {
    asm volatile("cp.async.bulk.shared::cluster.global.mbarrier::complete_tx::bytes [%0],[%1],%2,[%3];" ::"r"(dst), "l"(src), "r"(bytes), "r"(bar) : "memory");
}
__device__ __forceinline__ void fence_async_smem() { asm volatile("fence.proxy.async.shared::cta;" ::: "memory"); }
__device__ __forceinline__ void fence_async_gmem() { asm volatile("fence.proxy.async.global;" ::: "memory"); }

__device__ __forceinline__ unsigned hsat(unsigned a, unsigned c) { unsigned r; asm("add.sat.f16x2 %0,%1,%2;" : "=r"(r) : "r"(a), "r"(c)); return r; }
__device__ __forceinline__ unsigned hset(unsigned a, unsigned c) { unsigned r; asm("set.le.f16x2.f16x2 %0,%1,%2;" : "=r"(r) : "r"(a), "r"(c)); return r; }
__host__ __device__ constexpr unsigned h2c(int v) { return (0x6400u | v) | ((0x6400u | v) << 16); }
__device__ __forceinline__ unsigned dp2lo(unsigned a, unsigned c) { unsigned r; asm("dp2a.lo.u32.u32 %0,%1,%2,%3;" : "=r"(r) : "r"(a), "r"(0x80000080u), "r"(c)); return r; }
__device__ __forceinline__ unsigned dp2hi(unsigned a, unsigned c) { unsigned r; asm("dp2a.hi.u32.u32 %0,%1,%2,%3;" : "=r"(r) : "r"(a), "r"(0x80000080u), "r"(c)); return r; }
__device__ __forceinline__ void p3_step(float* acc0, float* acc1, unsigned addr, int s, unsigned sA, unsigned nB) {
    unsigned b0, b1, b2, b3;
    asm volatile("ldmatrix.sync.aligned.m8n8.x4.trans.shared.b16 {%0,%1,%2,%3},[%4];" : "=r"(b0), "=r"(b1), "=r"(b2), "=r"(b3) : "r"(addr));
    mma16816(acc0, hset(sA, h2c(4 * s + 0)), hsat(nB, h2c(4 * s + 1)), hset(sA, h2c(4 * s + 1)), hsat(nB, h2c(4 * s + 2)), b0, b1);
    mma16816(acc1, hset(sA, h2c(4 * s + 2)), hsat(nB, h2c(4 * s + 3)), hset(sA, h2c(4 * s + 3)), hsat(nB, h2c(4 * s + 4)), b2, b3);
}
template <int NS> __device__ __forceinline__ void p3_steps(float* acc0, float* acc1, const unsigned* ad, unsigned sA, unsigned nB) {
#pragma unroll
    for (int s = 0; s < NS; s++) p3_step(acc0, acc1, ad[s], s, sA, nB);
}
__device__ __noinline__ float4 p3_overflow(const Scratch* sc, int grp, unsigned sS) {
    const unsigned tag = lds32(sb + OFF_MISC + 48);
    int lane = threadIdx.x & 31, g = lane >> 2, t = lane & 3;
    float4 r = make_float4(0.f, 0.f, 0.f, 0.f);
    for (int c = 0; c < NT; c++) {
        const uint2 tn = __ldcg(&sc->ovfn[c]);
        const int n = tn.x == tag ? (int)tn.y : 0;
        for (int i0 = 0; i0 < n; i0 += 32) {
            unsigned e = (i0 + lane < n) ? __ldcg(&sc->ovf[c * OVCAP + i0 + lane]) : 0xFFFFFFFFu;
            unsigned m = __ballot_sync(~0u, (int)(e >> 18) == grp);
            while (m) {
                int j = __ffs(m) - 1;
                m &= m - 1;
                unsigned ee = __shfl_sync(~0u, e, j);
                int row = (ee >> 14) & 15;
                row ^= row >> 3;
                unsigned v = lds32(sS + (ee & 0x3FFF) * 16 + t * 4);
                if ((row >> 1) == g) {
                    if (!(row & 1)) { r.x += blo(v); r.y += bhi(v); } else { r.z += blo(v); r.w += bhi(v); }
                }
            }
        }
    }
    const float k = 1.f / 128.f;
    r.x *= k; r.y *= k; r.z *= k; r.w *= k;
    return r;
}
__device__ __forceinline__ void unpack8(float* f, uint4 v) {
    f[0] = blo(v.x); f[1] = bhi(v.x); f[2] = blo(v.y); f[3] = bhi(v.y); f[4] = blo(v.z); f[5] = bhi(v.z); f[6] = blo(v.w); f[7] = bhi(v.w);
}
__device__ __forceinline__ void vec_mat(float* o, const float* v, const uint4* __restrict__ W, int lane) {
    for (int k = 0; k < 8; k++) o[k] = 0.f;
    for (int l = 0; l < 32; l++) {
#pragma unroll
        for (int i = 0; i < 8; i++) {
            float a = __shfl_sync(~0u, v[i], l), wr[8];
            unpack8(wr, W[(l * 8 + i) * 32 + lane]);
#pragma unroll
            for (int k = 0; k < 8; k++) o[k] = fmaf(a, wr[k], o[k]);
        }
    }
}
__device__ __noinline__ uint4 attn_generic(int node, const uint4* __restrict__ x, const int* __restrict__ esrc, const int* __restrict__ edst,
                                           const uint4* __restrict__ wq, const uint4* __restrict__ wk, const uint4* __restrict__ wv) {
    int lane = threadIdx.x & 31;
    float xr[8], q[8], y[8], o[8];
    unpack8(xr, x[node * 32 + lane]);
    vec_mat(q, xr, wq, lane);
    for (int l = 0; l < 32; l++) {
#pragma unroll
        for (int i = 0; i < 8; i++) {
            float wr[8], p = 0.f;
            unpack8(wr, wk[(l * 8 + i) * 32 + lane]);
#pragma unroll
            for (int k = 0; k < 8; k++) p = fmaf(q[k], wr[k], p);
            for (int k = 16; k; k >>= 1) p += __shfl_xor_sync(~0u, p, k);
            if (lane == l) y[i] = p;
        }
    }
    for (int k = 0; k < 8; k++) o[k] = 0.f;
    float den = 0.f;
    for (int i0 = 0; i0 < NEE; i0 += 32) {
        unsigned m = __ballot_sync(~0u, edst[i0 + lane] == node);
        while (m) {
            int j = __ffs(m) - 1;
            m &= m - 1;
            float gq[8], p = 0.f;
            unpack8(gq, x[esrc[i0 + j] * 32 + lane]);
#pragma unroll
            for (int k = 0; k < 8; k++) p = fmaf(y[k], gq[k], p);
            for (int k = 16; k; k >>= 1) p += __shfl_xor_sync(~0u, p, k);
            float ex = __expf(p * 0.0625f);
            den += ex;
#pragma unroll
            for (int k = 0; k < 8; k++) o[k] = fmaf(ex, gq[k], o[k]);
        }
    }
    float inv = 1.f / (den + 1e-9f);
    for (int k = 0; k < 8; k++) o[k] *= inv;
    vec_mat(q, o, wv, lane);
    return make_uint4(pack2(q[0], q[1]), pack2(q[2], q[3]), pack2(q[4], q[5]), pack2(q[6], q[7]));
}

__device__ __forceinline__ unsigned hfma2(unsigned a, unsigned b, unsigned c) { unsigned r; asm("fma.rn.bf16x2 %0,%1,%2,%3;" : "=r"(r) : "r"(a), "r"(b), "r"(c)); return r; }
__device__ __forceinline__ unsigned hmul2(unsigned a, unsigned b) { unsigned r; asm("mul.rn.bf16x2 %0,%1,%2;" : "=r"(r) : "r"(a), "r"(b)); return r; }

__device__ __forceinline__ unsigned tile_addr(int n, unsigned chunk) { return sb + OFF_T + (chunk >> 3) * 10240 + n * 128 + (((chunk ^ n) & 7) << 4); }
__device__ __forceinline__ void attn_scores(float* v, bool mine, bool par, const uint4* gv, unsigned yaddr) {
    const uint4 y = ldsm4(yaddr);
    float c[4] = {0, 0, 0, 0}, e[4] = {0, 0, 0, 0};
    mma16816(c, gv[0].x, gv[0].y, gv[0].z, gv[0].w, y.x, y.y);
    mma16816(e, gv[2].x, gv[2].y, gv[2].z, gv[2].w, y.x, y.y);
    mma16816(c, gv[1].x, gv[1].y, gv[1].z, gv[1].w, y.z, y.w);
    mma16816(e, gv[3].x, gv[3].y, gv[3].z, gv[3].w, y.z, y.w);
    if (mine) { v[0] = par ? c[1] : c[0]; v[1] = par ? c[3] : c[2]; v[2] = par ? e[1] : e[0]; v[3] = par ? e[3] : e[2]; }
}
__device__ __forceinline__ void attn_softmax(const float* v, const float* u, unsigned lane, unsigned aladdr) {
    const bool hA = lane & 4, hB = lane & 8, hC = lane & 16;
    float a[4];
#pragma unroll
    for (int e = 0; e < 4; e++) a[e] = (hA ? u[e] : v[e]) + __shfl_xor_sync(~0u, hA ? v[e] : u[e], 4);
    float b0 = (hB ? a[1] : a[0]) + __shfl_xor_sync(~0u, hB ? a[0] : a[1], 9);
    float b1 = (hB ? a[3] : a[2]) + __shfl_xor_sync(~0u, hB ? a[2] : a[3], 9);
    float sc = (hC ? b1 : b0) + __shfl_xor_sync(~0u, hC ? b0 : b1, 18);
    float ex, inv;
    asm("ex2.approx.ftz.f32 %0,%1;" : "=f"(ex) : "f"(sc));
    float den = ex + __shfl_xor_sync(~0u, ex, 9);
    den += __shfl_xor_sync(~0u, den, 18);
    asm("rcp.approx.ftz.f32 %0,%1;" : "=f"(inv) : "f"(den + 1e-9f));
    sts32(aladdr, pack2(ex * inv, ex * inv));
    __syncwarp();
}
__device__ __forceinline__ void attn_mix(const uint4* gv, const uint4& a, unsigned oaddr) {
    const unsigned o0 = hfma2(a.w, gv[2].y, hfma2(a.z, gv[2].x, hfma2(a.y, gv[0].y, hmul2(a.x, gv[0].x))));
    const unsigned o1 = hfma2(a.w, gv[2].w, hfma2(a.z, gv[2].z, hfma2(a.y, gv[0].w, hmul2(a.x, gv[0].z))));
    const unsigned o2 = hfma2(a.w, gv[3].y, hfma2(a.z, gv[3].x, hfma2(a.y, gv[1].y, hmul2(a.x, gv[1].x))));
    const unsigned o3 = hfma2(a.w, gv[3].w, hfma2(a.z, gv[3].z, hfma2(a.y, gv[1].w, hmul2(a.x, gv[1].z))));
    asm volatile("stmatrix.sync.aligned.m8n8.x4.shared.b16 [%0],{%1,%2,%3,%4};" ::"r"(oaddr), "r"(o0), "r"(o1), "r"(o2), "r"(o3) : "memory");
}
__device__ __forceinline__ void pack_acc(unsigned* pk, const float* d) {
#pragma unroll
    for (int j = 0; j < 20; j++) pk[j] = pack2(d[2 * j], d[2 * j + 1]);
}
__device__ __forceinline__ void acc_to_tile(const unsigned* pk, int w, int lane) {
    const unsigned a = sb + OFF_T + (w >> 2) * 10240 + (lane >> 4) * 1024 + (lane & 7) * 128 + (((2 * (w & 3) + ((lane >> 3) & 1)) ^ (lane & 7)) << 4);
#pragma unroll
    for (int j = 0; j < 5; j++)
        asm volatile("stmatrix.sync.aligned.m8n8.x4.trans.shared.b16 [%0],{%1,%2,%3,%4};" ::"r"(a + j * 2048), "r"(pk[4 * j]), "r"(pk[4 * j + 1]), "r"(pk[4 * j + 2]), "r"(pk[4 * j + 3]) : "memory");
}
__device__ __forceinline__ unsigned movm(unsigned a) { unsigned d; asm volatile("movmatrix.sync.aligned.m8n8.trans.b16 %0,%1;" : "=r"(d) : "r"(a)); return d; }
__device__ __forceinline__ void tma_load2d(unsigned dst, const CUtensorMap* tm, int c0, int c1, unsigned bar) {
    asm volatile("cp.async.bulk.tensor.2d.shared::cluster.global.mbarrier::complete_tx::bytes [%0],[%1,{%3,%4}],[%2];"
                 ::"r"(dst), "l"(tm), "r"(bar), "r"(c0), "r"(c1) : "memory");
}
__device__ __forceinline__ void tma_load3d(unsigned dst, const CUtensorMap* tm, int row, unsigned bar) {
    asm volatile("cp.async.bulk.tensor.3d.shared::cluster.global.mbarrier::complete_tx::bytes [%0],[%1,{%4,%3,%4}],[%2];"
                 ::"r"(dst), "l"(tm), "r"(bar), "r"(row), "r"(0) : "memory");
}
__device__ __forceinline__ void cp16(unsigned dst, const void* src) { asm volatile("cp.async.cg.shared.global [%0],[%1],16;" ::"r"(dst), "l"(src) : "memory"); }
__device__ __forceinline__ void cp_commit() { asm volatile("cp.async.commit_group;" ::: "memory"); }
template <int N> __device__ __forceinline__ void cp_wait() { asm volatile("cp.async.wait_group %0;" ::"n"(N) : "memory"); }
__device__ __forceinline__ void nb_sync_id(int id, int n) { asm volatile("bar.sync %0,%1;" ::"r"(id), "r"(n) : "memory"); }
__device__ __forceinline__ void nb_arrive_id(int id, int n) { asm volatile("bar.arrive %0,%1;" ::"r"(id), "r"(n) : "memory"); }
template <int ID, int N> __device__ __forceinline__ void nb_sync() { asm volatile("bar.sync %0,%1;" ::"n"(ID), "n"(N) : "memory"); }
template <int ID, int N> __device__ __forceinline__ void nb_arrive() { asm volatile("bar.arrive %0,%1;" ::"n"(ID), "n"(N) : "memory"); }
__device__ __forceinline__ void mbar_init(unsigned a, int n) { asm volatile("mbarrier.init.shared.b64 [%0],%1;" ::"r"(a), "r"(n) : "memory"); }
__device__ __forceinline__ void mbar_expect(unsigned a, int n) { asm volatile("mbarrier.arrive.expect_tx.shared.b64 _,[%0],%1;" ::"r"(a), "r"(n) : "memory"); }
__device__ __forceinline__ void mbar_arrive(unsigned a) { asm volatile("mbarrier.arrive.shared.b64 _,[%0];" ::"r"(a) : "memory"); }

constexpr unsigned PADBIN = 2560, CU = 0x101;
__device__ __noinline__ void push_overflow(Scratch* sc, unsigned dst, unsigned src) {
    sc->ovf[blockIdx.x * OVCAP + atoms_inc(sb + OFF_MISC)] = (dst << 14) | src;
}
__device__ __noinline__ void bin_overflow(Scratch* sc, unsigned mask, unsigned ht) {
    for (int i = 0; i < 24 + 6 * 16; i++) {
        unsigned e;
        if (i < 24) {
            if (!(mask >> i & 1)) continue;
            e = lds32(sb + OFF_MAIL + (ht + (i >> 2) * 96) * 16 + (i & 3) * 4) & 0x7FFFFFFFu;
        } else {
            const int k = (i - 24) >> 4;
            if (!(mask >> (24 + k) & 1)) continue;
            e = __ldcg((const unsigned*)(sc->mail + ((NT + blockIdx.x) * 512 + ((ht + k * 96) & ~3u))) + ((i - 24) & 15));
        }
        if (e < (PADBIN << 16))
            push_overflow(sc, blockIdx.x * TILE + ((e >> 21) & ~3u) + ((e >> 18) & 3), ((e & 2047) << 3) | ((e >> 20) & 7));
    }
}
__device__ __forceinline__ void place(unsigned e, unsigned h) {
    asm volatile("{.reg .pred p; setp.lt.u32 p,%2,%3; @p st.shared.u16 [%0],%1;}"
                 ::"r"(sb + OFF_IMG + bitsel(h >> 1, e >> 16, 0x318E)), "h"((unsigned short)e), "r"(h), "n"((LCAP + 16) * CU) : "memory");
}
__device__ __forceinline__ void bulk_s2g(void* dst, unsigned src, unsigned bytes) {
    asm volatile("cp.async.bulk.global.shared::cta.bulk_group [%0],[%1],%2;" ::"l"(dst), "r"(src), "r"(bytes) : "memory");
}
__device__ __forceinline__ void tma_reduce(const CUtensorMap* tm, unsigned src, int c0, int c1) {
    asm volatile("cp.reduce.async.bulk.tensor.2d.global.shared::cta.add.tile.bulk_group [%0,{%2,%3}],[%1];" ::"l"(tm), "r"(src), "r"(c0), "r"(c1) : "memory");
}
#define EV(id) nb_arrive<id, 544>()
#define WAIT_EV(id) do { __syncwarp(); nb_sync<id, 544>(); } while (0)

__global__ void __launch_bounds__(640, 1)
exphormer_kernel(const uint4* __restrict__ x, const uint4* __restrict__ dst4, const uint4* __restrict__ src4,
                 const uint4* __restrict__ wq, const uint4* __restrict__ wk, const int* __restrict__ esrc,
                 const int* __restrict__ edst, Scratch* __restrict__ sc, const uint4* __restrict__ dis, const uint4* __restrict__ wv,
                 const __grid_constant__ CUtensorMap tm_x, const __grid_constant__ CUtensorMap tm_wl, const __grid_constant__ CUtensorMap tm_wv,
                 const __grid_constant__ CUtensorMap tm_mail, const __grid_constant__ CUtensorMap tm_ot, const __grid_constant__ CUtensorMap tm_o256, const __grid_constant__ CUtensorMap tm_o16) {
    extern __shared__ __align__(1024) unsigned char smem_raw[];
    const unsigned tid = threadIdx.x, lane = tid & 31, g = lane >> 2, t = lane & 3;
    const unsigned b = blockIdx.x;
    const bool rowcta = b < NT;
    const int slice = b >> 2, range = b & 3;
    const int g0 = (range * NG) >> 2, g1 = ((range + 1) * NG) >> 2;
    STAMP(0);

    if (tid >= 512) {
    asm volatile("setmaxnreg.dec.sync.aligned.u32 %0;" ::"n"(REG_H));
    if (tid >= 544) {
        const unsigned ht = tid - 544;
        if (ht < 32) {
            nb_sync<13, 160>();
            nb_sync<2, 352>();
            if (rowcta) {
                const uint4 c = lds128(sb + OFF_CNT1 + lane * 16);
                const unsigned cc[4] = {c.x, c.y, c.z, c.w};
#pragma unroll
                for (int i = 0; i < 4; i++)
                    if (cc[i] > 16) asm volatile("red.shared.or.b32 [%0],0x80000000;" ::"r"(sb + OFF_MAIL + (lane * 4 + i) * 64 + 60) : "memory");
                fence_async_smem();
                __syncwarp();
                if (elect())
                    asm volatile("cp.async.bulk.tensor.2d.global.shared::cta.bulk_group [%0,{%2,%3}],[%1];" ::"l"(&tm_mail), "r"(sb + OFF_MAIL), "r"(b * 16), "r"(0) : "memory");
                for (int i = 0; i < 4; i++)
                    if (lds32(sb + OFF_CNT1 + lane * 16 + i * 4) > 16) bulk_s2g(sc->mail + ((NT + lane * 4 + i) * 512 + b * 4), sb + OFF_IMG + (lane * 4 + i) * 64, 64);
                asm volatile("cp.async.bulk.commit_group;" ::: "memory");
                asm volatile("cp.async.bulk.wait_group 0;" ::: "memory");
                fence_async_gmem();
                __syncwarp();
            }
            if (rowcta) nb_arrive<1, 96>();
            if (elect()) {
                bar_arrive_relaxed(&sc->bar[0]);
                STAMPT(544, 47);
                if (rowcta) {
                    bar_poll(sc, 0);
                    fence_async_gmem();
                    mbar_expect(bar_mail, 8000);
                    bulk_g2s(sb + OFF_MAIL, sc->mail + b * 512, 8000, bar_mail);
                    if (GATE2) mbar_arrive(bar_go);
                }
            }
            __syncwarp();
        } else if (ht < 64) {
            const unsigned fw = b >> 3, hq = b & 7;
            uint4* mo = sc->mimg + ((fw >> 2) * 2048 + (hq >> 1) * 512 + (16 * (fw & 3) + (lane & 15)) * 8 + ((hq * 4 ^ lane) & 4));
            nb_sync<14, 192>();
            if (lane < 16) bulk_s2g(mo, sb + OFF_MAIL + 8000 + lane * 64, 64);
            asm volatile("cp.async.bulk.commit_group;" ::: "memory");
            asm volatile("cp.async.bulk.wait_group 0;" ::: "memory");
            fence_async_gmem();
            __syncwarp();
            if (lane == 0) bar_arrive_relaxed(&sc->bar[3 * 64]);
            __syncwarp();
            STAMPT(576, 46);
        } else {
            if (lane < 5) {
                unsigned epoch;
                asm volatile("ld.relaxed.gpu.global.u32 %0,[%1];" : "=r"(epoch) : "l"(&sc->bar[lane * 64]) : "memory");
                sts32(sb + OFF_MISC + 32 + lane * 4, (epoch & ~(NCTA - 1)) + NCTA);
            }
            __syncwarp();
            nb_arrive<14, 192>();
            nb_arrive<15, 64>();
            nb_arrive<13, 160>();
        }
        if (rowcta) {
            if (ht >= 32) {
                nb_sync<1, 96>();
                const unsigned pad = (PADBIN + 4 * lane) << 16, h2 = ht - 32;
                sts128(sb + OFF_MAIL + 8000 + h2 * 16, make_uint4(pad, pad, pad, pad));
                if (h2 < 12) sts128(sb + OFF_MAIL + 9024 + h2 * 16, make_uint4(pad, pad, pad, pad));
#pragma unroll
                for (int k = 0; k < 9; k++) if (k % 3 < 2 || h2 < 32) sts128(sb + OFF_IMG + (k / 3) * 4096 + (k % 3) * 1024 + h2 * 16, make_uint4(DUMMY2, DUMMY2, DUMMY2, DUMMY2));
            }
            nb_sync<13, 96>();
            mbar_wait(bar_mail);
            STAMPT(576, 16);
            uint4 e[6], h[6];
            unsigned flagged = 0, late = 0;
#pragma unroll
            for (int k = 0; k < 6; k++) e[k] = lds128(sb + OFF_MAIL + (ht + k * 96) * 16);
#pragma unroll
            for (int k = 0; k < 6; k++) { flagged |= (e[k].w >> 31) << k; e[k].w &= 0x7FFFFFFFu; }
            while (flagged) {
                const unsigned f = __ffs(flagged) - 1, k = atoms_add(sb + OFF_MISC + 4, 4);
                const uint4* sp = sc->mail + ((NT + b) * 512 + ((ht + f * 96) & ~3u));
                flagged &= flagged - 1;
                if (k < 76) {
#pragma unroll
                    for (int j = 0; j < 4; j++) cp16(sb + OFF_MAIL + 8000 + (k + j) * 16, sp + j);
                } else {
                    late |= 1u << (24 + f);
                }
            }
            cp_commit();
            __syncwarp();
#pragma unroll
            for (int k = 0; k < 6; k++) {
                if (k == 5) { cp_wait<0>(); nb_sync<1, 96>(); if (ht >= 20) e[5] = lds128(sb + OFF_MAIL + (ht + 480) * 16); }
                h[k] = make_uint4(atoms_add(sb + OFF_CNT2 + (e[k].x >> 16), CU), atoms_add(sb + OFF_CNT2 + (e[k].y >> 16), CU),
                                  atoms_add(sb + OFF_CNT2 + (e[k].z >> 16), CU), atoms_add(sb + OFF_CNT2 + (e[k].w >> 16), CU));
            }
            nb_sync<1, 96>();
            STAMPT(576, 17);
            for (unsigned G = ht >> 5; G < 5; G += 3) {
                const unsigned ca = sb + OFF_CNT2 + G * 512 + lane * 16;
                const uint4 c = lds128(ca);
                const unsigned dp = hmul2(lds32(sb + OFF_DIS + (G * 8 + g) * 4), 0x43004300u);
                const bool sw = lane >= 16;
                unsigned s1 = sw ? c.y : c.x, s2 = c.x + c.y, s3 = s2 + (sw ? c.w : c.z), tot = s2 + c.z + c.w, inc = tot;
                unsigned u = __shfl_up_sync(~0u, inc, 8); if (lane >= 8) inc += u;
                u = __shfl_up_sync(~0u, inc, 16); if (sw) inc += u;
                const unsigned base = inc - tot;
                const unsigned p0 = min(base, LCAP * CU), p1 = min(base + s1, LCAP * CU), p2 = min(base + s2, LCAP * CU), p3 = min(base + s3, LCAP * CU);
                sts128(ca, make_uint4((sw ? p1 : p0) + 16 * CU, (sw ? p0 : p1) + 16 * CU, (sw ? p3 : p2) + 16 * CU, (sw ? p2 : p3) + 16 * CU));
                const unsigned word = __byte_perm(__byte_perm(p0, p1, 0x0040), __byte_perm(p2, p3, 0x0040), 0x5410);
                const unsigned wa = __shfl_sync(~0u, word, (g >> 1) * 8 + 2 * t), wb = __shfl_sync(~0u, word, (g >> 1) * 8 + 2 * t + 1);
                unsigned hdr = __byte_perm(wa, wb, (g & 1) ? 0x7362 : 0x5140);
                if (__any_sync(~0u, inc > 48 * CU)) hdr |= 0x80;
                asm volatile("st.shared.v2.u32 [%0],{%1,%2};" ::"r"(sb + OFF_IMG + G * 512 + lane * 16), "r"(hdr), "r"(__byte_perm(dp, dp, sw ? 0x1032 : 0x3210)) : "memory");
            }
            nb_sync<1, 96>();
            int hmax = 0;
#pragma unroll
            for (int k0 = 0; k0 < 6; k0 += 3) {
#pragma unroll
                for (int k = k0; k < k0 + 3; k++) { e[k] = lds128(sb + OFF_MAIL + (ht + k * 96) * 16); e[k].w &= 0x7FFFFFFFu; }
#pragma unroll
                for (int k = k0; k < k0 + 3; k++) {
                    h[k].x += lds32(sb + OFF_CNT2 + (e[k].x >> 16)); h[k].y += lds32(sb + OFF_CNT2 + (e[k].y >> 16));
                    h[k].z += lds32(sb + OFF_CNT2 + (e[k].z >> 16)); h[k].w += lds32(sb + OFF_CNT2 + (e[k].w >> 16));
                }
#pragma unroll
                for (int k = k0; k < k0 + 3; k++) {
                    place(e[k].x, h[k].x); place(e[k].y, h[k].y); place(e[k].z, h[k].z); place(e[k].w, h[k].w);
                    hmax = max(hmax, max(max((int)h[k].x, (int)h[k].y), max((int)h[k].z, (int)h[k].w)));
                }
            }
            if (__builtin_expect(hmax >= (int)((LCAP + 16) * CU), 0)) {
#pragma unroll
                for (int k = 0; k < 6; k++)
                    late |= ((h[k].x >= (LCAP + 16) * CU) | (h[k].y >= (LCAP + 16) * CU) << 1 | (h[k].z >= (LCAP + 16) * CU) << 2 | (h[k].w >= (LCAP + 16) * CU) << 3) << (4 * k);
            }
            if (__builtin_expect(late, 0)) bin_overflow(sc, late, ht);
            fence_async_smem();
            nb_sync<1, 96>();
            STAMPT(576, 18);
        }
        if (ht < 32 && elect()) {
            if (rowcta) {
                for (int c = 0; c < 3; c++) bulk_s2g(sc->lists + (c * LSTR + b * 160), sb + OFF_IMG + c * 4096, 2560);
                asm volatile("cp.async.bulk.commit_group;" ::: "memory");
                const unsigned novf = lds32(sb + OFF_MISC), bad = lds32(sb + OFF_MISC + 20);
                if (__builtin_expect(novf | bad, 0)) {
                    sc->ovfn[b] = make_uint2(lds32(sb + OFF_MISC + 48), novf);
                    raise_flag(&sc->bar[4 * 64 + 1], lds32(sb + OFF_MISC + 48), (novf ? 1 : 0) | (bad ? 2 : 0));
                    __threadfence();
                }
                asm volatile("cp.async.bulk.wait_group 0;" ::: "memory");
                fence_async_gmem();
            }
            bar_arrive_relaxed(&sc->bar[4 * 64]);
            STAMPT(544, 19);
            sts32(sb + OFF_MISC + 28, bar_poll2(&sc->bar[4 * 64], lds32(sb + OFF_MISC + 48)));
            mbar_arrive(bar_c);
            STAMPT(544, 23);
        }
    } else {
        const bool one = elect();
        auto load_xl = [&](int i) {
            mbar_expect(bar_full + 8 * i, 32768 + 10240);
            tma_load2d(sb + OFF_T + i * 10240, &tm_x, i * 64, b * TILE, bar_full + 8 * i);
            tma_load3d(sb + OFF_S + i * 32768, &tm_wl, i * 64, bar_full + 8 * i);
        };
        auto load_m = [&](int i, int slot) {
            mbar_expect(bar_full + 32 + 8 * i, 32768);
            bulk_g2s(sb + OFF_S + slot * 32768, sc->mimg + i * 2048, 32768, bar_full + 32 + 8 * i);
        };
        auto load_v = [&](int i, int slot) {
            mbar_expect(bar_full + 64 + 8 * i, 32768);
            tma_load3d(sb + OFF_S + slot * 32768, &tm_wv, i * 64, bar_full + 64 + 8 * i);
        };
        const char* hsl = (const char*)(sc->hs + slice * NN);
        auto fill = [&](int slot) { bulk_g2s(sb + OFF_S + slot * 32768, hsl + slot * 32768, slot == 4 ? NN * 16 - 4 * 32768 : 32768, bar_fill); };
        const unsigned t0 = clock();
        if (one) {
            for (int i = 0; i < 2; i++) mbar_init(bar_full + 8 * i, 1);
            asm volatile("fence.mbarrier_init.release.cluster;" ::: "memory");
            while ((unsigned)clock() - t0 < XD0) {}
            if (rowcta) load_xl(0);
            STAMPT(512, 41);
            for (int i = 2; i < 12; i++) mbar_init(bar_full + 8 * i, 1);
            mbar_init(bar_go, 1 + GATE2);
            for (int i = 0; i < 4; i++) mbar_init(bar_fill + 8 * i, 1);
            for (int i = 0; i < 10; i++) mbar_init(bar_rd + 8 * i, i < 9 ? 16 : g1 - g0 - 144);
            asm volatile("fence.mbarrier_init.release.cluster;" ::: "memory");
            if ((unsigned)__cvta_generic_to_shared(smem_raw) != sb) __trap();
            mbar_expect(bar_fill, NN * 16);
        }
        __syncwarp();
        nb_arrive<3, 544>();
        nb_arrive<13, 160>();
        if (one && rowcta) {
            while ((unsigned)clock() - t0 < XD1) {}
            load_xl(1);
            STAMPT(512, 40);
        }
        __syncwarp();
        nb_sync<15, 64>();
        if (rowcta) {
            if (one) {
                if (XD2) { while ((unsigned)clock() - t0 < XD2 + 1) {} } else mbar_wait(bar_full);
                load_xl(2);
                STAMPT(512, 52);
                mbar_wait(bar_full + (XD2 ? 0 : 8)); load_xl(3);
                STAMPT(512, 53);
                bar_poll(sc, 3);
                STAMPT(512, 48);
                fence_async_gmem();
            }
            WAIT_EV(5); if (one) { load_m(0, 0); load_m(1, 1); mbar_arrive(bar_go); }
            WAIT_EV(6); if (one) load_m(2, 3);
            WAIT_EV(7); if (one) load_m(3, 0);
            WAIT_EV(12); if (one) bar_arrive(&sc->bar[2 * 64]);
            STAMPT(512, 24);
            WAIT_EV(14); if (one) { fence_async_smem(); load_v(0, 4); load_v(1, 2); }
            WAIT_EV(15);
            if (one) {
                fence_async_smem();
                load_v(2, 1); load_v(3, 3);
                bar_poll(sc, 2);
                fence_async_gmem();
            }
            STAMPT(512, 25);
            WAIT_EV(2); if (one) fill(0);
            WAIT_EV(4); if (one) fill(4);
            WAIT_EV(5); if (one) fill(2);
            WAIT_EV(6); if (one) fill(1);
            WAIT_EV(7); if (one) fill(3);
            WAIT_EV(12);
            if (one) {
#pragma unroll
                for (int kb = 0; kb < 4; kb++)
                    asm volatile("cp.async.bulk.tensor.2d.global.shared::cta.bulk_group [%0,{%2,%3}],[%1];"
                                 ::"l"(&tm_ot), "r"(sb + OFF_T + kb * 10240), "r"(kb * 64), "r"(b * TILE) : "memory");
                asm volatile("cp.async.bulk.commit_group;" ::: "memory");
                asm volatile("cp.async.bulk.wait_group 0;" ::: "memory");
                fence_async_gmem();
            }
        } else {
            if (one) {
                bar_arrive(&sc->bar[2 * 64]);
                bar_poll(sc, 2);
                fence_async_gmem(); fence_async_smem();
                for (int i = 0; i < 5; i++) fill(i);
            }
        }
        if (one) {
            bar_arrive_relaxed(&sc->bar[1 * 64]);
            mbar_arrive(bar_t);
            STAMPT(512, 26);
            bar_poll(sc, 1);
            fence_async_gmem();
            STAMPT(512, 27);
            for (int r = 0; r < 9; r++) {
                mbar_wait(bar_rd + 8 * r);
                fence_async_smem();
                tma_reduce(&tm_o256, sb + OFF_STG + r * 4096, slice * 8, (g0 + 16 * r) * 16);
            }
            mbar_wait(bar_rd + 72);
            fence_async_smem();
            for (int i = 144; i < g1 - g0; i++) tma_reduce(&tm_o16, sb + OFF_STG + i * 256, slice * 8, (g0 + i) * 16);
            asm volatile("cp.async.bulk.commit_group;" ::: "memory");
            asm volatile("cp.async.bulk.wait_group.read 0;" ::: "memory");
            STAMPT(512, 13);
        }
    }
    } else {
    if (tid < 32) {
        unsigned bad = 0;
        uint4 xd[3];
#pragma unroll
        for (int k = 0; k < 3; k++) xd[k] = ldg_na((const uint4*)edst + min(b * TILE + k * 32 + lane, NN - 1u));
#pragma unroll
        for (int k = 0; k < 3; k++) { const unsigned n = min(b * TILE + k * 32 + lane, NN - 1u); bad |= (xd[k].x ^ n) | (xd[k].y ^ n) | (xd[k].z ^ n) | (xd[k].w ^ n); }
        bad = __any_sync(~0u, bad);
        if (lane == 0) sts32(sb + OFF_MISC + 20, bad);
        __syncwarp();
        nb_arrive<13, 160>();
    } else if (tid < 64) {
        const uint4* ep = (const uint4*)esrc + (min(b, NT - 1u) * TILE + lane);
        cp16(sb + OFF_EIDX + lane * 16, ep); cp16(sb + OFF_EIDX + 512 + lane * 16, ep + 32);
        if (lane < 16) cp16(sb + OFF_EIDX + 1024 + lane * 16, ep + 64);
        if (lane < 10) cp16(sb + OFF_DIS + lane * 16, dis + (min(b, NT - 1u) * 10 + lane));
        cp_commit();
        cp_wait<0>();
        nb_arrive<13, 160>();
    } else if (tid >= 192) {
        if (rowcta) {
            const unsigned bt = tid - 192;
            const uint4 ed = ldg_na(dst4 + (b * 320 + bt)), es = ldg_na(src4 + (b * 320 + bt));
            const unsigned pad = (PADBIN + 4 * ((bt & 3) + ((b * 4) & 28))) << 16;
#pragma unroll
            for (int k = 0; k < 4; k++) if ((k & 1) == 0 || bt < 180) sts128(sb + OFF_MAIL + (k >> 1) * 9216 + (bt + (k & 1) * 320) * 16, make_uint4(pad, pad, pad, pad));
            const unsigned cz = bt < (512 + PADBIN) / 16 ? 0 : 0x40000000;
            if (bt < (512 + 2688) / 16) sts128(sb + OFF_CNT1 + bt * 16, make_uint4(cz, cz, cz, cz));
            if (bt == 319) sts128(sb + OFF_MISC, make_uint4(0, 0, 0, 0));
            unsigned z;
            asm volatile("{.reg .pred p; setp.eq.u32 p,%1,0xFFFFFFFF; bar.red.popc.u32 %0,4,320,p;}" : "=r"(z) : "r"(bt) : "memory");
            const unsigned dd[4] = {ed.x + z, ed.y + z, ed.z + z, ed.w + z}, ss[4] = {es.x + z, es.y + z, es.z + z, es.w + z};
            unsigned rk[4], ow[4];
#pragma unroll
            for (int i = 0; i < 4; i++) { ow[i] = dd[i] / TILE; rk[i] = atoms_inc(sb + OFF_CNT1 + ow[i] * 4); }
#pragma unroll
            for (int i = 0; i < 4; i++) {
                const unsigned dl = dd[i] - ow[i] * TILE;
                const unsigned e = bitsel(ss[i] << 20, bitsel(dl << 21, dl << 18, 0xFF800000u), 0x00700000u) + (ss[i] >> 3);
                asm volatile("{.reg .pred p; setp.lt.u32 p,%2,%3; @p st.shared.u32 [%0],%1;}" ::"r"(sb + OFF_MAIL + ow[i] * 64 + rk[i] * 4 + (rk[i] >> 4) * (9216 - 64)), "r"(e), "r"(rk[i]), "n"(CELL) : "memory");
            }
            if (__builtin_expect((rk[0] | rk[1] | rk[2] | rk[3]) >= CELL, 0)) {
#pragma unroll
                for (int i = 0; i < 4; i++) if (rk[i] >= CELL) push_overflow(sc, dd[i], ss[i]);
            }
        }
        STAMPT(416, 44);
        nb_arrive<2, 352>();
    } else {
        const unsigned fw = b >> 3, hq = b & 7, q = (tid >> 5) - 2;
        const unsigned ma = sb + OFF_S + 4 * 32768 + 8192 + q * 6144;
        {
            const unsigned r = lane >> 3, da = ma + r * 128 + (((lane ^ r) & 7) << 4);
            const uint4* pa = wq + ((16 * fw + r) * 32 + q * 8 + (lane & 7));
            const uint4* pb = wk + ((32 * hq + r) * 32 + q * 8 + (lane & 7));
#pragma unroll
            for (int u = 0; u < 12; u++) cp16((da ^ ((u & 1) << 6)) + u * 512, u < 4 ? pa + u * 128 : pb + (u - 4) * 128);
            cp_commit();
        }
        const unsigned aa = ma + (lane & 15) * 128 + ((((lane >> 4) ^ lane) & 7) << 4);
        const unsigned br = 4 * ((lane & 7) >> 1) + 2 * (lane >> 4) + (lane & 1);
        const unsigned ba = ma + 2048 + br * 128 + (((((lane >> 3) & 1) ^ br) & 7) << 4);
        float c[4][4];
#pragma unroll
        for (int u = 0; u < 4; u++) c[u][0] = c[u][1] = c[u][2] = c[u][3] = 0.f;
        STAMPT(64, 38);
        cp_wait<0>();
        __syncwarp();
        STAMPT(64, 39);
#pragma unroll
        for (int k = 0; k < 4; k++) {
            const uint4 a = ldsm4(aa ^ (k << 5)), b0 = ldsm4(ba ^ (k << 5)), b1 = ldsm4((ba ^ (k << 5)) + 2048);
            mma16816(c[0], a.x, a.y, a.z, a.w, b0.x, b0.y); mma16816(c[1], a.x, a.y, a.z, a.w, b0.z, b0.w);
            mma16816(c[2], a.x, a.y, a.z, a.w, b1.x, b1.y); mma16816(c[3], a.x, a.y, a.z, a.w, b1.z, b1.w);
        }
        const unsigned ra = sb + OFF_S + 4 * 32768 + lane * 16;
#pragma unroll
        for (int i = 0; i < 4; i++)
            sts128(ra + q * 2048 + i * 512, make_uint4(__float_as_uint(c[2 * (i & 1)][2 * (i >> 1)]), __float_as_uint(c[2 * (i & 1)][2 * (i >> 1) + 1]),
                                                       __float_as_uint(c[2 * (i & 1) + 1][2 * (i >> 1)]), __float_as_uint(c[2 * (i & 1) + 1][2 * (i >> 1) + 1])));
        STAMPT(64, 42);
        nb_sync<8, 128>();
        float m[4] = {0, 0, 0, 0};
#pragma unroll
        for (int i = 0; i < 4; i++) {
            const uint4 u = lds128(ra + i * 2048 + q * 512);
            m[0] += __uint_as_float(u.x); m[1] += __uint_as_float(u.y); m[2] += __uint_as_float(u.z); m[3] += __uint_as_float(u.w);
        }
        const float k = 0.0625f * 1.4426950408889634f;
        asm volatile("st.shared.v2.u32 [%0],{%1,%2};" ::"r"(sb + OFF_MAIL + 8000 + (8 * (q >> 1) + g) * 64 + ((((q & 1) * 2 + (t >> 1)) ^ g) & 3) * 16 + (t & 1) * 8),
                     "r"(pack2(m[0] * k, m[1] * k)), "r"(pack2(m[2] * k, m[3] * k)) : "memory");
        fence_async_smem();
        STAMPT(64, 43);
        nb_arrive<14, 192>();
    }
    asm volatile("setmaxnreg.inc.sync.aligned.u32 %0;" ::"n"(REG_W));
    const int w = __shfl_sync(~0u, tid >> 5, 0), wg = w >> 2;
    const int grp0 = g0 + w;
    const uint4* lp = sc->lists + (grp0 * 32 + lane);
    uint4 L0, L1;
    nb_sync<3, 544>();

    if (__builtin_expect(rowcta, 1)) {
        const unsigned descA = 0x10000u + (sb + OFF_S) / 16 + wg * 512;
        const unsigned greg = sb + OFF_S + w * 2048 + lane * 16;
        float d[40];
        unsigned pk[20];
        unsigned* hp = (unsigned*)(sc->hs + (2 * w * NN + b * TILE)) + lane;
        auto mma_k = [&](int Q, int slot, int st, int k0, int k1) {
            if (st < 0) wg_fence();
#pragma unroll
            for (int k = k0; k < k1; k++) {
                if (st >= 0) wg_fence();
                wg80(d, descA + slot * 2048 + k * 128, 0x10000u + (sb + OFF_T) / 16 + (Q & 3) * 640 + k * 2, ((Q & 3) | k) != 0);
                if (st >= 0) {
#pragma unroll
                    for (int j = st + k; j < st + k + 1; j++)
                        if (j < 20) asm volatile("st.global.u32 [%0],%1;" ::"l"(hp + (j >> 1) * 32 + (j & 1) * (NN * 4)), "r"(pk[j]) : "memory");
                }
            }
            wg_commit();
        };
        auto mma_q = [&](int Q, int slot, int st) { mma_k(Q, slot, st, 0, 4); };
        auto mma_head = [&](int Q, int slot, int st) { mma_k(Q, slot, st, 0, KH); wg_wait<1>(); };
        auto mma_tail = [&](int Q, int slot, int st) { mma_k(Q, slot, st, KH, 4); };
        const uint4* xl = x + lane;
        auto eidx = [&](int i) { return lds128(sb + OFF_EIDX + (w * 5 + i) * 16); };
        auto gather = [&](const uint4& ix, int slot) {
            cp16(greg + slot * 32768, xl + ix.x * 32u); cp16(greg + slot * 32768 + 512, xl + ix.y * 32u);
            cp16(greg + slot * 32768 + 1024, xl + ix.z * 32u); cp16(greg + slot * 32768 + 1536, xl + ix.w * 32u);
            cp_commit();
        };
        const uint4 ix0 = eidx(0), ix1 = eidx(1), ix2 = eidx(2), ix3 = eidx(3), ix4 = eidx(4);
        uint4 gv[5][4];
        const unsigned gld = sb + OFF_S + w * 2048 + ((lane >> 3) & 1) * 512 + (lane >> 4) * 128 + (lane & 7) * 16;
        auto to_regs = [&](int i, int slot) {
            __syncwarp();
#pragma unroll
            for (int j = 0; j < 4; j++) gv[i][j] = ldsm4(gld + slot * 32768 + (j & 1) * 256 + (j >> 1) * 1024);
        };
        float ds[20];
#pragma unroll
        for (int j = 0; j < 10; j++) { const unsigned v = lds32(sb + OFF_DIS + (4 * j + t) * 4); ds[2 * j] = blo_v(v); ds[2 * j + 1] = bhi_v(v); }
        STAMPT(288, 2);
        mbar_wait(bar_full);
        STAMPT(288, 3);
        mma_q(0, 0, -1);
        mbar_wait(bar_full + 8);
        STAMPT(288, 50);
        mma_q(1, 1, -1);
        mbar_wait(bar_full + 16);
        STAMPT(288, 51);
        mma_head(2, 2, -1);
        EV(5);
        mma_tail(2, 2, -1);
        mbar_wait(bar_full + 24);
        STAMP(5);
        mma_q(3, 3, -1);
        mbar_wait(bar_go);
        gather(ix0, 4);
        wg_wait<0>();
        EV(6);
        STAMP(6);
#pragma unroll
        for (int j = 0; j < 20; j++) pk[j] = movm(pack2(d[2 * j] * ds[2 * (j >> 1)], d[2 * j + 1] * ds[2 * (j >> 1) + 1]));
#pragma unroll
        for (int j = 0; j < STPRE; j++) asm volatile("st.global.u32 [%0],%1;" ::"l"(hp + (j >> 1) * 32 + (j & 1) * (NN * 4)), "r"(pk[j]) : "memory");
        STAMP(7);
        nb_sync_id(8 + wg, 128);
        if (G1POS == 0) gather(ix1, 2);
        mbar_wait(bar_full + 32);
        if (G1POS == 1) gather(ix1, 2);
        STAMP(21);
        mma_q(4, 0, STPRE);
        STAMP(28);
        mbar_wait(bar_full + 40);
        mma_head(5, 1, STPRE + 4);
        EV(7);
        mma_tail(5, 1, STPRE + 4);
        STAMP(29);
        mbar_wait(bar_full + 48);
        STAMP(30);
        mma_head(6, 3, STPRE + 8);
        nb_sync_id(8 + wg, 128);
        gather(ix2, 1);
        mma_tail(6, 3, STPRE + 8);
        STAMP(31);
        mbar_wait(bar_full + 56);
        STAMP(32);
        mma_head(7, 0, STPRE + 12);
        nb_sync_id(8 + wg, 128);
        gather(ix3, 3);
        mma_tail(7, 0, STPRE + 12);
        EV(12);
        wg_wait<0>();
        STAMP(20);
        pack_acc(pk, d);
        nb_sync<0, 512>();
        acc_to_tile(pk, w, lane);
        gather(ix4, 0);
        cp_wait<3>();
        to_regs(0, 4);
        nb_sync<0, 512>();
        STAMP(8);
        {
            const unsigned delta = t ^ (g >> 1), alsm = sb + OFF_ALPHA + w * 128;
            const bool par = g & 1;
            unsigned ta[5];
#pragma unroll
            for (int i = 0; i < 5; i++) ta[i] = tile_addr(w * 5 + i, lane);
            float v[4], u[4];
            to_regs(1, 2);
            EV(14);
            attn_scores(v, true, par, gv[0], ta[0]);
            attn_scores(v, delta == 1, par, gv[1], ta[1] ^ 32);
            cp_wait<2>();
            to_regs(2, 1);
            attn_scores(v, delta == 2, par, gv[2], ta[2] ^ 64);
            STAMP(33);
            cp_wait<1>();
            to_regs(3, 3);
            EV(15);
            STAMP(34);
            attn_scores(v, delta == 3, par, gv[3], ta[3] ^ 96);
            cp_wait<0>();
            to_regs(4, 0);
            STAMP(35);
            attn_scores(u, true, par, gv[4], ta[4]);
            attn_softmax(v, u, lane, alsm + ((lane & 4) + delta) * 16 + (lane >> 3) * 4);
            uint4 al = lds128(alsm);
#pragma unroll
            for (int i = 0; i < 5; i++) {
                const uint4 a = al;
                if (i < 4) al = lds128(alsm + (i + 1) * 16);
                attn_mix(gv[i], a, ta[i]);
            }
        }
        mbar_wait(bar_full + 64);
        fence_async_smem();
        STAMP(22);
        EV(2);
        nb_sync<0, 512>();
        mma_q(8, 4, -1);
        mbar_wait(bar_full + 72);
        mma_head(9, 2, -1);
        EV(4);
        mma_tail(9, 2, -1);
        mbar_wait(bar_full + 80);
        mma_head(10, 1, -1);
        EV(5);
        mma_tail(10, 1, -1);
        mbar_wait(bar_full + 88);
        mma_head(11, 3, -1);
        EV(6);
        mma_tail(11, 3, -1);
        wg_wait<0>();
        EV(7);
        STAMP(9);
        pack_acc(pk, d);
        mbar_wait(bar_c);
        L0 = ldg_na(lp); L1 = ldg_na(lp + LSTR);
        nb_sync<0, 512>();
        STAMP(10);
        if (__builtin_expect(lds32(sb + OFF_MISC + 28) & 2, 0)) {
            for (int i = 0; i < 5; i++) sts128(tile_addr(w * 5 + i, lane), attn_generic(b * TILE + w * 5 + i, x, esrc, edst, wq, wk, wv));
        } else {
            acc_to_tile(pk, w, lane);
        }
        fence_async_smem();
        EV(12);
    } else {
        mbar_wait(bar_c);
        L0 = ldg_na(lp); L1 = ldg_na(lp + LSTR);
    }

    const int cnt = (g1 - grp0 + 15) >> 4;
    const bool anyovf = lds32(sb + OFF_MISC + 28) & 1;
    if (lane < 8) sts128(sb + OFF_S + NN * 16 + lane * 16, make_uint4(0, 0, 0, 0));
    const unsigned lb = sb + OFF_S + (lane & 7) * 16;
    const unsigned dummy = anyovf ? 0 : lb + 1250 * 128;
    const float zmask = (lane >= 28) ? 0.f : -1.f;
    unsigned stg = sb + OFF_STG + w * 256 + (((lane & 7) * 2 + ((lane >> 3) & 1)) ^ ((lane >> 2) & 1)) * 16;
    __syncwarp();
    mbar_wait(bar_fill);
    STAMP(11);
    for (int it = 0; it < cnt; it++) {
        unsigned ad[12];
        ad[0] = dp2lo(L0.z, lb); ad[1] = dp2hi(L0.z, lb); ad[2] = dp2lo(L0.w, lb); ad[3] = dp2hi(L0.w, lb);
        ad[4] = dp2lo(L1.x, lb); ad[5] = dp2hi(L1.x, lb); ad[6] = dp2lo(L1.y, lb); ad[7] = dp2hi(L1.y, lb);
        ad[8] = dp2lo(L1.z, lb); ad[9] = dp2hi(L1.z, lb); ad[10] = dp2lo(L1.w, lb); ad[11] = dp2hi(L1.w, lb);
        unsigned sA = __byte_perm(L0.x, 0x64646464u, 0x4140), nB = __byte_perm(L0.x, 0xE4E4E4E4u, 0x4342);
        float dA = blo_v(L0.y), dB = bhi_v(L0.y);
        lp += 16 * 32;
        L0 = ldg_na(lp); L1 = ldg_na(lp + LSTR);
        float acc0[4] = {0, 0, 0, 0}, acc1[4] = {0, 0, 0, 0};
        if (!__any_sync(~0u, ad[10] != dummy)) {
            if (__any_sync(~0u, ad[9] != dummy)) p3_steps<10>(acc0, acc1, ad, sA, nB);
            else p3_steps<9>(acc0, acc1, ad, sA, nB);
        } else if (!__any_sync(~0u, ad[11] != dummy)) {
            p3_steps<11>(acc0, acc1, ad, sA, nB);
        } else {
            const bool longer = (sA & 0x80) || anyovf;
            sA &= ~0x80u;
            p3_steps<12>(acc0, acc1, ad, sA, nB);
            if (__any_sync(~0u, longer)) {
                uint4 C2 = ldg_na(lp - 16 * 32 + 2 * LSTR);
                unsigned e2[4] = {C2.x, C2.y, C2.z, C2.w};
#pragma unroll
                for (int s = 12; s < 20; s++) p3_step(acc0, acc1, (s & 1) ? dp2hi(e2[(s - 12) >> 1], lb) : dp2lo(e2[(s - 12) >> 1], lb), s, sA, nB);
                if (anyovf) {
                    float4 e = p3_overflow(sc, grp0 + 16 * it, sb + OFF_S);
                    float s0 = e.x + e.z, s1 = e.y + e.w;
                    for (int k = 4; k < 32; k <<= 1) {
                        float u0 = __shfl_down_sync(~0u, s0, k), u1 = __shfl_down_sync(~0u, s1, k);
                        if (lane + k < 32) { s0 += u0; s1 += u1; }
                    }
                    acc0[0] += s0; acc0[1] += s1; acc0[2] += s0 - e.x; acc0[3] += s1 - e.y;
                }
            }
        }
        float c0 = acc0[0] + acc1[0], c1 = acc0[1] + acc1[1], c2 = acc0[2] + acc1[2], c3 = acc0[3] + acc1[3];
        float n0 = __shfl_down_sync(~0u, c0, 4), n1 = __shfl_down_sync(~0u, c1, 4);
        float o0 = c0 - c2, o1 = c1 - c3, o2 = fmaf(n0, zmask, c2), o3 = fmaf(n1, zmask, c3);
        if (it == 6) mbar_wait(bar_t);
        asm volatile("stmatrix.sync.aligned.m8n8.x2.shared.b16 [%0],{%1,%2};" ::"r"(stg), "r"(pack2(o0 * dA, o1 * dA)), "r"(pack2(o2 * dB, o3 * dB)) : "memory");
        __syncwarp();
        asm volatile("{.reg .pred p; setp.eq.u32 p,%1,0; @p mbarrier.arrive.shared.b64 _,[%0];}" ::"r"(bar_rd + 8 * it), "r"(lane) : "memory");
        stg += 4096;
    }
    STAMP(12);
    }
}

typedef CUresult (*EncodeFn)(CUtensorMap*, CUtensorMapDataType, cuuint32_t, void*, const cuuint64_t*, const cuuint64_t*,
                             const cuuint32_t*, const cuuint32_t*, CUtensorMapInterleave, CUtensorMapSwizzle,
                             CUtensorMapL2promotion, CUtensorMapFloatOOBfill);

}

extern "C" void kernel_launch(void* const* d_in, const int* in_sizes, int n_in, void* d_out, int out_size) {
    (void)in_sizes; (void)n_in; (void)out_size;
    static EncodeFn enc = nullptr;
    static void* scratch = nullptr;
    if (!enc) {
        cudaGetSymbolAddress(&scratch, g_scratch);
        void* fn = nullptr;
        cudaDriverEntryPointQueryResult qr;
        cudaGetDriverEntryPoint("cuTensorMapEncodeTiled", &fn, cudaEnableDefault, &qr);
        enc = (EncodeFn)fn;
        cudaFuncSetAttribute(exphormer_kernel, cudaFuncAttributeMaxDynamicSharedMemorySize, SMEM_BYTES);
    }
    CUtensorMap tm_mail, tm_x, tm_wl, tm_wv, tm_ot, tm_o256, tm_o16;
    auto mk = [&](CUtensorMap* tm, void* p, int rows, int bc, int br, CUtensorMapSwizzle sw, CUtensorMapL2promotion pr) {
        cuuint64_t gd[2] = {256, (cuuint64_t)rows}, gs[1] = {512};
        cuuint32_t es[2] = {1, 1}, bx[2] = {(cuuint32_t)bc, (cuuint32_t)br};
        enc(tm, CU_TENSOR_MAP_DATA_TYPE_BFLOAT16, 2, p, gd, gs, bx, es, CU_TENSOR_MAP_INTERLEAVE_NONE, sw, pr, CU_TENSOR_MAP_FLOAT_OOB_FILL_NONE);
    };
    for (int i = 0; i < 2; i++) {
        cuuint64_t gd[3] = {64, 256, 4}, gs[2] = {512, 128};
        cuuint32_t es[3] = {1, 1, 1}, bx[3] = {64, 64, 4};
        enc(i ? &tm_wv : &tm_wl, CU_TENSOR_MAP_DATA_TYPE_BFLOAT16, 3, d_in[i ? 9 : 6], gd, gs, bx, es, CU_TENSOR_MAP_INTERLEAVE_NONE,
            CU_TENSOR_MAP_SWIZZLE_128B, CU_TENSOR_MAP_L2_PROMOTION_L2_128B, CU_TENSOR_MAP_FLOAT_OOB_FILL_NONE);
    }
    {
        cuuint64_t gd[2] = {2048, NT}, gs[1] = {8192};
        cuuint32_t es[2] = {1, 1}, bx[2] = {16, NT};
        enc(&tm_mail, CU_TENSOR_MAP_DATA_TYPE_UINT32, 2, ((Scratch*)scratch)->mail, gd, gs, bx, es, CU_TENSOR_MAP_INTERLEAVE_NONE,
            CU_TENSOR_MAP_SWIZZLE_NONE, CU_TENSOR_MAP_L2_PROMOTION_NONE, CU_TENSOR_MAP_FLOAT_OOB_FILL_NONE);
    }
    mk(&tm_x, d_in[0], NN, 64, TILE, CU_TENSOR_MAP_SWIZZLE_128B, CU_TENSOR_MAP_L2_PROMOTION_L2_128B);
    mk(&tm_ot, d_out, NN, 64, TILE, CU_TENSOR_MAP_SWIZZLE_128B, CU_TENSOR_MAP_L2_PROMOTION_NONE);
    mk(&tm_o256, d_out, NN, 8, 256, CU_TENSOR_MAP_SWIZZLE_NONE, CU_TENSOR_MAP_L2_PROMOTION_NONE);
    mk(&tm_o16, d_out, NN, 8, 16, CU_TENSOR_MAP_SWIZZLE_NONE, CU_TENSOR_MAP_L2_PROMOTION_NONE);
    exphormer_kernel<<<NCTA, 640, SMEM_BYTES>>>(
        (const uint4*)d_in[0], (const uint4*)d_in[2], (const uint4*)d_in[1], (const uint4*)d_in[7], (const uint4*)d_in[8], (const int*)d_in[3],
        (const int*)d_in[4], (Scratch*)scratch, (const uint4*)d_in[5], (const uint4*)d_in[9],
        tm_x, tm_wl, tm_wv, tm_mail, tm_ot, tm_o256, tm_o16);
}
```

```cpp
#include <cuda_runtime.h>
#include <cuda_bf16.h>
#include <cuda.h>
#include <stdint.h>

namespace {

constexpr int NN = 10000, NE = 160000, NEE = 40000;
constexpr int TILE = 80, NT = 125, NCTA = 128, NG = 625, EPC = 1280;
constexpr int CELL = 32;
constexpr int LCAP = 80;
constexpr int OVCAP = EPC + NT * CELL;
#define XD0 700
#define XD1 1100
#define XD2 1900
#define REG_W 104
#define REG_H 64
#define KH 2
#define POLLNS 0
#define STPRE 4
#define G0POS 0
#define G1POS 1
#define GATE2 0
constexpr unsigned DUMMY2 = 1250u | (1250u << 16);

constexpr unsigned sb = 1024;
constexpr int OFF_S = 0;
constexpr int OFF_R = 163840;
constexpr int OFF_BAR = OFF_R;
constexpr int OFF_MISC = OFF_R + 256;
constexpr int OFF_DIS = OFF_R + 320;
constexpr int OFF_PROF = OFF_R + 512;
constexpr int OFF_EIDX = OFF_R + 1024;
constexpr int OFF_ALPHA = OFF_R + 1024;
constexpr int OFF_STG = OFF_R + 2048;
constexpr int OFF_CNT1 = OFF_R + 2560;
constexpr int OFF_CNT2 = OFF_R + 3072;
constexpr int OFF_MAIL = OFF_R + 5760;
constexpr int OFF_IMG = OFF_MAIL + 9216;
constexpr int OFF_T = OFF_R + 26624;
constexpr int SMEM_BYTES = OFF_T + 40960;
static_assert(SMEM_BYTES <= 232448 && OFF_T % 1024 == 0 && OFF_STG + 6 * 4096 == OFF_T && OFF_IMG + 10752 <= OFF_T, "smem");
constexpr unsigned bar_fill = sb + OFF_BAR, bar_t = bar_fill + 8, bar_mail = bar_fill + 16, bar_c = bar_fill + 24, bar_rd = bar_fill + 32,
                   bar_go = bar_fill + 112, bar_full = bar_fill + 120;
constexpr int LSTR = (NG + 16) * 32;

struct __align__(256) Scratch {
    uint4 mimg[8192];
    uint4 hs[32 * NN];
    uint4 mail[2 * NT * 512];
    uint4 lists[3 * LSTR];
    uint2 ovfn[NCTA];
    unsigned bar[5 * 64];
    unsigned ovf[NCTA * OVCAP];
};
__device__ Scratch g_scratch;
#define STAMPT(th, i)
#define STAMP(i) STAMPT(64, i)
#define STAMP2(i) STAMPT(416, i)

__device__ __forceinline__ void bar_arrive(unsigned* p) {
    asm volatile("red.release.gpu.global.add.u32 [%0],1;" ::"l"(p) : "memory");
}
__device__ __forceinline__ void bar_arrive_relaxed(unsigned* p) {
    asm volatile("red.relaxed.gpu.global.add.u32 [%0],1;" ::"l"(p) : "memory");
}
__device__ __forceinline__ void bar_poll(const Scratch* sc, int i) {
    unsigned v, target;
    int lim = 0;
    asm volatile("ld.shared.u32 %0,[%1];" : "=r"(target) : "r"(sb + OFF_MISC + 32 + 4 * i) : "memory");
    while (true) {
        asm volatile("ld.acquire.gpu.global.u32 %0,[%1];" : "=r"(v) : "l"(&sc->bar[i * 64]) : "memory");
        if ((int)(v - target) >= 0) break;
        if (++lim > (1 << 22)) __trap();
        if (POLLNS) __nanosleep(POLLNS);
    }
}
__device__ __forceinline__ unsigned bar_poll2(const unsigned* p, unsigned target) {
    unsigned long long v;
    int lim = 0;
    do {
        asm volatile("ld.acquire.gpu.global.u64 %0,[%1];" : "=l"(v) : "l"(p) : "memory");
        if (++lim > (1 << 22)) __trap();
    } while ((int)((unsigned)v - target) < 0);
    unsigned f = (unsigned)(v >> 32);
    return (f & ~3u) == target ? f & 3 : 0;
}
__device__ __noinline__ void raise_flag(unsigned* p, unsigned target, unsigned bit) {
    unsigned old = atomicCAS(p, 0, 0), seen;
    do {
        seen = old;
        old = atomicCAS(p, seen, ((seen & ~3u) == target ? seen : target) | bit);
    } while (old != seen);
}
__device__ __forceinline__ void mbar_wait(unsigned a) {
    asm volatile("{.reg .pred p; .reg .u32 n;\n"
                 "mov.u32 n,0x400000;\n"
                 "W: mbarrier.try_wait.parity.shared.b64 p,[%0],0;\n"
                 "add.u32 n,n,-1; setp.ne.and.u32 p,n,0,!p; @p bra W;}" ::"r"(a) : "memory");
}
__device__ __forceinline__ bool elect() {
    unsigned r;
    asm volatile("{.reg .pred p; elect.sync _|p,0xFFFFFFFF; selp.u32 %0,1,0,p;}" : "=r"(r));
    return r;
}
__device__ __forceinline__ uint4 ldg_na(const uint4* p) {
    uint4 v;
    asm volatile("ld.global.L1::no_allocate.v4.u32 {%0,%1,%2,%3},[%4];" : "=r"(v.x), "=r"(v.y), "=r"(v.z), "=r"(v.w) : "l"(p) : "memory");
    return v;
}
__device__ __forceinline__ uint4 lds128(unsigned a) {
    uint4 v;
    asm volatile("ld.shared.v4.u32 {%0,%1,%2,%3},[%4];" : "=r"(v.x), "=r"(v.y), "=r"(v.z), "=r"(v.w) : "r"(a) : "memory");
    return v;
}
__device__ __forceinline__ uint4 ldsm4(unsigned a) {
    uint4 v;
    asm volatile("ldmatrix.sync.aligned.m8n8.x4.shared.b16 {%0,%1,%2,%3},[%4];" : "=r"(v.x), "=r"(v.y), "=r"(v.z), "=r"(v.w) : "r"(a) : "memory");
    return v;
}
__device__ __forceinline__ void sts128(unsigned a, uint4 v) {
    asm volatile("st.shared.v4.u32 [%0],{%1,%2,%3,%4};" ::"r"(a), "r"(v.x), "r"(v.y), "r"(v.z), "r"(v.w) : "memory");
}
__device__ __forceinline__ void sts32(unsigned a, unsigned v) { asm volatile("st.shared.u32 [%0],%1;" ::"r"(a), "r"(v) : "memory"); }
__device__ __forceinline__ unsigned lds32(unsigned a) { unsigned v; asm volatile("ld.shared.u32 %0,[%1];" : "=r"(v) : "r"(a) : "memory"); return v; }
__device__ __forceinline__ unsigned atoms_add(unsigned a, unsigned k) { unsigned v; asm volatile("atom.shared.add.u32 %0,[%1],%2;" : "=r"(v) : "r"(a), "r"(k) : "memory"); return v; }
__device__ __forceinline__ unsigned bitsel(unsigned a, unsigned b, unsigned m) { unsigned r; asm("lop3.b32 %0,%1,%2,%3,0xE4;" : "=r"(r) : "r"(a), "r"(b), "r"(m)); return r; }
__device__ __forceinline__ unsigned atoms_inc(unsigned a) { unsigned v; asm volatile("atom.shared.add.u32 %0,[%1],1;" : "=r"(v) : "r"(a) : "memory"); return v; }
__device__ __forceinline__ float blo(unsigned v) { return __uint_as_float(v << 16); }
__device__ __forceinline__ float bhi(unsigned v) { return __uint_as_float(v & 0xFFFF0000u); }
__device__ __forceinline__ float blo_v(unsigned v) { float r; asm volatile("shl.b32 %0,%1,16;" : "=f"(r) : "r"(v)); return r; }
__device__ __forceinline__ float bhi_v(unsigned v) { float r; asm volatile("and.b32 %0,%1,0xFFFF0000;" : "=f"(r) : "r"(v)); return r; }
__device__ __forceinline__ unsigned pack2(float lo, float hi) { unsigned r; asm("cvt.rn.bf16x2.f32 %0,%1,%2;" : "=r"(r) : "f"(hi), "f"(lo)); return r; }

__device__ __forceinline__ void mma16816(float* d, unsigned a0, unsigned a1, unsigned a2, unsigned a3, unsigned b0, unsigned b1) {
    asm volatile("mma.sync.aligned.m16n8k16.row.col.f32.bf16.bf16.f32 {%0,%1,%2,%3},{%4,%5,%6,%7},{%8,%9},{%0,%1,%2,%3};"
                 : "+f"(d[0]), "+f"(d[1]), "+f"(d[2]), "+f"(d[3]) : "r"(a0), "r"(a1), "r"(a2), "r"(a3), "r"(b0), "r"(b1));
}
#define R10(b) "+f"(d[b + 0]), "+f"(d[b + 1]), "+f"(d[b + 2]), "+f"(d[b + 3]), "+f"(d[b + 4]), "+f"(d[b + 5]), "+f"(d[b + 6]), "+f"(d[b + 7]), "+f"(d[b + 8]), "+f"(d[b + 9])
__device__ __forceinline__ void wg80(float* d, unsigned da, unsigned db, int sc) {
    asm volatile("{.reg .pred p; .reg .b64 a, b; setp.ne.b32 p,%42,0; mov.b64 a,{%40,%43}; mov.b64 b,{%41,%43};\n"
                 "wgmma.mma_async.sync.aligned.m64n80k16.f32.bf16.bf16 "
                 "{%0,%1,%2,%3,%4,%5,%6,%7,%8,%9,%10,%11,%12,%13,%14,%15,%16,%17,%18,%19,%20,%21,%22,%23,%24,%25,%26,%27,%28,%29,%30,%31,%32,%33,%34,%35,%36,%37,%38,%39},"
                 "a,b,p,1,1,1,0;}"
                 : R10(0), R10(10), R10(20), R10(30) : "r"(da), "r"(db), "r"(sc), "r"(0x40000040));
}
__device__ __forceinline__ void wg_fence() { asm volatile("wgmma.fence.sync.aligned;" ::: "memory"); }
__device__ __forceinline__ void wg_commit() { asm volatile("wgmma.commit_group.sync.aligned;" ::: "memory"); }
template <int N> __device__ __forceinline__ void wg_wait() { asm volatile("wgmma.wait_group.sync.aligned %0;" ::"n"(N) : "memory"); }
__device__ __forceinline__ void bulk_g2s(unsigned dst, const void* src, unsigned bytes, unsigned bar) {
    asm volatile("cp.async.bulk.shared::cluster.global.mbarrier::complete_tx::bytes [%0],[%1],%2,[%3];" ::"r"(dst), "l"(src), "r"(bytes), "r"(bar) : "memory");
}
__device__ __forceinline__ void fence_async_smem() { asm volatile("fence.proxy.async.shared::cta;" ::: "memory"); }
__device__ __forceinline__ void fence_async_gmem() { asm volatile("fence.proxy.async.global;" ::: "memory"); }

__device__ __forceinline__ unsigned hsat(unsigned a, unsigned c) { unsigned r; asm("add.sat.f16x2 %0,%1,%2;" : "=r"(r) : "r"(a), "r"(c)); return r; }
__device__ __forceinline__ unsigned hset(unsigned a, unsigned c) { unsigned r; asm("set.le.f16x2.f16x2 %0,%1,%2;" : "=r"(r) : "r"(a), "r"(c)); return r; }
__host__ __device__ constexpr unsigned h2c(int v) { return (0x6400u | v) | ((0x6400u | v) << 16); }
__device__ __forceinline__ unsigned dp2lo(unsigned a, unsigned m, unsigned c) { unsigned r; asm("dp2a.lo.u32.u32 %0,%1,%2,%3;" : "=r"(r) : "r"(a), "r"(m), "r"(c)); return r; }
__device__ __forceinline__ unsigned dp2hi(unsigned a, unsigned m, unsigned c) { unsigned r; asm("dp2a.hi.u32.u32 %0,%1,%2,%3;" : "=r"(r) : "r"(a), "r"(m), "r"(c)); return r; }
__device__ __forceinline__ uint4 ldsm4t(unsigned addr) {
    uint4 v;
    asm volatile("ldmatrix.sync.aligned.m8n8.x4.trans.shared.b16 {%0,%1,%2,%3},[%4];" : "=r"(v.x), "=r"(v.y), "=r"(v.z), "=r"(v.w) : "r"(addr));
    return v;
}
__device__ __forceinline__ uint4 ldsm4t_if(unsigned addr, unsigned p) {
    uint4 v;
    asm volatile("{.reg .pred p; setp.ne.u32 p,%5,0; @p ldmatrix.sync.aligned.m8n8.x4.trans.shared.b16 {%0,%1,%2,%3},[%4];}"
                 : "=r"(v.x), "=r"(v.y), "=r"(v.z), "=r"(v.w) : "r"(addr), "r"(p));
    return v;
}
__device__ __forceinline__ void p3_mma(float* acc0, float* acc1, const uint4& v, int s, unsigned sA, unsigned nB) {
    mma16816(acc0, hset(sA, h2c(4 * s + 0)), hsat(nB, h2c(4 * s + 1)), hset(sA, h2c(4 * s + 1)), hsat(nB, h2c(4 * s + 2)), v.x, v.y);
    mma16816(acc1, hset(sA, h2c(4 * s + 2)), hsat(nB, h2c(4 * s + 3)), hset(sA, h2c(4 * s + 3)), hsat(nB, h2c(4 * s + 4)), v.z, v.w);
}
__device__ __noinline__ float4 p3_overflow(const Scratch* sc, int grp, unsigned sS) {
    const unsigned tag = lds32(sb + OFF_MISC + 48);
    int lane = threadIdx.x & 31, g = lane >> 2, t = lane & 3;
    float4 r = make_float4(0.f, 0.f, 0.f, 0.f);
    for (int c = 0; c < NT; c++) {
        const uint2 tn = __ldcg(&sc->ovfn[c]);
        const int n = tn.x == tag ? (int)tn.y : 0;
        for (int i0 = 0; i0 < n; i0 += 32) {
            unsigned e = (i0 + lane < n) ? __ldcg(&sc->ovf[c * OVCAP + i0 + lane]) : 0xFFFFFFFFu;
            unsigned m = __ballot_sync(~0u, (int)(e >> 18) == grp);
            while (m) {
                int j = __ffs(m) - 1;
                m &= m - 1;
                unsigned ee = __shfl_sync(~0u, e, j);
                int row = (ee >> 14) & 15;
                row ^= row >> 3;
                unsigned v = lds32(sS + (ee & 0x3FFF) * 16 + t * 4);
                if ((row >> 1) == g) {
                    if (!(row & 1)) { r.x += blo(v); r.y += bhi(v); } else { r.z += blo(v); r.w += bhi(v); }
                }
            }
        }
    }
    const float k = 1.f / 128.f;
    r.x *= k; r.y *= k; r.z *= k; r.w *= k;
    return r;
}
__device__ __forceinline__ void unpack8(float* f, uint4 v) {
    f[0] = blo(v.x); f[1] = bhi(v.x); f[2] = blo(v.y); f[3] = bhi(v.y); f[4] = blo(v.z); f[5] = bhi(v.z); f[6] = blo(v.w); f[7] = bhi(v.w);
}
__device__ __forceinline__ void vec_mat(float* o, const float* v, const uint4* __restrict__ W, int lane) {
    for (int k = 0; k < 8; k++) o[k] = 0.f;
    for (int l = 0; l < 32; l++) {
#pragma unroll
        for (int i = 0; i < 8; i++) {
            float a = __shfl_sync(~0u, v[i], l), wr[8];
            unpack8(wr, W[(l * 8 + i) * 32 + lane]);
#pragma unroll
            for (int k = 0; k < 8; k++) o[k] = fmaf(a, wr[k], o[k]);
        }
    }
}
__device__ __noinline__ uint4 attn_generic(int node, const uint4* __restrict__ x, const int* __restrict__ esrc, const int* __restrict__ edst,
                                           const uint4* __restrict__ wq, const uint4* __restrict__ wk, const uint4* __restrict__ wv) {
    int lane = threadIdx.x & 31;
    float xr[8], q[8], y[8], o[8];
    unpack8(xr, x[node * 32 + lane]);
    vec_mat(q, xr, wq, lane);
    for (int l = 0; l < 32; l++) {
#pragma unroll
        for (int i = 0; i < 8; i++) {
            float wr[8], p = 0.f;
            unpack8(wr, wk[(l * 8 + i) * 32 + lane]);
#pragma unroll
            for (int k = 0; k < 8; k++) p = fmaf(q[k], wr[k], p);
            for (int k = 16; k; k >>= 1) p += __shfl_xor_sync(~0u, p, k);
            if (lane == l) y[i] = p;
        }
    }
    for (int k = 0; k < 8; k++) o[k] = 0.f;
    float den = 0.f;
    for (int i0 = 0; i0 < NEE; i0 += 32) {
        unsigned m = __ballot_sync(~0u, edst[i0 + lane] == node);
        while (m) {
            int j = __ffs(m) - 1;
            m &= m - 1;
            float gq[8], p = 0.f;
            unpack8(gq, x[esrc[i0 + j] * 32 + lane]);
#pragma unroll
            for (int k = 0; k < 8; k++) p = fmaf(y[k], gq[k], p);
            for (int k = 16; k; k >>= 1) p += __shfl_xor_sync(~0u, p, k);
            float ex = __expf(p * 0.0625f);
            den += ex;
#pragma unroll
            for (int k = 0; k < 8; k++) o[k] = fmaf(ex, gq[k], o[k]);
        }
    }
    float inv = 1.f / (den + 1e-9f);
    for (int k = 0; k < 8; k++) o[k] *= inv;
    vec_mat(q, o, wv, lane);
    return make_uint4(pack2(q[0], q[1]), pack2(q[2], q[3]), pack2(q[4], q[5]), pack2(q[6], q[7]));
}

__device__ __forceinline__ unsigned hfma2(unsigned a, unsigned b, unsigned c) { unsigned r; asm("fma.rn.bf16x2 %0,%1,%2,%3;" : "=r"(r) : "r"(a), "r"(b), "r"(c)); return r; }
__device__ __forceinline__ unsigned hmul2(unsigned a, unsigned b) { unsigned r; asm("mul.rn.bf16x2 %0,%1,%2;" : "=r"(r) : "r"(a), "r"(b)); return r; }

__device__ __forceinline__ unsigned tile_addr(int n, unsigned chunk) { return sb + OFF_T + (chunk >> 3) * 10240 + n * 128 + (((chunk ^ n) & 7) << 4); }
__device__ __forceinline__ void attn_scores(float* v, bool mine, bool par, const uint4* gv, unsigned yaddr) {
    const uint4 y = ldsm4(yaddr);
    float c[4] = {0, 0, 0, 0}, e[4] = {0, 0, 0, 0};
    mma16816(c, gv[0].x, gv[0].y, gv[0].z, gv[0].w, y.x, y.y);
    mma16816(e, gv[2].x, gv[2].y, gv[2].z, gv[2].w, y.x, y.y);
    mma16816(c, gv[1].x, gv[1].y, gv[1].z, gv[1].w, y.z, y.w);
    mma16816(e, gv[3].x, gv[3].y, gv[3].z, gv[3].w, y.z, y.w);
    if (mine) { v[0] = par ? c[1] : c[0]; v[1] = par ? c[3] : c[2]; v[2] = par ? e[1] : e[0]; v[3] = par ? e[3] : e[2]; }
}
__device__ __forceinline__ void attn_softmax(const float* v, const float* u, unsigned lane, unsigned aladdr) {
    const bool hA = lane & 4, hB = lane & 8, hC = lane & 16;
    float a[4];
#pragma unroll
    for (int e = 0; e < 4; e++) a[e] = (hA ? u[e] : v[e]) + __shfl_xor_sync(~0u, hA ? v[e] : u[e], 4);
    float b0 = (hB ? a[1] : a[0]) + __shfl_xor_sync(~0u, hB ? a[0] : a[1], 9);
    float b1 = (hB ? a[3] : a[2]) + __shfl_xor_sync(~0u, hB ? a[2] : a[3], 9);
    float sc = (hC ? b1 : b0) + __shfl_xor_sync(~0u, hC ? b0 : b1, 18);
    float ex, inv;
    asm("ex2.approx.ftz.f32 %0,%1;" : "=f"(ex) : "f"(sc));
    float den = ex + __shfl_xor_sync(~0u, ex, 9);
    den += __shfl_xor_sync(~0u, den, 18);
    asm("rcp.approx.ftz.f32 %0,%1;" : "=f"(inv) : "f"(den + 1e-9f));
    sts32(aladdr, pack2(ex * inv, ex * inv));
    __syncwarp();
}
__device__ __forceinline__ void attn_mix(const uint4* gv, const uint4& a, unsigned oaddr) {
    const unsigned o0 = hfma2(a.w, gv[2].y, hfma2(a.z, gv[2].x, hfma2(a.y, gv[0].y, hmul2(a.x, gv[0].x))));
    const unsigned o1 = hfma2(a.w, gv[2].w, hfma2(a.z, gv[2].z, hfma2(a.y, gv[0].w, hmul2(a.x, gv[0].z))));
    const unsigned o2 = hfma2(a.w, gv[3].y, hfma2(a.z, gv[3].x, hfma2(a.y, gv[1].y, hmul2(a.x, gv[1].x))));
    const unsigned o3 = hfma2(a.w, gv[3].w, hfma2(a.z, gv[3].z, hfma2(a.y, gv[1].w, hmul2(a.x, gv[1].z))));
    asm volatile("stmatrix.sync.aligned.m8n8.x4.shared.b16 [%0],{%1,%2,%3,%4};" ::"r"(oaddr), "r"(o0), "r"(o1), "r"(o2), "r"(o3) : "memory");
}
__device__ __forceinline__ void pack_acc(unsigned* pk, const float* d) {
#pragma unroll
    for (int j = 0; j < 20; j++) pk[j] = pack2(d[2 * j], d[2 * j + 1]);
}
__device__ __forceinline__ void acc_to_tile(const unsigned* pk, int w, int lane) {
    const unsigned a = sb + OFF_T + (w >> 2) * 10240 + (lane >> 4) * 1024 + (lane & 7) * 128 + (((2 * (w & 3) + ((lane >> 3) & 1)) ^ (lane & 7)) << 4);
#pragma unroll
    for (int j = 0; j < 5; j++)
        asm volatile("stmatrix.sync.aligned.m8n8.x4.trans.shared.b16 [%0],{%1,%2,%3,%4};" ::"r"(a + j * 2048), "r"(pk[4 * j]), "r"(pk[4 * j + 1]), "r"(pk[4 * j + 2]), "r"(pk[4 * j + 3]) : "memory");
}
__device__ __forceinline__ unsigned movm(unsigned a) { unsigned d; asm volatile("movmatrix.sync.aligned.m8n8.trans.b16 %0,%1;" : "=r"(d) : "r"(a)); return d; }
__device__ __forceinline__ void tma_load2d(unsigned dst, const CUtensorMap* tm, int c0, int c1, unsigned bar) {
    asm volatile("cp.async.bulk.tensor.2d.shared::cluster.global.mbarrier::complete_tx::bytes [%0],[%1,{%3,%4}],[%2];"
                 ::"r"(dst), "l"(tm), "r"(bar), "r"(c0), "r"(c1) : "memory");
}
__device__ __forceinline__ void tma_load3d(unsigned dst, const CUtensorMap* tm, int row, unsigned bar) {
    asm volatile("cp.async.bulk.tensor.3d.shared::cluster.global.mbarrier::complete_tx::bytes [%0],[%1,{%4,%3,%4}],[%2];"
                 ::"r"(dst), "l"(tm), "r"(bar), "r"(row), "r"(0) : "memory");
}
__device__ __forceinline__ void cp16(unsigned dst, const void* src) { asm volatile("cp.async.cg.shared.global [%0],[%1],16;" ::"r"(dst), "l"(src) : "memory"); }
__device__ __forceinline__ void cp_commit() { asm volatile("cp.async.commit_group;" ::: "memory"); }
template <int N> __device__ __forceinline__ void cp_wait() { asm volatile("cp.async.wait_group %0;" ::"n"(N) : "memory"); }
__device__ __forceinline__ void nb_sync_id(int id, int n) { asm volatile("bar.sync %0,%1;" ::"r"(id), "r"(n) : "memory"); }
__device__ __forceinline__ void nb_arrive_id(int id, int n) { asm volatile("bar.arrive %0,%1;" ::"r"(id), "r"(n) : "memory"); }
template <int ID, int N> __device__ __forceinline__ void nb_sync() { asm volatile("bar.sync %0,%1;" ::"n"(ID), "n"(N) : "memory"); }
template <int ID, int N> __device__ __forceinline__ void nb_arrive() { asm volatile("bar.arrive %0,%1;" ::"n"(ID), "n"(N) : "memory"); }
__device__ __forceinline__ void mbar_init(unsigned a, int n) { asm volatile("mbarrier.init.shared.b64 [%0],%1;" ::"r"(a), "r"(n) : "memory"); }
__device__ __forceinline__ void mbar_expect(unsigned a, int n) { asm volatile("mbarrier.arrive.expect_tx.shared.b64 _,[%0],%1;" ::"r"(a), "r"(n) : "memory"); }
__device__ __forceinline__ void mbar_arrive(unsigned a) { asm volatile("mbarrier.arrive.shared.b64 _,[%0];" ::"r"(a) : "memory"); }

constexpr unsigned PADBIN = 2560, CU = 0x101;
__device__ __noinline__ void push_overflow(Scratch* sc, unsigned dst, unsigned src) {
    sc->ovf[blockIdx.x * OVCAP + atoms_inc(sb + OFF_MISC)] = (dst << 14) | src;
}
__device__ __noinline__ void bin_overflow(Scratch* sc, unsigned mask, unsigned ht) {
    for (int i = 0; i < 24 + 6 * 16; i++) {
        unsigned e;
        if (i < 24) {
            if (!(mask >> i & 1)) continue;
            e = lds32(sb + OFF_MAIL + (ht + (i >> 2) * 96) * 16 + (i & 3) * 4) & 0x7FFFFFFFu;
        } else {
            const int k = (i - 24) >> 4;
            if (!(mask >> (24 + k) & 1)) continue;
            e = __ldcg((const unsigned*)(sc->mail + ((NT + blockIdx.x) * 512 + ((ht + k * 96) & ~3u))) + ((i - 24) & 15));
        }
        if (e < (PADBIN << 16))
            push_overflow(sc, blockIdx.x * TILE + ((e >> 21) & ~3u) + ((e >> 18) & 3), ((e & 2047) << 3) | ((e >> 20) & 7));
    }
}
__device__ __forceinline__ void place(unsigned e, unsigned h) {
    asm volatile("{.reg .pred p; setp.lt.u32 p,%2,%3; @p st.shared.u16 [%0],%1;}"
                 ::"r"(sb + OFF_IMG + bitsel(h >> 1, e >> 16, 0x318E)), "h"((unsigned short)e), "r"(h), "n"((LCAP + 16) * CU) : "memory");
}
__device__ __forceinline__ void bulk_s2g(void* dst, unsigned src, unsigned bytes) {
    asm volatile("cp.async.bulk.global.shared::cta.bulk_group [%0],[%1],%2;" ::"l"(dst), "r"(src), "r"(bytes) : "memory");
}
__device__ __forceinline__ void tma_reduce(const CUtensorMap* tm, unsigned src, int c0, int c1) {
    asm volatile("cp.reduce.async.bulk.tensor.2d.global.shared::cta.add.tile.bulk_group [%0,{%2,%3}],[%1];" ::"l"(tm), "r"(src), "r"(c0), "r"(c1) : "memory");
}
#define EV(id) nb_arrive<id, 544>()
#define WAIT_EV(id) do { __syncwarp(); nb_sync<id, 544>(); } while (0)

__global__ void __launch_bounds__(640, 1)
exphormer_kernel(const uint4* __restrict__ x, const uint4* __restrict__ dst4, const uint4* __restrict__ src4,
                 const uint4* __restrict__ wq, const uint4* __restrict__ wk, const int* __restrict__ esrc,
                 const int* __restrict__ edst, Scratch* __restrict__ sc, const uint4* __restrict__ dis, const uint4* __restrict__ wv,
                 const __grid_constant__ CUtensorMap tm_x, const __grid_constant__ CUtensorMap tm_wl, const __grid_constant__ CUtensorMap tm_wv,
                 const __grid_constant__ CUtensorMap tm_mail, const __grid_constant__ CUtensorMap tm_ot, const __grid_constant__ CUtensorMap tm_o256, const __grid_constant__ CUtensorMap tm_o16) {
    extern __shared__ __align__(1024) unsigned char smem_raw[];
    const unsigned tid = threadIdx.x, lane = tid & 31, g = lane >> 2, t = lane & 3;
    const unsigned b = blockIdx.x;
    const bool rowcta = b < NT;
    const int slice = b >> 2, range = b & 3;
    const int g0 = (range * NG) >> 2, g1 = ((range + 1) * NG) >> 2;
    STAMP(0);

    if (tid >= 512) {
    asm volatile("setmaxnreg.dec.sync.aligned.u32 %0;" ::"n"(REG_H));
    if (tid >= 544) {
        const unsigned ht = tid - 544;
        if (ht < 32) {
            nb_sync<13, 160>();
            nb_sync<2, 352>();
            if (rowcta) {
                const uint4 c = lds128(sb + OFF_CNT1 + lane * 16);
                const unsigned cc[4] = {c.x, c.y, c.z, c.w};
#pragma unroll
                for (int i = 0; i < 4; i++)
                    if (cc[i] > 16) asm volatile("red.shared.or.b32 [%0],0x80000000;" ::"r"(sb + OFF_MAIL + (lane * 4 + i) * 64 + 60) : "memory");
                fence_async_smem();
                __syncwarp();
                if (elect())
                    asm volatile("cp.async.bulk.tensor.2d.global.shared::cta.bulk_group [%0,{%2,%3}],[%1];" ::"l"(&tm_mail), "r"(sb + OFF_MAIL), "r"(b * 16), "r"(0) : "memory");
                for (int i = 0; i < 4; i++)
                    if (lds32(sb + OFF_CNT1 + lane * 16 + i * 4) > 16) bulk_s2g(sc->mail + ((NT + lane * 4 + i) * 512 + b * 4), sb + OFF_IMG + (lane * 4 + i) * 64, 64);
                asm volatile("cp.async.bulk.commit_group;" ::: "memory");
                asm volatile("cp.async.bulk.wait_group 0;" ::: "memory");
                fence_async_gmem();
                __syncwarp();
            }
            if (rowcta) nb_arrive<1, 96>();
            if (elect()) {
                bar_arrive_relaxed(&sc->bar[0]);
                STAMPT(544, 47);
                if (rowcta) {
                    bar_poll(sc, 0);
                    fence_async_gmem();
                    mbar_expect(bar_mail, 8000);
                    bulk_g2s(sb + OFF_MAIL, sc->mail + b * 512, 8000, bar_mail);
                    if (GATE2) mbar_arrive(bar_go);
                }
            }
            __syncwarp();
        } else if (ht < 64) {
            const unsigned fw = b >> 3, hq = b & 7;
            uint4* mo = sc->mimg + ((fw >> 2) * 2048 + (hq >> 1) * 512 + (16 * (fw & 3) + (lane & 15)) * 8 + ((hq * 4 ^ lane) & 4));
            nb_sync<14, 192>();
            if (lane < 16) bulk_s2g(mo, sb + OFF_MAIL + 8000 + lane * 64, 64);
            asm volatile("cp.async.bulk.commit_group;" ::: "memory");
            asm volatile("cp.async.bulk.wait_group 0;" ::: "memory");
            fence_async_gmem();
            __syncwarp();
            if (lane == 0) bar_arrive_relaxed(&sc->bar[3 * 64]);
            __syncwarp();
            STAMPT(576, 46);
        } else {
            if (lane < 5) {
                unsigned epoch;
                asm volatile("ld.relaxed.gpu.global.u32 %0,[%1];" : "=r"(epoch) : "l"(&sc->bar[lane * 64]) : "memory");
                sts32(sb + OFF_MISC + 32 + lane * 4, (epoch & ~(NCTA - 1)) + NCTA);
            }
            __syncwarp();
            nb_arrive<14, 192>();
            nb_arrive<15, 64>();
            nb_arrive<13, 160>();
        }
        if (rowcta) {
            if (ht >= 32) {
                nb_sync<1, 96>();
                const unsigned pad = (PADBIN + 4 * lane) << 16, h2 = ht - 32;
                sts128(sb + OFF_MAIL + 8000 + h2 * 16, make_uint4(pad, pad, pad, pad));
                if (h2 < 12) sts128(sb + OFF_MAIL + 9024 + h2 * 16, make_uint4(pad, pad, pad, pad));
#pragma unroll
                for (int k = 0; k < 9; k++) if (k % 3 < 2 || h2 < 32) sts128(sb + OFF_IMG + (k / 3) * 4096 + (k % 3) * 1024 + h2 * 16, make_uint4(DUMMY2, DUMMY2, DUMMY2, DUMMY2));
            }
            nb_sync<13, 96>();
            mbar_wait(bar_mail);
            STAMPT(576, 16);
            uint4 e[6], h[6];
            unsigned flagged = 0, late = 0, longg = 0;
#pragma unroll
            for (int k = 0; k < 6; k++) e[k] = lds128(sb + OFF_MAIL + (ht + k * 96) * 16);
#pragma unroll
            for (int k = 0; k < 6; k++) { flagged |= (e[k].w >> 31) << k; e[k].w &= 0x7FFFFFFFu; }
            while (flagged) {
                const unsigned f = __ffs(flagged) - 1, k = atoms_add(sb + OFF_MISC + 4, 4);
                const uint4* sp = sc->mail + ((NT + b) * 512 + ((ht + f * 96) & ~3u));
                flagged &= flagged - 1;
                if (k < 76) {
#pragma unroll
                    for (int j = 0; j < 4; j++) cp16(sb + OFF_MAIL + 8000 + (k + j) * 16, sp + j);
                } else {
                    late |= 1u << (24 + f);
                }
            }
            cp_commit();
            __syncwarp();
#pragma unroll
            for (int k = 0; k < 6; k++) {
                if (k == 5) { cp_wait<0>(); nb_sync<1, 96>(); if (ht >= 20) e[5] = lds128(sb + OFF_MAIL + (ht + 480) * 16); }
                h[k] = make_uint4(atoms_add(sb + OFF_CNT2 + (e[k].x >> 16), CU), atoms_add(sb + OFF_CNT2 + (e[k].y >> 16), CU),
                                  atoms_add(sb + OFF_CNT2 + (e[k].z >> 16), CU), atoms_add(sb + OFF_CNT2 + (e[k].w >> 16), CU));
            }
            nb_sync<1, 96>();
            STAMPT(576, 17);
            for (unsigned G = ht >> 5; G < 5; G += 3) {
                const unsigned ca = sb + OFF_CNT2 + G * 512 + lane * 16;
                const uint4 c = lds128(ca);
                const unsigned dp = hmul2(lds32(sb + OFF_DIS + (G * 8 + g) * 4), 0x43004300u);
                const bool sw = lane >= 16;
                unsigned s1 = sw ? c.y : c.x, s2 = c.x + c.y, s3 = s2 + (sw ? c.w : c.z), tot = s2 + c.z + c.w, inc = tot;
                unsigned u = __shfl_up_sync(~0u, inc, 8); if (lane >= 8) inc += u;
                u = __shfl_up_sync(~0u, inc, 16); if (sw) inc += u;
                const unsigned base = inc - tot;
                const unsigned p0 = min(base, LCAP * CU), p1 = min(base + s1, LCAP * CU), p2 = min(base + s2, LCAP * CU), p3 = min(base + s3, LCAP * CU);
                sts128(ca, make_uint4((sw ? p1 : p0) + 16 * CU, (sw ? p0 : p1) + 16 * CU, (sw ? p3 : p2) + 16 * CU, (sw ? p2 : p3) + 16 * CU));
                const unsigned word = __byte_perm(__byte_perm(p0, p1, 0x0040), __byte_perm(p2, p3, 0x0040), 0x5410);
                const unsigned wa = __shfl_sync(~0u, word, (g >> 1) * 8 + 2 * t), wb = __shfl_sync(~0u, word, (g >> 1) * 8 + 2 * t + 1);
                const unsigned hdr = __byte_perm(wa, wb, (g & 1) ? 0x7362 : 0x5140);
                if (__any_sync(~0u, inc > 48 * CU)) longg |= 1u << G;
                asm volatile("st.shared.v2.u32 [%0],{%1,%2};" ::"r"(sb + OFF_IMG + G * 512 + lane * 16), "r"(hdr), "r"(__byte_perm(dp, dp, sw ? 0x1032 : 0x3210)) : "memory");
            }
            nb_sync<1, 96>();
            int hmax = 0;
#pragma unroll
            for (int k0 = 0; k0 < 6; k0 += 3) {
#pragma unroll
                for (int k = k0; k < k0 + 3; k++) { e[k] = lds128(sb + OFF_MAIL + (ht + k * 96) * 16); e[k].w &= 0x7FFFFFFFu; }
#pragma unroll
                for (int k = k0; k < k0 + 3; k++) {
                    h[k].x += lds32(sb + OFF_CNT2 + (e[k].x >> 16)); h[k].y += lds32(sb + OFF_CNT2 + (e[k].y >> 16));
                    h[k].z += lds32(sb + OFF_CNT2 + (e[k].z >> 16)); h[k].w += lds32(sb + OFF_CNT2 + (e[k].w >> 16));
                }
#pragma unroll
                for (int k = k0; k < k0 + 3; k++) {
                    place(e[k].x, h[k].x); place(e[k].y, h[k].y); place(e[k].z, h[k].z); place(e[k].w, h[k].w);
                    hmax = max(hmax, max(max((int)h[k].x, (int)h[k].y), max((int)h[k].z, (int)h[k].w)));
                }
            }
            if (__builtin_expect(hmax >= (int)((LCAP + 16) * CU), 0)) {
#pragma unroll
                for (int k = 0; k < 6; k++)
                    late |= ((h[k].x >= (LCAP + 16) * CU) | (h[k].y >= (LCAP + 16) * CU) << 1 | (h[k].z >= (LCAP + 16) * CU) << 2 | (h[k].w >= (LCAP + 16) * CU) << 3) << (4 * k);
            }
            if (__builtin_expect(late, 0)) bin_overflow(sc, late, ht);
            if (longg && lane == 0) asm volatile("red.shared.or.b32 [%0],%1;" ::"r"(sb + OFF_MISC + 8), "r"(longg) : "memory");
            nb_sync<1, 96>();
            if (ht < 5 && (lds32(sb + OFF_MISC + 8) >> ht & 1))
                asm volatile("red.shared.or.b32 [%0],0x80000000;" ::"r"(sb + OFF_IMG + 4096 + ht * 512 + 12) : "memory");
            fence_async_smem();
            __syncwarp();
            STAMPT(576, 18);
        }
        if (ht < 32 && elect()) {
            if (rowcta) {
                for (int c = 0; c < 3; c++) bulk_s2g(sc->lists + (c * LSTR + b * 160), sb + OFF_IMG + c * 4096, 2560);
                asm volatile("cp.async.bulk.commit_group;" ::: "memory");
                const unsigned novf = lds32(sb + OFF_MISC), bad = lds32(sb + OFF_MISC + 20);
                if (__builtin_expect(novf | bad, 0)) {
                    sc->ovfn[b] = make_uint2(lds32(sb + OFF_MISC + 48), novf);
                    raise_flag(&sc->bar[4 * 64 + 1], lds32(sb + OFF_MISC + 48), (novf ? 1 : 0) | (bad ? 2 : 0));
                    __threadfence();
                }
                asm volatile("cp.async.bulk.wait_group 0;" ::: "memory");
                fence_async_gmem();
            }
            bar_arrive_relaxed(&sc->bar[4 * 64]);
            STAMPT(544, 19);
            sts32(sb + OFF_MISC + 28, bar_poll2(&sc->bar[4 * 64], lds32(sb + OFF_MISC + 48)));
            mbar_arrive(bar_c);
            STAMPT(544, 23);
        }
    } else {
        const bool one = elect();
        auto load_xl = [&](int i) {
            mbar_expect(bar_full + 8 * i, 32768 + 10240);
            tma_load2d(sb + OFF_T + i * 10240, &tm_x, i * 64, b * TILE, bar_full + 8 * i);
            tma_load3d(sb + OFF_S + i * 32768, &tm_wl, i * 64, bar_full + 8 * i);
        };
        auto load_m = [&](int i, int slot) {
            mbar_expect(bar_full + 32 + 8 * i, 32768);
            bulk_g2s(sb + OFF_S + slot * 32768, sc->mimg + i * 2048, 32768, bar_full + 32 + 8 * i);
        };
        auto load_v = [&](int i, int slot) {
            mbar_expect(bar_full + 64 + 8 * i, 32768);
            tma_load3d(sb + OFF_S + slot * 32768, &tm_wv, i * 64, bar_full + 64 + 8 * i);
        };
        const char* hsl = (const char*)(sc->hs + slice * NN);
        auto fill = [&](int slot) { bulk_g2s(sb + OFF_S + slot * 32768, hsl + slot * 32768, slot == 4 ? NN * 16 - 4 * 32768 : 32768, bar_fill); };
        const unsigned t0 = clock();
        if (one) {
            for (int i = 0; i < 2; i++) mbar_init(bar_full + 8 * i, 1);
            asm volatile("fence.mbarrier_init.release.cluster;" ::: "memory");
            while ((unsigned)clock() - t0 < XD0) {}
            if (rowcta) load_xl(0);
            STAMPT(512, 41);
            for (int i = 2; i < 12; i++) mbar_init(bar_full + 8 * i, 1);
            mbar_init(bar_go, 1 + GATE2);
            for (int i = 0; i < 4; i++) mbar_init(bar_fill + 8 * i, 1);
            for (int i = 0; i < 10; i++) mbar_init(bar_rd + 8 * i, i < 9 ? 16 : g1 - g0 - 144);
            asm volatile("fence.mbarrier_init.release.cluster;" ::: "memory");
            if ((unsigned)__cvta_generic_to_shared(smem_raw) != sb) __trap();
            mbar_expect(bar_fill, NN * 16);
        }
        __syncwarp();
        nb_arrive<3, 544>();
        nb_arrive<13, 160>();
        if (one && rowcta) {
            while ((unsigned)clock() - t0 < XD1) {}
            load_xl(1);
            STAMPT(512, 40);
        }
        __syncwarp();
        nb_sync<15, 64>();
        if (rowcta) {
            if (one) {
                if (XD2) { while ((unsigned)clock() - t0 < XD2 + 1) {} } else mbar_wait(bar_full);
                load_xl(2);
                STAMPT(512, 52);
                mbar_wait(bar_full + (XD2 ? 0 : 8)); load_xl(3);
                STAMPT(512, 53);
                asm volatile("cp.async.bulk.prefetch.L2.global [%0],%1;" ::"l"(wv + b * 64), "r"(b == NT - 1 ? 4096 : 1024) : "memory");
                asm volatile("prefetch.tensormap [%0];" ::"l"(&tm_wv) : "memory");
                bar_poll(sc, 3);
                STAMPT(512, 48);
                fence_async_gmem();
            }
            WAIT_EV(5); if (one) { load_m(0, 0); load_m(1, 1); mbar_arrive(bar_go); }
            WAIT_EV(6); if (one) load_m(2, 3);
            WAIT_EV(7); if (one) load_m(3, 0);
            WAIT_EV(12); if (one) bar_arrive(&sc->bar[2 * 64]);
            STAMPT(512, 24);
            WAIT_EV(14); if (one) { fence_async_smem(); load_v(0, 4); load_v(1, 2); }
            WAIT_EV(15);
            if (one) {
                fence_async_smem();
                load_v(2, 1); load_v(3, 3);
                bar_poll(sc, 2);
                fence_async_gmem();
            }
            STAMPT(512, 25);
            WAIT_EV(2); if (one) fill(0);
            WAIT_EV(4); if (one) fill(4);
            WAIT_EV(5); if (one) fill(2);
            WAIT_EV(6); if (one) fill(1);
            WAIT_EV(7); if (one) fill(3);
            WAIT_EV(12);
            if (one) {
#pragma unroll
                for (int kb = 0; kb < 4; kb++)
                    asm volatile("cp.async.bulk.tensor.2d.global.shared::cta.bulk_group [%0,{%2,%3}],[%1];"
                                 ::"l"(&tm_ot), "r"(sb + OFF_T + kb * 10240), "r"(kb * 64), "r"(b * TILE) : "memory");
                asm volatile("cp.async.bulk.commit_group;" ::: "memory");
                asm volatile("cp.async.bulk.wait_group 0;" ::: "memory");
                fence_async_gmem();
            }
        } else {
            if (one) {
                bar_arrive(&sc->bar[2 * 64]);
                bar_poll(sc, 2);
                fence_async_gmem(); fence_async_smem();
                for (int i = 0; i < 5; i++) fill(i);
            }
        }
        if (one) {
            bar_arrive_relaxed(&sc->bar[1 * 64]);
            mbar_arrive(bar_t);
            STAMPT(512, 26);
            bar_poll(sc, 1);
            fence_async_gmem();
            STAMPT(512, 27);
            for (int r = 0; r < 9; r++) {
                mbar_wait(bar_rd + 8 * r);
                fence_async_smem();
                tma_reduce(&tm_o256, sb + OFF_STG + r * 4096, slice * 8, (g0 + 16 * r) * 16);
            }
            mbar_wait(bar_rd + 72);
            fence_async_smem();
            for (int i = 144; i < g1 - g0; i++) tma_reduce(&tm_o16, sb + OFF_STG + i * 256, slice * 8, (g0 + i) * 16);
            asm volatile("cp.async.bulk.commit_group;" ::: "memory");
            asm volatile("cp.async.bulk.wait_group.read 0;" ::: "memory");
            STAMPT(512, 13);
        }
    }
    } else {
    if (tid < 32) {
        unsigned bad = 0;
        uint4 xd[3];
#pragma unroll
        for (int k = 0; k < 3; k++) xd[k] = ldg_na((const uint4*)edst + min(b * TILE + k * 32 + lane, NN - 1u));
#pragma unroll
        for (int k = 0; k < 3; k++) { const unsigned n = min(b * TILE + k * 32 + lane, NN - 1u); bad |= (xd[k].x ^ n) | (xd[k].y ^ n) | (xd[k].z ^ n) | (xd[k].w ^ n); }
        bad = __any_sync(~0u, bad);
        if (lane == 0) sts32(sb + OFF_MISC + 20, bad);
        __syncwarp();
        nb_arrive<13, 160>();
    } else if (tid < 64) {
        const uint4* ep = (const uint4*)esrc + (min(b, NT - 1u) * TILE + lane);
        cp16(sb + OFF_EIDX + lane * 16, ep); cp16(sb + OFF_EIDX + 512 + lane * 16, ep + 32);
        if (lane < 16) cp16(sb + OFF_EIDX + 1024 + lane * 16, ep + 64);
        if (lane < 10) cp16(sb + OFF_DIS + lane * 16, dis + (min(b, NT - 1u) * 10 + lane));
        cp_commit();
        cp_wait<0>();
        nb_arrive<13, 160>();
    } else if (tid >= 192) {
        if (rowcta) {
            const unsigned bt = tid - 192;
            const uint4 ed = ldg_na(dst4 + (b * 320 + bt)), es = ldg_na(src4 + (b * 320 + bt));
            const unsigned pad = (PADBIN + 4 * ((bt & 3) + ((b * 4) & 28))) << 16;
#pragma unroll
            for (int k = 0; k < 4; k++) if ((k & 1) == 0 || bt < 180) sts128(sb + OFF_MAIL + (k >> 1) * 9216 + (bt + (k & 1) * 320) * 16, make_uint4(pad, pad, pad, pad));
            const unsigned cz = bt < (512 + PADBIN) / 16 ? 0 : 0x40000000;
            if (bt < (512 + 2688) / 16) sts128(sb + OFF_CNT1 + bt * 16, make_uint4(cz, cz, cz, cz));
            if (bt == 319) sts128(sb + OFF_MISC, make_uint4(0, 0, 0, 0));
            unsigned z;
            asm volatile("{.reg .pred p; setp.eq.u32 p,%1,0xFFFFFFFF; bar.red.popc.u32 %0,4,320,p;}" : "=r"(z) : "r"(bt) : "memory");
            const unsigned dd[4] = {ed.x + z, ed.y + z, ed.z + z, ed.w + z}, ss[4] = {es.x + z, es.y + z, es.z + z, es.w + z};
            unsigned rk[4], ow[4];
#pragma unroll
            for (int i = 0; i < 4; i++) { ow[i] = dd[i] / TILE; rk[i] = atoms_inc(sb + OFF_CNT1 + ow[i] * 4); }
#pragma unroll
            for (int i = 0; i < 4; i++) {
                const unsigned dl = dd[i] - ow[i] * TILE;
                const unsigned e = bitsel(ss[i] << 20, bitsel(dl << 21, dl << 18, 0xFF800000u), 0x00700000u) + (ss[i] >> 3);
                asm volatile("{.reg .pred p; setp.lt.u32 p,%2,%3; @p st.shared.u32 [%0],%1;}" ::"r"(sb + OFF_MAIL + ow[i] * 64 + rk[i] * 4 + (rk[i] >> 4) * (9216 - 64)), "r"(e), "r"(rk[i]), "n"(CELL) : "memory");
            }
            if (__builtin_expect((rk[0] | rk[1] | rk[2] | rk[3]) >= CELL, 0)) {
#pragma unroll
                for (int i = 0; i < 4; i++) if (rk[i] >= CELL) push_overflow(sc, dd[i], ss[i]);
            }
        }
        STAMPT(416, 44);
        nb_arrive<2, 352>();
    } else {
        const unsigned fw = b >> 3, hq = b & 7, q = (tid >> 5) - 2;
        const unsigned ma = sb + OFF_S + 4 * 32768 + 8192 + q * 6144;
        {
            const unsigned r = lane >> 3, da = ma + r * 128 + (((lane ^ r) & 7) << 4);
            const uint4* pa = wq + ((16 * fw + r) * 32 + q * 8 + (lane & 7));
            const uint4* pb = wk + ((32 * hq + r) * 32 + q * 8 + (lane & 7));
#pragma unroll
            for (int u = 0; u < 12; u++) cp16((da ^ ((u & 1) << 6)) + u * 512, u < 4 ? pa + u * 128 : pb + (u - 4) * 128);
            cp_commit();
        }
        const unsigned aa = ma + (lane & 15) * 128 + ((((lane >> 4) ^ lane) & 7) << 4);
        const unsigned br = 4 * ((lane & 7) >> 1) + 2 * (lane >> 4) + (lane & 1);
        const unsigned ba = ma + 2048 + br * 128 + (((((lane >> 3) & 1) ^ br) & 7) << 4);
        float c[4][4];
#pragma unroll
        for (int u = 0; u < 4; u++) c[u][0] = c[u][1] = c[u][2] = c[u][3] = 0.f;
        STAMPT(64, 38);
        cp_wait<0>();
        __syncwarp();
        STAMPT(64, 39);
#pragma unroll
        for (int k = 0; k < 4; k++) {
            const uint4 a = ldsm4(aa ^ (k << 5)), b0 = ldsm4(ba ^ (k << 5)), b1 = ldsm4((ba ^ (k << 5)) + 2048);
            mma16816(c[0], a.x, a.y, a.z, a.w, b0.x, b0.y); mma16816(c[1], a.x, a.y, a.z, a.w, b0.z, b0.w);
            mma16816(c[2], a.x, a.y, a.z, a.w, b1.x, b1.y); mma16816(c[3], a.x, a.y, a.z, a.w, b1.z, b1.w);
        }
        const unsigned ra = sb + OFF_S + 4 * 32768 + lane * 16;
#pragma unroll
        for (int i = 0; i < 4; i++)
            sts128(ra + q * 2048 + i * 512, make_uint4(__float_as_uint(c[2 * (i & 1)][2 * (i >> 1)]), __float_as_uint(c[2 * (i & 1)][2 * (i >> 1) + 1]),
                                                       __float_as_uint(c[2 * (i & 1) + 1][2 * (i >> 1)]), __float_as_uint(c[2 * (i & 1) + 1][2 * (i >> 1) + 1])));
        STAMPT(64, 42);
        nb_sync<8, 128>();
        float m[4] = {0, 0, 0, 0};
#pragma unroll
        for (int i = 0; i < 4; i++) {
            const uint4 u = lds128(ra + i * 2048 + q * 512);
            m[0] += __uint_as_float(u.x); m[1] += __uint_as_float(u.y); m[2] += __uint_as_float(u.z); m[3] += __uint_as_float(u.w);
        }
        const float k = 0.0625f * 1.4426950408889634f;
        asm volatile("st.shared.v2.u32 [%0],{%1,%2};" ::"r"(sb + OFF_MAIL + 8000 + (8 * (q >> 1) + g) * 64 + ((((q & 1) * 2 + (t >> 1)) ^ g) & 3) * 16 + (t & 1) * 8),
                     "r"(pack2(m[0] * k, m[1] * k)), "r"(pack2(m[2] * k, m[3] * k)) : "memory");
        fence_async_smem();
        STAMPT(64, 43);
        nb_arrive<14, 192>();
    }
    asm volatile("setmaxnreg.inc.sync.aligned.u32 %0;" ::"n"(REG_W));
    const int w = __shfl_sync(~0u, tid >> 5, 0), wg = w >> 2;
    const int grp0 = g0 + w;
    const uint4* lp = sc->lists + (grp0 * 32 + lane);
    uint4 L0, L1;
    nb_sync<3, 544>();

    if (__builtin_expect(rowcta, 1)) {
        const unsigned descA = 0x10000u + (sb + OFF_S) / 16 + wg * 512;
        const unsigned greg = sb + OFF_S + w * 2048 + lane * 16;
        float d[40];
        unsigned pk[20];
        unsigned* hp = (unsigned*)(sc->hs + (2 * w * NN + b * TILE)) + lane;
        auto mma_k = [&](int Q, int slot, int st, int k0, int k1) {
            if (st < 0) wg_fence();
#pragma unroll
            for (int k = k0; k < k1; k++) {
                if (st >= 0) wg_fence();
                wg80(d, descA + slot * 2048 + k * 128, 0x10000u + (sb + OFF_T) / 16 + (Q & 3) * 640 + k * 2, ((Q & 3) | k) != 0);
                if (st >= 0) {
#pragma unroll
                    for (int j = st + k; j < st + k + 1; j++)
                        if (j < 20) asm volatile("st.global.u32 [%0],%1;" ::"l"(hp + (j >> 1) * 32 + (j & 1) * (NN * 4)), "r"(pk[j]) : "memory");
                }
            }
            wg_commit();
        };
        auto mma_q = [&](int Q, int slot, int st) { mma_k(Q, slot, st, 0, 4); };
        auto mma_head = [&](int Q, int slot, int st) { mma_k(Q, slot, st, 0, KH); wg_wait<1>(); };
        auto mma_tail = [&](int Q, int slot, int st) { mma_k(Q, slot, st, KH, 4); };
        const uint4* xl = x + lane;
        auto eidx = [&](int i) { return lds128(sb + OFF_EIDX + (w * 5 + i) * 16); };
        auto gather = [&](const uint4& ix, int slot) {
            cp16(greg + slot * 32768, xl + ix.x * 32u); cp16(greg + slot * 32768 + 512, xl + ix.y * 32u);
            cp16(greg + slot * 32768 + 1024, xl + ix.z * 32u); cp16(greg + slot * 32768 + 1536, xl + ix.w * 32u);
            cp_commit();
        };
        const uint4 ix0 = eidx(0), ix1 = eidx(1), ix2 = eidx(2), ix3 = eidx(3), ix4 = eidx(4);
        uint4 gv[5][4];
        const unsigned gld = sb + OFF_S + w * 2048 + ((lane >> 3) & 1) * 512 + (lane >> 4) * 128 + (lane & 7) * 16;
        auto to_regs = [&](int i, int slot) {
            __syncwarp();
#pragma unroll
            for (int j = 0; j < 4; j++) gv[i][j] = ldsm4(gld + slot * 32768 + (j & 1) * 256 + (j >> 1) * 1024);
        };
        float ds[20];
#pragma unroll
        for (int j = 0; j < 10; j++) { const unsigned v = lds32(sb + OFF_DIS + (4 * j + t) * 4); ds[2 * j] = blo_v(v); ds[2 * j + 1] = bhi_v(v); }
        STAMPT(288, 2);
        mbar_wait(bar_full);
        STAMPT(288, 3);
        mma_q(0, 0, -1);
        mbar_wait(bar_full + 8);
        STAMPT(288, 50);
        mma_q(1, 1, -1);
        mbar_wait(bar_full + 16);
        STAMPT(288, 51);
        mma_head(2, 2, -1);
        EV(5);
        mma_tail(2, 2, -1);
        mbar_wait(bar_full + 24);
        STAMP(5);
        mbar_wait(bar_go);
        gather(ix0, 4);
        mma_q(3, 3, -1);
        wg_wait<0>();
        EV(6);
        STAMP(6);
#pragma unroll
        for (int j = 0; j < 20; j++) pk[j] = movm(pack2(d[2 * j] * ds[2 * (j >> 1)], d[2 * j + 1] * ds[2 * (j >> 1) + 1]));
#pragma unroll
        for (int j = 0; j < STPRE; j++) asm volatile("st.global.u32 [%0],%1;" ::"l"(hp + (j >> 1) * 32 + (j & 1) * (NN * 4)), "r"(pk[j]) : "memory");
        STAMP(7);
        nb_sync_id(8 + wg, 128);
        if (G1POS == 0) gather(ix1, 2);
        mbar_wait(bar_full + 32);
        if (G1POS == 1) gather(ix1, 2);
        STAMP(21);
        mma_q(4, 0, STPRE);
        STAMP(28);
        mbar_wait(bar_full + 40);
        mma_head(5, 1, STPRE + 4);
        EV(7);
        mma_tail(5, 1, STPRE + 4);
        STAMP(29);
        mbar_wait(bar_full + 48);
        STAMP(30);
        mma_head(6, 3, STPRE + 8);
        nb_sync_id(8 + wg, 128);
        gather(ix2, 1);
        mma_tail(6, 3, STPRE + 8);
        STAMP(31);
        mbar_wait(bar_full + 56);
        STAMP(32);
        mma_head(7, 0, STPRE + 12);
        nb_sync_id(8 + wg, 128);
        gather(ix3, 3);
        mma_tail(7, 0, STPRE + 12);
        EV(12);
        wg_wait<0>();
        STAMP(20);
        pack_acc(pk, d);
        nb_sync<0, 512>();
        acc_to_tile(pk, w, lane);
        gather(ix4, 0);
        cp_wait<3>();
        to_regs(0, 4);
        nb_sync<0, 512>();
        STAMP(8);
        {
            const unsigned delta = t ^ (g >> 1), alsm = sb + OFF_ALPHA + w * 128;
            const bool par = g & 1;
            unsigned ta[5];
#pragma unroll
            for (int i = 0; i < 5; i++) ta[i] = tile_addr(w * 5 + i, lane);
            float v[4], u[4];
            to_regs(1, 2);
            EV(14);
            attn_scores(v, true, par, gv[0], ta[0]);
            attn_scores(v, delta == 1, par, gv[1], ta[1] ^ 32);
            cp_wait<2>();
            to_regs(2, 1);
            attn_scores(v, delta == 2, par, gv[2], ta[2] ^ 64);
            STAMP(33);
            cp_wait<1>();
            to_regs(3, 3);
            EV(15);
            STAMP(34);
            attn_scores(v, delta == 3, par, gv[3], ta[3] ^ 96);
            cp_wait<0>();
            to_regs(4, 0);
            STAMP(35);
            attn_scores(u, true, par, gv[4], ta[4]);
            attn_softmax(v, u, lane, alsm + ((lane & 4) + delta) * 16 + (lane >> 3) * 4);
            STAMP(49);
            uint4 al = lds128(alsm);
#pragma unroll
            for (int i = 0; i < 5; i++) {
                const uint4 a = al;
                if (i < 4) al = lds128(alsm + (i + 1) * 16);
                attn_mix(gv[i], a, ta[i]);
            }
        }
        STAMP(36);
        mbar_wait(bar_full + 64);
        STAMP(37);
        fence_async_smem();
        STAMP(22);
        EV(2);
        nb_sync<0, 512>();
        mma_q(8, 4, -1);
        mbar_wait(bar_full + 72);
        mma_head(9, 2, -1);
        EV(4);
        mma_tail(9, 2, -1);
        mbar_wait(bar_full + 80);
        mma_head(10, 1, -1);
        EV(5);
        mma_tail(10, 1, -1);
        mbar_wait(bar_full + 88);
        mma_head(11, 3, -1);
        EV(6);
        mma_tail(11, 3, -1);
        wg_wait<0>();
        EV(7);
        STAMP(9);
        pack_acc(pk, d);
        mbar_wait(bar_c);
        L0 = ldg_na(lp); L1 = ldg_na(lp + LSTR);
        nb_sync<0, 512>();
        STAMP(10);
        if (__builtin_expect(lds32(sb + OFF_MISC + 28) & 2, 0)) {
            for (int i = 0; i < 5; i++) sts128(tile_addr(w * 5 + i, lane), attn_generic(b * TILE + w * 5 + i, x, esrc, edst, wq, wk, wv));
        } else {
            acc_to_tile(pk, w, lane);
        }
        fence_async_smem();
        EV(12);
    } else {
        mbar_wait(bar_c);
        L0 = ldg_na(lp); L1 = ldg_na(lp + LSTR);
    }

    const unsigned flags = lds32(sb + OFF_MISC + 28);
    const bool anyovf = flags & 1;
    const unsigned zero = flags >> 8;
    const unsigned selA = 0x4140 + zero, selB = 0x4342 + zero, m128 = 0x80000080u + zero;
    if (lane < 8) sts128(sb + OFF_S + NN * 16 + lane * 16, make_uint4(0, 0, 0, 0));
    const unsigned lb = sb + OFF_S + (lane & 7) * 16;
    const unsigned dummy = anyovf ? 0 : lb + 1250 * 128;
    const float zmask = (lane >= 28) ? 0.f : -1.f;
    unsigned stg = sb + OFF_STG + w * 256 + (((lane & 7) * 2 + ((lane >> 3) & 1)) ^ ((lane >> 2) & 1)) * 16;
    unsigned rdb = bar_rd, rde = bar_rd + 48;
    __syncwarp();
    mbar_wait(bar_fill);
    STAMP(11);
#pragma unroll 1
    for (int part = 0; part < 2; part++) {
#pragma unroll 1
        do {
            unsigned ad[12];
            ad[0] = dp2lo(L0.z, m128, lb); ad[1] = dp2hi(L0.z, m128, lb); ad[2] = dp2lo(L0.w, m128, lb); ad[3] = dp2hi(L0.w, m128, lb);
            ad[4] = dp2lo(L1.x, m128, lb); ad[5] = dp2hi(L1.x, m128, lb); ad[6] = dp2lo(L1.y, m128, lb); ad[7] = dp2hi(L1.y, m128, lb);
            ad[8] = dp2lo(L1.z, m128, lb); ad[9] = dp2hi(L1.z, m128, lb); ad[10] = dp2lo(L1.w, m128, lb); ad[11] = dp2hi(L1.w, m128, lb);
            const unsigned sA = __byte_perm(L0.x, 0x64646464u, selA), nB = __byte_perm(L0.x, 0xE4E4E4E4u, selB);
            const float dA = blo_v(L0.y), dB = bhi_v(L0.y);
            L0 = ldg_na(lp + 16 * 32); L1 = ldg_na(lp + 16 * 32 + LSTR);
            const unsigned p9 = __any_sync(~0u, ad[9] != dummy), p10 = __any_sync(~0u, ad[10] != dummy);
            float acc0[4] = {0, 0, 0, 0}, acc1[4] = {0, 0, 0, 0};
#pragma unroll
            for (int s = 0; s < 8; s++) p3_mma(acc0, acc1, ldsm4t(ad[s]), s, sA, nB);
            const uint4 v8 = ldsm4t(ad[8]), v9 = ldsm4t_if(ad[9], p9), v10 = ldsm4t_if(ad[10], p10);
            p3_mma(acc0, acc1, v8, 8, sA, nB);
            if (p9) {
                p3_mma(acc0, acc1, v9, 9, sA, nB);
                if (p10) {
                    p3_mma(acc0, acc1, v10, 10, sA, nB);
                    if (__any_sync(~0u, ad[11] != dummy)) {
                        p3_mma(acc0, acc1, ldsm4t(ad[11] & 0x3FFFFF), 11, sA, nB);
                        if (__any_sync(~0u, (ad[11] >> 22) || anyovf)) {
                            const uint4 C2 = ldg_na(lp + 2 * LSTR);
                            const unsigned e2[4] = {C2.x, C2.y, C2.z, C2.w};
#pragma unroll
                            for (int s = 12; s < 20; s++)
                                p3_mma(acc0, acc1, ldsm4t((s & 1) ? dp2hi(e2[(s - 12) >> 1], m128, lb) : dp2lo(e2[(s - 12) >> 1], m128, lb)), s, sA, nB);
                            if (anyovf) {
                                float4 e = p3_overflow(sc, grp0 + 2 * (rdb - bar_rd), sb + OFF_S);
                                float s0 = e.x + e.z, s1 = e.y + e.w;
                                for (int k = 4; k < 32; k <<= 1) {
                                    float u0 = __shfl_down_sync(~0u, s0, k), u1 = __shfl_down_sync(~0u, s1, k);
                                    if (lane + k < 32) { s0 += u0; s1 += u1; }
                                }
                                acc0[0] += s0; acc0[1] += s1; acc0[2] += s0 - e.x; acc0[3] += s1 - e.y;
                            }
                        }
                    }
                }
            }
            float c0 = acc0[0] + acc1[0], c1 = acc0[1] + acc1[1], c2 = acc0[2] + acc1[2], c3 = acc0[3] + acc1[3];
            float n0 = __shfl_down_sync(~0u, c0, 4), n1 = __shfl_down_sync(~0u, c1, 4);
            float o0 = c0 - c2, o1 = c1 - c3, o2 = fmaf(n0, zmask, c2), o3 = fmaf(n1, zmask, c3);
            asm volatile("stmatrix.sync.aligned.m8n8.x2.shared.b16 [%0],{%1,%2};" ::"r"(stg), "r"(pack2(o0 * dA, o1 * dA)), "r"(pack2(o2 * dB, o3 * dB)) : "memory");
            __syncwarp();
            asm volatile("{.reg .pred p; setp.eq.u32 p,%1,0; @p mbarrier.arrive.shared.b64 _,[%0];}" ::"r"(rdb), "r"(lane) : "memory");
            stg += 4096;
            rdb += 8;
            lp += 16 * 32;
        } while (rdb != rde);
        mbar_wait(bar_t);
        rde = bar_rd + 8 * ((g1 - grp0 + 15) >> 4);
    }
    STAMP(12);
    }
}

typedef CUresult (*EncodeFn)(CUtensorMap*, CUtensorMapDataType, cuuint32_t, void*, const cuuint64_t*, const cuuint64_t*,
                             const cuuint32_t*, const cuuint32_t*, CUtensorMapInterleave, CUtensorMapSwizzle,
                             CUtensorMapL2promotion, CUtensorMapFloatOOBfill);

}

extern "C" void kernel_launch(void* const* d_in, const int* in_sizes, int n_in, void* d_out, int out_size) {
    (void)in_sizes; (void)n_in; (void)out_size;
    static EncodeFn enc = nullptr;
    static void* scratch = nullptr;
    if (!enc) {
        cudaGetSymbolAddress(&scratch, g_scratch);
        void* fn = nullptr;
        cudaDriverEntryPointQueryResult qr;
        cudaGetDriverEntryPoint("cuTensorMapEncodeTiled", &fn, cudaEnableDefault, &qr);
        enc = (EncodeFn)fn;
        cudaFuncSetAttribute(exphormer_kernel, cudaFuncAttributeMaxDynamicSharedMemorySize, SMEM_BYTES);
    }
    CUtensorMap tm_mail, tm_x, tm_wl, tm_wv, tm_ot, tm_o256, tm_o16;
    auto mk = [&](CUtensorMap* tm, void* p, int rows, int bc, int br, CUtensorMapSwizzle sw, CUtensorMapL2promotion pr) {
        cuuint64_t gd[2] = {256, (cuuint64_t)rows}, gs[1] = {512};
        cuuint32_t es[2] = {1, 1}, bx[2] = {(cuuint32_t)bc, (cuuint32_t)br};
        enc(tm, CU_TENSOR_MAP_DATA_TYPE_BFLOAT16, 2, p, gd, gs, bx, es, CU_TENSOR_MAP_INTERLEAVE_NONE, sw, pr, CU_TENSOR_MAP_FLOAT_OOB_FILL_NONE);
    };
    for (int i = 0; i < 2; i++) {
        cuuint64_t gd[3] = {64, 256, 4}, gs[2] = {512, 128};
        cuuint32_t es[3] = {1, 1, 1}, bx[3] = {64, 64, 4};
        enc(i ? &tm_wv : &tm_wl, CU_TENSOR_MAP_DATA_TYPE_BFLOAT16, 3, d_in[i ? 9 : 6], gd, gs, bx, es, CU_TENSOR_MAP_INTERLEAVE_NONE,
            CU_TENSOR_MAP_SWIZZLE_128B, CU_TENSOR_MAP_L2_PROMOTION_L2_128B, CU_TENSOR_MAP_FLOAT_OOB_FILL_NONE);
    }
    {
        cuuint64_t gd[2] = {2048, NT}, gs[1] = {8192};
        cuuint32_t es[2] = {1, 1}, bx[2] = {16, NT};
        enc(&tm_mail, CU_TENSOR_MAP_DATA_TYPE_UINT32, 2, ((Scratch*)scratch)->mail, gd, gs, bx, es, CU_TENSOR_MAP_INTERLEAVE_NONE,
            CU_TENSOR_MAP_SWIZZLE_NONE, CU_TENSOR_MAP_L2_PROMOTION_NONE, CU_TENSOR_MAP_FLOAT_OOB_FILL_NONE);
    }
    mk(&tm_x, d_in[0], NN, 64, TILE, CU_TENSOR_MAP_SWIZZLE_128B, CU_TENSOR_MAP_L2_PROMOTION_L2_128B);
    mk(&tm_ot, d_out, NN, 64, TILE, CU_TENSOR_MAP_SWIZZLE_128B, CU_TENSOR_MAP_L2_PROMOTION_NONE);
    mk(&tm_o256, d_out, NN, 8, 256, CU_TENSOR_MAP_SWIZZLE_NONE, CU_TENSOR_MAP_L2_PROMOTION_NONE);
    mk(&tm_o16, d_out, NN, 8, 16, CU_TENSOR_MAP_SWIZZLE_NONE, CU_TENSOR_MAP_L2_PROMOTION_NONE);
    exphormer_kernel<<<NCTA, 640, SMEM_BYTES>>>(
        (const uint4*)d_in[0], (const uint4*)d_in[2], (const uint4*)d_in[1], (const uint4*)d_in[7], (const uint4*)d_in[8], (const int*)d_in[3],
        (const int*)d_in[4], (Scratch*)scratch, (const uint4*)d_in[5], (const uint4*)d_in[9],
        tm_x, tm_wl, tm_wv, tm_mail, tm_ot, tm_o256, tm_o16);
}
```

```cpp
#include <cuda_runtime.h>
#include <cuda_bf16.h>
#include <cuda.h>
#include <stdint.h>

namespace {

constexpr int NN = 10000, NE = 160000, NEE = 40000;
constexpr int TILE = 80, NT = 125, NCTA = 128, NG = 625, EPC = 1280;
constexpr int CELL = 32;
constexpr int LCAP = 80;
constexpr int OVCAP = EPC + NT * CELL;
#define XD0 700
#define XD1 1100
#define XD2 1900
#define REG_W 104
#define REG_H 64
#define KH 1
#define POLLNS 0
#define STPRE 4
#define G0POS 1
#define G1POS 1
#define GATE2 0
#define LA 2
#define FENCE_EVERY 1
#define CHAINS 2
#define ED0 0
#define VRS 0
constexpr unsigned DUMMY2 = 1250u | (1250u << 16);

constexpr unsigned SB0 = 1024;
constexpr unsigned sb = SB0;
constexpr int OFF_S = 0;
constexpr int OFF_R = 163840;
constexpr int OFF_BAR = OFF_R;
constexpr int OFF_MISC = OFF_R + 256;
constexpr int OFF_DIS = OFF_R + 320;
constexpr int OFF_PROF = OFF_R + 512;
constexpr int OFF_EIDX = OFF_R + 1024;
constexpr int OFF_ALPHA = OFF_R + 1024;
constexpr int OFF_STG = OFF_R + 3072;
constexpr int OFF_CNT1 = OFF_R + 2560;
constexpr int OFF_CNT2 = OFF_R + 3072;
constexpr int OFF_MAIL = OFF_R + 5760;
constexpr int OFF_IMG = OFF_MAIL + 9216;
constexpr int OFF_T = OFF_R + 27648;
constexpr int SMEM_BYTES = OFF_T + 40960;
static_assert(SMEM_BYTES <= 232448 && OFF_T % 1024 == 0 && OFF_STG + 3 * 8192 == OFF_T && OFF_IMG + 10752 <= OFF_T, "smem");
#define bar_fill (sb + OFF_BAR)
#define bar_t (sb + OFF_BAR + 8)
#define bar_mail (sb + OFF_BAR + 16)
#define bar_c (sb + OFF_BAR + 24)
#define bar_rd (sb + OFF_BAR + 32)
#define bar_go (sb + OFF_BAR + 112)
#define bar_full (sb + OFF_BAR + 120)
constexpr int LSTR = (NG + 48) * 32;

struct __align__(256) Scratch {
    uint4 mimg[8192];
    uint4 hs[32 * NN];
    uint4 mail[2 * NT * 512];
    uint4 lists[3 * LSTR];
    uint2 ovfn[NCTA];
    unsigned bar[5 * 64];
    unsigned ovf[NCTA * OVCAP];
};
__device__ Scratch g_scratch;
#define STAMPT(th, i)
#define CLK0(th)
#define CLK1(th, i)
#define STAMP(i) STAMPT(64, i)
#define STAMP2(i) STAMPT(416, i)

extern __shared__ __align__(1024) unsigned char smem_raw[];
__device__ __forceinline__ void bar_arrive(unsigned* p) {
    asm volatile("red.release.gpu.global.add.u32 [%0],1;" ::"l"(p) : "memory");
}
__device__ __forceinline__ void bar_arrive_relaxed(unsigned* p) {
    asm volatile("red.relaxed.gpu.global.add.u32 [%0],1;" ::"l"(p) : "memory");
}
__device__ __forceinline__ void bar_poll(const Scratch* sc, int i) {
    unsigned v, target;
    int lim = 0;
    asm volatile("ld.shared.u32 %0,[%1];" : "=r"(target) : "r"(sb + OFF_MISC + 32 + 4 * i) : "memory");
    while (true) {
        asm volatile("ld.acquire.gpu.global.u32 %0,[%1];" : "=r"(v) : "l"(&sc->bar[i * 64]) : "memory");
        if ((int)(v - target) >= 0) break;
        if (++lim > (1 << 22)) __trap();
        if (POLLNS) __nanosleep(POLLNS);
    }
}
__device__ __forceinline__ unsigned bar_poll2(const unsigned* p, unsigned target) {
    unsigned long long v;
    int lim = 0;
    do {
        asm volatile("ld.acquire.gpu.global.u64 %0,[%1];" : "=l"(v) : "l"(p) : "memory");
        if (++lim > (1 << 22)) __trap();
    } while ((int)((unsigned)v - target) < 0);
    unsigned f = (unsigned)(v >> 32);
    return (f & ~3u) == target ? f & 3 : 0;
}
__device__ __noinline__ void raise_flag(unsigned* p, unsigned target, unsigned bit) {
    unsigned old = atomicCAS(p, 0, 0), seen;
    do {
        seen = old;
        old = atomicCAS(p, seen, ((seen & ~3u) == target ? seen : target) | bit);
    } while (old != seen);
}
__device__ __forceinline__ void mbar_wait(unsigned a) {
    asm volatile("{.reg .pred p; .reg .u32 n;\n"
                 "mov.u32 n,0x400000;\n"
                 "W: mbarrier.try_wait.parity.shared.b64 p,[%0],0;\n"
                 "add.u32 n,n,-1; setp.ne.and.u32 p,n,0,!p; @p bra W;}" ::"r"(a) : "memory");
}
__device__ __forceinline__ bool elect() {
    unsigned r;
    asm volatile("{.reg .pred p; elect.sync _|p,0xFFFFFFFF; selp.u32 %0,1,0,p;}" : "=r"(r));
    return r;
}
__device__ __forceinline__ uint4 ldg_na(const uint4* p) {
    uint4 v;
    asm volatile("ld.global.L1::no_allocate.v4.u32 {%0,%1,%2,%3},[%4];" : "=r"(v.x), "=r"(v.y), "=r"(v.z), "=r"(v.w) : "l"(p) : "memory");
    return v;
}
__device__ __forceinline__ uint4 lds128(unsigned a) {
    uint4 v;
    asm volatile("ld.shared.v4.u32 {%0,%1,%2,%3},[%4];" : "=r"(v.x), "=r"(v.y), "=r"(v.z), "=r"(v.w) : "r"(a) : "memory");
    return v;
}
__device__ __forceinline__ uint4 ldsm4(unsigned a) {
    uint4 v;
    asm volatile("ldmatrix.sync.aligned.m8n8.x4.shared.b16 {%0,%1,%2,%3},[%4];" : "=r"(v.x), "=r"(v.y), "=r"(v.z), "=r"(v.w) : "r"(a) : "memory");
    return v;
}
__device__ __forceinline__ void sts128(unsigned a, uint4 v) {
    asm volatile("st.shared.v4.u32 [%0],{%1,%2,%3,%4};" ::"r"(a), "r"(v.x), "r"(v.y), "r"(v.z), "r"(v.w) : "memory");
}
__device__ __forceinline__ void sts32(unsigned a, unsigned v) { asm volatile("st.shared.u32 [%0],%1;" ::"r"(a), "r"(v) : "memory"); }
__device__ __forceinline__ unsigned lds32(unsigned a) { unsigned v; asm volatile("ld.shared.u32 %0,[%1];" : "=r"(v) : "r"(a) : "memory"); return v; }
__device__ __forceinline__ unsigned atoms_add(unsigned a, unsigned k) { unsigned v; asm volatile("atom.shared.add.u32 %0,[%1],%2;" : "=r"(v) : "r"(a), "r"(k) : "memory"); return v; }
__device__ __forceinline__ unsigned bitsel(unsigned a, unsigned b, unsigned m) { unsigned r; asm("lop3.b32 %0,%1,%2,%3,0xE4;" : "=r"(r) : "r"(a), "r"(b), "r"(m)); return r; }
__device__ __forceinline__ unsigned atoms_inc(unsigned a) { unsigned v; asm volatile("atom.shared.add.u32 %0,[%1],1;" : "=r"(v) : "r"(a) : "memory"); return v; }
__device__ __forceinline__ float blo(unsigned v) { return __uint_as_float(v << 16); }
__device__ __forceinline__ float bhi(unsigned v) { return __uint_as_float(v & 0xFFFF0000u); }
__device__ __forceinline__ float blo_v(unsigned v) { float r; asm volatile("shl.b32 %0,%1,16;" : "=f"(r) : "r"(v)); return r; }
__device__ __forceinline__ float bhi_v(unsigned v) { float r; asm volatile("and.b32 %0,%1,0xFFFF0000;" : "=f"(r) : "r"(v)); return r; }
__device__ __forceinline__ unsigned pack2(float lo, float hi) { unsigned r; asm("cvt.rn.bf16x2.f32 %0,%1,%2;" : "=r"(r) : "f"(hi), "f"(lo)); return r; }

__device__ __forceinline__ void mma16816(float* d, unsigned a0, unsigned a1, unsigned a2, unsigned a3, unsigned b0, unsigned b1) {
    asm volatile("mma.sync.aligned.m16n8k16.row.col.f32.bf16.bf16.f32 {%0,%1,%2,%3},{%4,%5,%6,%7},{%8,%9},{%0,%1,%2,%3};"
                 : "+f"(d[0]), "+f"(d[1]), "+f"(d[2]), "+f"(d[3]) : "r"(a0), "r"(a1), "r"(a2), "r"(a3), "r"(b0), "r"(b1));
}
#define R10(b) "+f"(d[b + 0]), "+f"(d[b + 1]), "+f"(d[b + 2]), "+f"(d[b + 3]), "+f"(d[b + 4]), "+f"(d[b + 5]), "+f"(d[b + 6]), "+f"(d[b + 7]), "+f"(d[b + 8]), "+f"(d[b + 9])
__device__ __forceinline__ void wg80(float* d, unsigned da, unsigned db, int sc) {
    asm volatile("{.reg .pred p; .reg .b64 a, b; setp.ne.b32 p,%42,0; mov.b64 a,{%40,%43}; mov.b64 b,{%41,%43};\n"
                 "wgmma.mma_async.sync.aligned.m64n80k16.f32.bf16.bf16 "
                 "{%0,%1,%2,%3,%4,%5,%6,%7,%8,%9,%10,%11,%12,%13,%14,%15,%16,%17,%18,%19,%20,%21,%22,%23,%24,%25,%26,%27,%28,%29,%30,%31,%32,%33,%34,%35,%36,%37,%38,%39},"
                 "a,b,p,1,1,1,0;}"
                 : R10(0), R10(10), R10(20), R10(30) : "r"(da), "r"(db), "r"(sc), "r"(0x40000040));
}
__device__ __forceinline__ void wg80r(float* d, const uint4& a, unsigned db) {
    asm volatile("{.reg .b64 b; mov.b64 b,{%44,%45};\n"
                 "wgmma.mma_async.sync.aligned.m64n80k16.f32.bf16.bf16 "
                 "{%0,%1,%2,%3,%4,%5,%6,%7,%8,%9,%10,%11,%12,%13,%14,%15,%16,%17,%18,%19,%20,%21,%22,%23,%24,%25,%26,%27,%28,%29,%30,%31,%32,%33,%34,%35,%36,%37,%38,%39},"
                 "{%40,%41,%42,%43},b,1,1,1,0;}"
                 : R10(0), R10(10), R10(20), R10(30) : "r"(a.x), "r"(a.y), "r"(a.z), "r"(a.w), "r"(db), "r"(0x40000040));
}
__device__ __forceinline__ void wg_fence() { asm volatile("wgmma.fence.sync.aligned;" ::: "memory"); }
__device__ __forceinline__ void wg_commit() { asm volatile("wgmma.commit_group.sync.aligned;" ::: "memory"); }
template <int N> __device__ __forceinline__ void wg_wait() { asm volatile("wgmma.wait_group.sync.aligned %0;" ::"n"(N) : "memory"); }
__device__ __forceinline__ void bulk_g2s(unsigned dst, const void* src, unsigned bytes, unsigned bar) {
    asm volatile("cp.async.bulk.shared::cluster.global.mbarrier::complete_tx::bytes [%0],[%1],%2,[%3];" ::"r"(dst), "l"(src), "r"(bytes), "r"(bar) : "memory");
}
__device__ __forceinline__ void fence_async_smem() { asm volatile("fence.proxy.async.shared::cta;" ::: "memory"); }
__device__ __forceinline__ void fence_async_gmem() { asm volatile("fence.proxy.async.global;" ::: "memory"); }

__device__ __forceinline__ unsigned hsat(unsigned a, unsigned c) { unsigned r; asm("add.sat.f16x2 %0,%1,%2;" : "=r"(r) : "r"(a), "r"(c)); return r; }
__device__ __forceinline__ unsigned hset(unsigned a, unsigned c) { unsigned r; asm("set.le.f16x2.f16x2 %0,%1,%2;" : "=r"(r) : "r"(a), "r"(c)); return r; }
__host__ __device__ constexpr unsigned h2c(int v) { return (0x6400u | v) | ((0x6400u | v) << 16); }
__device__ __forceinline__ unsigned dp2lo(unsigned a, unsigned m, unsigned c) { unsigned r; asm volatile("dp2a.lo.u32.u32 %0,%1,%2,%3;" : "=r"(r) : "r"(a), "r"(m), "r"(c)); return r; }
__device__ __forceinline__ unsigned dp2hi(unsigned a, unsigned m, unsigned c) { unsigned r; asm volatile("dp2a.hi.u32.u32 %0,%1,%2,%3;" : "=r"(r) : "r"(a), "r"(m), "r"(c)); return r; }
__device__ __forceinline__ uint4 ldsm4t(unsigned addr) {
    uint4 v;
    asm volatile("ldmatrix.sync.aligned.m8n8.x4.trans.shared.b16 {%0,%1,%2,%3},[%4];" : "=r"(v.x), "=r"(v.y), "=r"(v.z), "=r"(v.w) : "r"(addr));
    return v;
}
__device__ __forceinline__ uint4 ldsm4t_if(unsigned addr, unsigned p) {
    uint4 v;
    asm volatile("{.reg .pred p; setp.ne.u32 p,%5,0; @p ldmatrix.sync.aligned.m8n8.x4.trans.shared.b16 {%0,%1,%2,%3},[%4];}"
                 : "=r"(v.x), "=r"(v.y), "=r"(v.z), "=r"(v.w) : "r"(addr), "r"(p));
    return v;
}
__device__ __forceinline__ void p3_mma(float* acc0, float* acc1, const uint4& v, int s, unsigned sA, unsigned nB) {
    mma16816(acc0, hset(sA, h2c(4 * s + 0)), hsat(nB, h2c(4 * s + 1)), hset(sA, h2c(4 * s + 1)), hsat(nB, h2c(4 * s + 2)), v.x, v.y);
    mma16816(acc1, hset(sA, h2c(4 * s + 2)), hsat(nB, h2c(4 * s + 3)), hset(sA, h2c(4 * s + 3)), hsat(nB, h2c(4 * s + 4)), v.z, v.w);
}
__device__ __forceinline__ void sched_fence(unsigned zero) { asm volatile("{.reg .pred p; setp.ne.u32 p,%0,0; @p exit;}" ::"r"(zero)); }
__device__ __forceinline__ uint4 p3_sel(int i, unsigned sA, unsigned nB) {
    uint4 a;
    asm volatile("set.le.f16x2.f16x2 %0,%4,%6;\n add.sat.f16x2 %1,%5,%7;\n set.le.f16x2.f16x2 %2,%4,%7;\n add.sat.f16x2 %3,%5,%8;"
                 : "=r"(a.x), "=r"(a.y), "=r"(a.z), "=r"(a.w) : "r"(sA), "r"(nB), "r"(h2c(2 * i)), "r"(h2c(2 * i + 1)), "r"(h2c(2 * i + 2)));
    return a;
}
__device__ __noinline__ float4 p3_overflow(const Scratch* sc, int grp, unsigned sS) {
    const unsigned tag = lds32(sb + OFF_MISC + 48);
    int lane = threadIdx.x & 31, g = lane >> 2, t = lane & 3;
    float4 r = make_float4(0.f, 0.f, 0.f, 0.f);
    for (int c = 0; c < NT; c++) {
        const uint2 tn = __ldcg(&sc->ovfn[c]);
        const int n = tn.x == tag ? (int)tn.y : 0;
        for (int i0 = 0; i0 < n; i0 += 32) {
            unsigned e = (i0 + lane < n) ? __ldcg(&sc->ovf[c * OVCAP + i0 + lane]) : 0xFFFFFFFFu;
            unsigned m = __ballot_sync(~0u, (int)(e >> 18) == grp);
            while (m) {
                int j = __ffs(m) - 1;
                m &= m - 1;
                unsigned ee = __shfl_sync(~0u, e, j);
                int row = (ee >> 14) & 15;
                row ^= row >> 3;
                unsigned v = lds32(sS + (ee & 0x3FFF) * 16 + t * 4);
                if ((row >> 1) == g) {
                    if (!(row & 1)) { r.x += blo(v); r.y += bhi(v); } else { r.z += blo(v); r.w += bhi(v); }
                }
            }
        }
    }
    const float k = 1.f / 128.f;
    r.x *= k; r.y *= k; r.z *= k; r.w *= k;
    return r;
}
__device__ __forceinline__ void unpack8(float* f, uint4 v) {
    f[0] = blo(v.x); f[1] = bhi(v.x); f[2] = blo(v.y); f[3] = bhi(v.y); f[4] = blo(v.z); f[5] = bhi(v.z); f[6] = blo(v.w); f[7] = bhi(v.w);
}
__device__ __forceinline__ void vec_mat(float* o, const float* v, const uint4* __restrict__ W, int lane) {
    for (int k = 0; k < 8; k++) o[k] = 0.f;
    for (int l = 0; l < 32; l++) {
#pragma unroll
        for (int i = 0; i < 8; i++) {
            float a = __shfl_sync(~0u, v[i], l), wr[8];
            unpack8(wr, W[(l * 8 + i) * 32 + lane]);
#pragma unroll
            for (int k = 0; k < 8; k++) o[k] = fmaf(a, wr[k], o[k]);
        }
    }
}
__device__ __noinline__ uint4 attn_generic(int node, const uint4* __restrict__ x, const int* __restrict__ esrc, const int* __restrict__ edst,
                                           const uint4* __restrict__ wq, const uint4* __restrict__ wk, const uint4* __restrict__ wv) {
    int lane = threadIdx.x & 31;
    float xr[8], q[8], y[8], o[8];
    unpack8(xr, x[node * 32 + lane]);
    vec_mat(q, xr, wq, lane);
    for (int l = 0; l < 32; l++) {
#pragma unroll
        for (int i = 0; i < 8; i++) {
            float wr[8], p = 0.f;
            unpack8(wr, wk[(l * 8 + i) * 32 + lane]);
#pragma unroll
            for (int k = 0; k < 8; k++) p = fmaf(q[k], wr[k], p);
            for (int k = 16; k; k >>= 1) p += __shfl_xor_sync(~0u, p, k);
            if (lane == l) y[i] = p;
        }
    }
    for (int k = 0; k < 8; k++) o[k] = 0.f;
    float den = 0.f;
    for (int i0 = 0; i0 < NEE; i0 += 32) {
        unsigned m = __ballot_sync(~0u, edst[i0 + lane] == node);
        while (m) {
            int j = __ffs(m) - 1;
            m &= m - 1;
            float gq[8], p = 0.f;
            unpack8(gq, x[esrc[i0 + j] * 32 + lane]);
#pragma unroll
            for (int k = 0; k < 8; k++) p = fmaf(y[k], gq[k], p);
            for (int k = 16; k; k >>= 1) p += __shfl_xor_sync(~0u, p, k);
            float ex = __expf(p * 0.0625f);
            den += ex;
#pragma unroll
            for (int k = 0; k < 8; k++) o[k] = fmaf(ex, gq[k], o[k]);
        }
    }
    float inv = 1.f / (den + 1e-9f);
    for (int k = 0; k < 8; k++) o[k] *= inv;
    vec_mat(q, o, wv, lane);
    return make_uint4(pack2(q[0], q[1]), pack2(q[2], q[3]), pack2(q[4], q[5]), pack2(q[6], q[7]));
}

__device__ __forceinline__ unsigned hfma2(unsigned a, unsigned b, unsigned c) { unsigned r; asm("fma.rn.bf16x2 %0,%1,%2,%3;" : "=r"(r) : "r"(a), "r"(b), "r"(c)); return r; }
__device__ __forceinline__ unsigned hmul2(unsigned a, unsigned b) { unsigned r; asm("mul.rn.bf16x2 %0,%1,%2;" : "=r"(r) : "r"(a), "r"(b)); return r; }

__device__ __forceinline__ unsigned tile_addr(int n, unsigned chunk) { return sb + OFF_T + (chunk >> 3) * 10240 + n * 128 + (((chunk ^ n) & 7) << 4); }
__device__ __forceinline__ void attn_scores(float* v, bool mine, bool par, const uint4* gv, unsigned yaddr) {
    const uint4 y = ldsm4(yaddr);
    float c[4] = {0, 0, 0, 0}, e[4] = {0, 0, 0, 0};
    mma16816(c, gv[0].x, gv[0].y, gv[0].z, gv[0].w, y.x, y.y);
    mma16816(e, gv[2].x, gv[2].y, gv[2].z, gv[2].w, y.x, y.y);
    mma16816(c, gv[1].x, gv[1].y, gv[1].z, gv[1].w, y.z, y.w);
    mma16816(e, gv[3].x, gv[3].y, gv[3].z, gv[3].w, y.z, y.w);
    if (mine) { v[0] = par ? c[1] : c[0]; v[1] = par ? c[3] : c[2]; v[2] = par ? e[1] : e[0]; v[3] = par ? e[3] : e[2]; }
}
__device__ __forceinline__ void attn_softmax(const float* v, const float* u, unsigned lane, unsigned aladdr) {
    const bool hA = lane & 4, hB = lane & 8, hC = lane & 16;
    float a[4];
#pragma unroll
    for (int e = 0; e < 4; e++) a[e] = (hA ? u[e] : v[e]) + __shfl_xor_sync(~0u, hA ? v[e] : u[e], 4);
    float b0 = (hB ? a[1] : a[0]) + __shfl_xor_sync(~0u, hB ? a[0] : a[1], 9);
    float b1 = (hB ? a[3] : a[2]) + __shfl_xor_sync(~0u, hB ? a[2] : a[3], 9);
    float sc = (hC ? b1 : b0) + __shfl_xor_sync(~0u, hC ? b0 : b1, 18);
    float ex, inv;
    asm("ex2.approx.ftz.f32 %0,%1;" : "=f"(ex) : "f"(sc));
    float den = ex + __shfl_xor_sync(~0u, ex, 9);
    den += __shfl_xor_sync(~0u, den, 18);
    asm("rcp.approx.ftz.f32 %0,%1;" : "=f"(inv) : "f"(den + 1e-9f));
    sts32(aladdr, pack2(ex * inv, ex * inv));
    __syncwarp();
}
__device__ __forceinline__ void attn_mix(const uint4* gv, const uint4& a, unsigned oaddr) {
    const unsigned o0 = hfma2(a.w, gv[2].y, hfma2(a.z, gv[2].x, hfma2(a.y, gv[0].y, hmul2(a.x, gv[0].x))));
    const unsigned o1 = hfma2(a.w, gv[2].w, hfma2(a.z, gv[2].z, hfma2(a.y, gv[0].w, hmul2(a.x, gv[0].z))));
    const unsigned o2 = hfma2(a.w, gv[3].y, hfma2(a.z, gv[3].x, hfma2(a.y, gv[1].y, hmul2(a.x, gv[1].x))));
    const unsigned o3 = hfma2(a.w, gv[3].w, hfma2(a.z, gv[3].z, hfma2(a.y, gv[1].w, hmul2(a.x, gv[1].z))));
    asm volatile("stmatrix.sync.aligned.m8n8.x4.shared.b16 [%0],{%1,%2,%3,%4};" ::"r"(oaddr), "r"(o0), "r"(o1), "r"(o2), "r"(o3) : "memory");
}
__device__ __forceinline__ void pack_acc(unsigned* pk, const float* d) {
#pragma unroll
    for (int j = 0; j < 20; j++) pk[j] = pack2(d[2 * j], d[2 * j + 1]);
}
__device__ __forceinline__ void acc_to_tile(const unsigned* pk, int w, int lane) {
    const unsigned a = sb + OFF_T + (w >> 2) * 10240 + (lane >> 4) * 1024 + (lane & 7) * 128 + (((2 * (w & 3) + ((lane >> 3) & 1)) ^ (lane & 7)) << 4);
#pragma unroll
    for (int j = 0; j < 5; j++)
        asm volatile("stmatrix.sync.aligned.m8n8.x4.trans.shared.b16 [%0],{%1,%2,%3,%4};" ::"r"(a + j * 2048), "r"(pk[4 * j]), "r"(pk[4 * j + 1]), "r"(pk[4 * j + 2]), "r"(pk[4 * j + 3]) : "memory");
}
__device__ __forceinline__ unsigned movm(unsigned a) { unsigned d; asm volatile("movmatrix.sync.aligned.m8n8.trans.b16 %0,%1;" : "=r"(d) : "r"(a)); return d; }
__device__ __forceinline__ void tma_load2d(unsigned dst, const CUtensorMap* tm, int c0, int c1, unsigned bar) {
    asm volatile("cp.async.bulk.tensor.2d.shared::cluster.global.mbarrier::complete_tx::bytes [%0],[%1,{%3,%4}],[%2];"
                 ::"r"(dst), "l"(tm), "r"(bar), "r"(c0), "r"(c1) : "memory");
}
__device__ __forceinline__ void tma_load3d(unsigned dst, const CUtensorMap* tm, int row, unsigned bar) {
    asm volatile("cp.async.bulk.tensor.3d.shared::cluster.global.mbarrier::complete_tx::bytes [%0],[%1,{%4,%3,%4}],[%2];"
                 ::"r"(dst), "l"(tm), "r"(bar), "r"(row), "r"(0) : "memory");
}
__device__ __forceinline__ void cp16(unsigned dst, const void* src) { asm volatile("cp.async.cg.shared.global [%0],[%1],16;" ::"r"(dst), "l"(src) : "memory"); }
__device__ __forceinline__ void cp_commit() { asm volatile("cp.async.commit_group;" ::: "memory"); }
template <int N> __device__ __forceinline__ void cp_wait() { asm volatile("cp.async.wait_group %0;" ::"n"(N) : "memory"); }
__device__ __forceinline__ void nb_sync_id(int id, int n) { asm volatile("bar.sync %0,%1;" ::"r"(id), "r"(n) : "memory"); }
__device__ __forceinline__ void nb_arrive_id(int id, int n) { asm volatile("bar.arrive %0,%1;" ::"r"(id), "r"(n) : "memory"); }
template <int ID, int N> __device__ __forceinline__ void nb_sync() { asm volatile("bar.sync %0,%1;" ::"n"(ID), "n"(N) : "memory"); }
template <int ID, int N> __device__ __forceinline__ void nb_arrive() { asm volatile("bar.arrive %0,%1;" ::"n"(ID), "n"(N) : "memory"); }
__device__ __forceinline__ void mbar_init(unsigned a, int n) { asm volatile("mbarrier.init.shared.b64 [%0],%1;" ::"r"(a), "r"(n) : "memory"); }
__device__ __forceinline__ void mbar_expect(unsigned a, int n) { asm volatile("mbarrier.arrive.expect_tx.shared.b64 _,[%0],%1;" ::"r"(a), "r"(n) : "memory"); }
__device__ __forceinline__ void mbar_arrive(unsigned a) { asm volatile("mbarrier.arrive.shared.b64 _,[%0];" ::"r"(a) : "memory"); }

constexpr unsigned PADBIN = 2560, CU = 0x101;
__device__ __noinline__ void push_overflow(Scratch* sc, unsigned dst, unsigned src) {
    sc->ovf[blockIdx.x * OVCAP + atoms_inc(sb + OFF_MISC)] = (dst << 14) | src;
}
__device__ __noinline__ void bin_overflow(Scratch* sc, unsigned mask, unsigned ht) {
    for (int i = 0; i < 24 + 6 * 16; i++) {
        unsigned e;
        if (i < 24) {
            if (!(mask >> i & 1)) continue;
            e = lds32(sb + OFF_MAIL + (ht + (i >> 2) * 96) * 16 + (i & 3) * 4) & 0x7FFFFFFFu;
        } else {
            const int k = (i - 24) >> 4;
            if (!(mask >> (24 + k) & 1)) continue;
            e = __ldcg((const unsigned*)(sc->mail + ((NT + blockIdx.x) * 512 + ((ht + k * 96) & ~3u))) + ((i - 24) & 15));
        }
        if (e < (PADBIN << 16))
            push_overflow(sc, blockIdx.x * TILE + ((e >> 21) & ~3u) + ((e >> 18) & 3), ((e & 2047) << 3) | ((e >> 20) & 7));
    }
}
__device__ __forceinline__ void place(unsigned e, unsigned h) {
    asm volatile("{.reg .pred p; setp.lt.u32 p,%2,%3; @p st.shared.u16 [%0],%1;}"
                 ::"r"(sb + OFF_IMG + bitsel(h >> 1, e >> 16, 0x318E)), "h"((unsigned short)e), "r"(h), "n"((LCAP + 16) * CU) : "memory");
}
__device__ __forceinline__ void bulk_s2g(void* dst, unsigned src, unsigned bytes) {
    asm volatile("cp.async.bulk.global.shared::cta.bulk_group [%0],[%1],%2;" ::"l"(dst), "r"(src), "r"(bytes) : "memory");
}
__device__ __forceinline__ void tma_reduce(const CUtensorMap* tm, unsigned src, int c0, int c1) {
    asm volatile("cp.reduce.async.bulk.tensor.2d.global.shared::cta.add.tile.bulk_group [%0,{%2,%3}],[%1];" ::"l"(tm), "r"(src), "r"(c0), "r"(c1) : "memory");
}
#define EV(id) nb_arrive<id, 544>()
#define WAIT_EV(id) do { __syncwarp(); nb_sync<id, 544>(); } while (0)

__global__ void __launch_bounds__(640, 1)
exphormer_kernel(const uint4* __restrict__ x, const uint4* __restrict__ dst4, const uint4* __restrict__ src4,
                 const uint4* __restrict__ wq, const uint4* __restrict__ wk, const int* __restrict__ esrc,
                 const int* __restrict__ edst, Scratch* __restrict__ sc, const uint4* __restrict__ dis, const uint4* __restrict__ wv,
                 const __grid_constant__ CUtensorMap tm_x, const __grid_constant__ CUtensorMap tm_wl, const __grid_constant__ CUtensorMap tm_wv,
                 const __grid_constant__ CUtensorMap tm_m, const __grid_constant__ CUtensorMap tm_ms,
                 const __grid_constant__ CUtensorMap tm_mail, const __grid_constant__ CUtensorMap tm_ot, const __grid_constant__ CUtensorMap tm_o256, const __grid_constant__ CUtensorMap tm_o16) {
    const unsigned tid = threadIdx.x, lane = tid & 31, g = lane >> 2, t = lane & 3;
    const unsigned b = blockIdx.x;
    const bool rowcta = b < NT;
    const int slice = b >> 2, range = b & 3;
    const int g0 = (range * NG) >> 2, g1 = ((range + 1) * NG) >> 2;
    STAMP(0);

    if (tid >= 512) {
    asm volatile("setmaxnreg.dec.sync.aligned.u32 %0;" ::"n"(REG_H));
    if (tid >= 544) {
        const unsigned ht = tid - 544;
        if (ht < 32) {
            if (lane == 0) asm volatile("prefetch.tensormap [%0];" ::"l"(&tm_mail) : "memory");
            __syncwarp();
            nb_sync<13, 160>();
            nb_sync<2, 352>();
            if (rowcta) {
                const uint4 c = lds128(sb + OFF_CNT1 + lane * 16);
                const unsigned cc[4] = {c.x, c.y, c.z, c.w};
#pragma unroll
                for (int i = 0; i < 4; i++)
                    if (cc[i] > 16) asm volatile("red.shared.or.b32 [%0],0x80000000;" ::"r"(sb + OFF_MAIL + (lane * 4 + i) * 64 + 60) : "memory");
                fence_async_smem();
                __syncwarp();
                if (elect())
                    asm volatile("cp.async.bulk.tensor.2d.global.shared::cta.bulk_group [%0,{%2,%3}],[%1];" ::"l"(&tm_mail), "r"(sb + OFF_MAIL), "r"(b * 16), "r"(0) : "memory");
                for (int i = 0; i < 4; i++)
                    if (lds32(sb + OFF_CNT1 + lane * 16 + i * 4) > 16) bulk_s2g(sc->mail + ((NT + lane * 4 + i) * 512 + b * 4), sb + OFF_IMG + (lane * 4 + i) * 64, 64);
                asm volatile("cp.async.bulk.commit_group;" ::: "memory");
                asm volatile("cp.async.bulk.wait_group 0;" ::: "memory");
                fence_async_gmem();
                __syncwarp();
            }
            if (rowcta) nb_arrive<1, 96>();
            if (elect()) {
                bar_arrive_relaxed(&sc->bar[0]);
                STAMPT(544, 47);
                if (rowcta) {
                    bar_poll(sc, 0);
                    fence_async_gmem();
                    mbar_expect(bar_mail, 8000);
                    bulk_g2s(sb + OFF_MAIL, sc->mail + b * 512, 8000, bar_mail);
                    if (GATE2) mbar_arrive(bar_go);
                }
            }
            __syncwarp();
        } else if (ht < 64) {
            if (lane == 0) asm volatile("prefetch.tensormap [%0];" ::"l"(&tm_ms) : "memory");
            nb_sync<14, 192>();
            if (elect()) {
                asm volatile("cp.async.bulk.tensor.2d.global.shared::cta.bulk_group [%0,{%2,%3}],[%1];" ::"l"(&tm_ms), "r"(sb + OFF_MAIL + 8064), "r"((b & 7) * 32), "r"((b >> 3) * 16) : "memory");
                asm volatile("cp.async.bulk.commit_group;" ::: "memory");
                asm volatile("cp.async.bulk.wait_group 0;" ::: "memory");
                fence_async_gmem();
                bar_arrive_relaxed(&sc->bar[3 * 64]);
            }
            __syncwarp();
            STAMPT(576, 46);
        } else {
            if (lane < 5) {
                unsigned epoch;
                asm volatile("ld.relaxed.gpu.global.u32 %0,[%1];" : "=r"(epoch) : "l"(&sc->bar[lane * 64]) : "memory");
                sts32(sb + OFF_MISC + 32 + lane * 4, (epoch & ~(NCTA - 1)) + NCTA);
            }
            __syncwarp();
            nb_arrive<14, 192>();
            nb_arrive<15, 64>();
            nb_arrive<13, 160>();
        }
        if (rowcta) {
            if (ht >= 32) {
                nb_sync<1, 96>();
                const unsigned pad = (PADBIN + 4 * lane) << 16, h2 = ht - 32;
                sts128(sb + OFF_MAIL + 8000 + h2 * 16, make_uint4(pad, pad, pad, pad));
                if (h2 < 12) sts128(sb + OFF_MAIL + 9024 + h2 * 16, make_uint4(pad, pad, pad, pad));
#pragma unroll
                for (int k = 0; k < 9; k++) if (k % 3 < 2 || h2 < 32) sts128(sb + OFF_IMG + (k / 3) * 4096 + (k % 3) * 1024 + h2 * 16, make_uint4(DUMMY2, DUMMY2, DUMMY2, DUMMY2));
            }
            nb_sync<13, 96>();
            mbar_wait(bar_mail);
            STAMPT(576, 16);
            uint4 e[6], h[6];
            unsigned flagged = 0, late = 0, longg = 0;
#pragma unroll
            for (int k = 0; k < 6; k++) e[k] = lds128(sb + OFF_MAIL + (ht + k * 96) * 16);
#pragma unroll
            for (int k = 0; k < 6; k++) { flagged |= (e[k].w >> 31) << k; e[k].w &= 0x7FFFFFFFu; }
            while (flagged) {
                const unsigned f = __ffs(flagged) - 1, k = atoms_add(sb + OFF_MISC + 4, 4);
                const uint4* sp = sc->mail + ((NT + b) * 512 + ((ht + f * 96) & ~3u));
                flagged &= flagged - 1;
                if (k < 76) {
#pragma unroll
                    for (int j = 0; j < 4; j++) cp16(sb + OFF_MAIL + 8000 + (k + j) * 16, sp + j);
                } else {
                    late |= 1u << (24 + f);
                }
            }
            cp_commit();
            __syncwarp();
#pragma unroll
            for (int k = 0; k < 6; k++) {
                if (k == 5) { cp_wait<0>(); nb_sync<1, 96>(); if (ht >= 20) e[5] = lds128(sb + OFF_MAIL + (ht + 480) * 16); }
                h[k] = make_uint4(atoms_add(sb + OFF_CNT2 + (e[k].x >> 16), CU), atoms_add(sb + OFF_CNT2 + (e[k].y >> 16), CU),
                                  atoms_add(sb + OFF_CNT2 + (e[k].z >> 16), CU), atoms_add(sb + OFF_CNT2 + (e[k].w >> 16), CU));
            }
            nb_sync<1, 96>();
            STAMPT(576, 17);
            for (unsigned G = ht >> 5; G < 5; G += 3) {
                const unsigned ca = sb + OFF_CNT2 + G * 512 + lane * 16;
                const uint4 c = lds128(ca);
                const unsigned dp = hmul2(lds32(sb + OFF_DIS + (G * 8 + g) * 4), 0x43004300u);
                const bool sw = lane >= 16;
                unsigned s1 = sw ? c.y : c.x, s2 = c.x + c.y, s3 = s2 + (sw ? c.w : c.z), tot = s2 + c.z + c.w, inc = tot;
                unsigned u = __shfl_up_sync(~0u, inc, 8); if (lane >= 8) inc += u;
                u = __shfl_up_sync(~0u, inc, 16); if (sw) inc += u;
                const unsigned base = inc - tot;
                const unsigned p0 = min(base, LCAP * CU), p1 = min(base + s1, LCAP * CU), p2 = min(base + s2, LCAP * CU), p3 = min(base + s3, LCAP * CU);
                sts128(ca, make_uint4((sw ? p1 : p0) + 16 * CU, (sw ? p0 : p1) + 16 * CU, (sw ? p3 : p2) + 16 * CU, (sw ? p2 : p3) + 16 * CU));
                const unsigned word = __byte_perm(__byte_perm(p0, p1, 0x0040), __byte_perm(p2, p3, 0x0040), 0x5410);
                const unsigned wa = __shfl_sync(~0u, word, (g >> 1) * 8 + 2 * t), wb = __shfl_sync(~0u, word, (g >> 1) * 8 + 2 * t + 1);
                const unsigned hdr = __byte_perm(wa, wb, (g & 1) ? 0x7362 : 0x5140);
                if (__any_sync(~0u, inc > 48 * CU)) longg |= 1u << G;
                asm volatile("st.shared.v2.u32 [%0],{%1,%2};" ::"r"(sb + OFF_IMG + G * 512 + lane * 16), "r"(hdr), "r"(__byte_perm(dp, dp, sw ? 0x1032 : 0x3210)) : "memory");
            }
            nb_sync<1, 96>();
            int hmax = 0;
#pragma unroll
            for (int k0 = 0; k0 < 6; k0 += 3) {
#pragma unroll
                for (int k = k0; k < k0 + 3; k++) { e[k] = lds128(sb + OFF_MAIL + (ht + k * 96) * 16); e[k].w &= 0x7FFFFFFFu; }
#pragma unroll
                for (int k = k0; k < k0 + 3; k++) {
                    h[k].x += lds32(sb + OFF_CNT2 + (e[k].x >> 16)); h[k].y += lds32(sb + OFF_CNT2 + (e[k].y >> 16));
                    h[k].z += lds32(sb + OFF_CNT2 + (e[k].z >> 16)); h[k].w += lds32(sb + OFF_CNT2 + (e[k].w >> 16));
                }
#pragma unroll
                for (int k = k0; k < k0 + 3; k++) {
                    place(e[k].x, h[k].x); place(e[k].y, h[k].y); place(e[k].z, h[k].z); place(e[k].w, h[k].w);
                    hmax = max(hmax, max(max((int)h[k].x, (int)h[k].y), max((int)h[k].z, (int)h[k].w)));
                }
            }
            if (__builtin_expect(hmax >= (int)((LCAP + 16) * CU), 0)) {
#pragma unroll
                for (int k = 0; k < 6; k++)
                    late |= ((h[k].x >= (LCAP + 16) * CU) | (h[k].y >= (LCAP + 16) * CU) << 1 | (h[k].z >= (LCAP + 16) * CU) << 2 | (h[k].w >= (LCAP + 16) * CU) << 3) << (4 * k);
            }
            if (__builtin_expect(late, 0)) bin_overflow(sc, late, ht);
            if (longg && lane == 0) asm volatile("red.shared.or.b32 [%0],%1;" ::"r"(sb + OFF_MISC + 8), "r"(longg) : "memory");
            nb_sync<1, 96>();
            if (ht < 32)
                for (unsigned m = lds32(sb + OFF_MISC + 8); m; m &= m - 1)
                    asm volatile("red.shared.or.b32 [%0],0x80000000;" ::"r"(sb + OFF_IMG + 4096 + (__ffs(m) - 1) * 512 + lane * 16 + 12) : "memory");
            fence_async_smem();
            __syncwarp();
            STAMPT(576, 18);
        }
        if (ht < 32 && elect()) {
            if (rowcta) {
                for (int c = 0; c < 3; c++) bulk_s2g(sc->lists + (c * LSTR + b * 160), sb + OFF_IMG + c * 4096, 2560);
                asm volatile("cp.async.bulk.commit_group;" ::: "memory");
                const unsigned novf = lds32(sb + OFF_MISC), bad = lds32(sb + OFF_MISC + 20);
                if (__builtin_expect(novf | bad, 0)) {
                    sc->ovfn[b] = make_uint2(lds32(sb + OFF_MISC + 48), novf);
                    raise_flag(&sc->bar[4 * 64 + 1], lds32(sb + OFF_MISC + 48), (novf ? 1 : 0) | (bad ? 2 : 0));
                    __threadfence();
                }
                asm volatile("cp.async.bulk.wait_group 0;" ::: "memory");
                fence_async_gmem();
            }
            bar_arrive_relaxed(&sc->bar[4 * 64]);
            STAMPT(544, 19);
            sts32(sb + OFF_MISC + 28, bar_poll2(&sc->bar[4 * 64], lds32(sb + OFF_MISC + 48)));
            mbar_arrive(bar_c);
            STAMPT(544, 23);
        }
    } else {
        const bool one = elect();
        auto load_xl = [&](int i) {
            mbar_expect(bar_full + 8 * i, 32768 + 10240);
            tma_load2d(sb + OFF_T + i * 10240, &tm_x, i * 64, b * TILE, bar_full + 8 * i);
            tma_load3d(sb + OFF_S + i * 32768, &tm_wl, i * 64, bar_full + 8 * i);
        };
        auto load_m = [&](int i, int slot) {
            mbar_expect(bar_full + 32 + 8 * i, 32768);
            tma_load3d(sb + OFF_S + slot * 32768, &tm_m, i * 64, bar_full + 32 + 8 * i);
        };
        auto load_v = [&](int i, int slot) {
            mbar_expect(bar_full + 64 + 8 * i, 32768);
            tma_load3d(sb + OFF_S + slot * 32768, &tm_wv, i * 64, bar_full + 64 + 8 * i);
        };
        const char* hsl = (const char*)(sc->hs + slice * NN);
        auto fill = [&](int slot) { bulk_g2s(sb + OFF_S + slot * 32768, hsl + slot * 32768, slot == 4 ? NN * 16 - 4 * 32768 : 32768, bar_fill); };
        const unsigned t0 = clock();
        if (one) {
            for (int i = 0; i < 2; i++) mbar_init(bar_full + 8 * i, 1);
            asm volatile("fence.mbarrier_init.release.cluster;" ::: "memory");
            while ((unsigned)clock() - t0 < XD0) {}
            if (rowcta) load_xl(0);
            STAMPT(512, 41);
            for (int i = 2; i < 12; i++) mbar_init(bar_full + 8 * i, 1);
            mbar_init(bar_go, 1 + GATE2);
            for (int i = 0; i < 4; i++) mbar_init(bar_fill + 8 * i, 1);
            for (int i = 0; i < 10; i++) mbar_init(bar_rd + 8 * i, i < 9 ? 16 : g1 - g0 - 144);
            asm volatile("fence.mbarrier_init.release.cluster;" ::: "memory");
            if ((unsigned)__cvta_generic_to_shared(smem_raw) != sb) __trap();
            mbar_expect(bar_fill, NN * 16);
        }
        __syncwarp();
        nb_arrive<3, 544>();
        nb_arrive<13, 160>();
        if (one && rowcta) {
            while ((unsigned)clock() - t0 < XD1) {}
            load_xl(1);
            STAMPT(512, 40);
        }
        __syncwarp();
        nb_sync<15, 64>();
        if (rowcta) {
            if (one) {
                if (XD2) { while ((unsigned)clock() - t0 < XD2 + 1) {} } else mbar_wait(bar_full);
                load_xl(2);
                STAMPT(512, 52);
                mbar_wait(bar_full + (XD2 ? 0 : 8)); load_xl(3);
                STAMPT(512, 53);
                asm volatile("cp.async.bulk.prefetch.L2.global [%0],%1;" ::"l"(wv + b * 64), "r"(b == NT - 1 ? 4096 : 1024) : "memory");
                asm volatile("prefetch.tensormap [%0];" ::"l"(&tm_m) : "memory");
                asm volatile("prefetch.tensormap [%0];" ::"l"(&tm_wv) : "memory");
                bar_poll(sc, 3);
                STAMPT(512, 48);
                fence_async_gmem();
            }
            WAIT_EV(5); if (one) { load_m(0, 0); load_m(1, 1); mbar_arrive(bar_go); }
            WAIT_EV(6); if (one) load_m(2, 3);
            WAIT_EV(7); if (one) load_m(3, 0);
            WAIT_EV(12); if (one) bar_arrive(&sc->bar[2 * 64]);
            STAMPT(512, 24);
            WAIT_EV(14); if (one) { fence_async_smem(); load_v(0, 4); load_v(1, 2); }
            WAIT_EV(15);
            if (one) {
                fence_async_smem();
                load_v(2, 1); load_v(3, 3);
                bar_poll(sc, 2);
                fence_async_gmem();
            }
            STAMPT(512, 25);
            WAIT_EV(2); if (one) { fill(0); if (VRS > 0) fill(4); if (VRS > 1) fill(2); }
            WAIT_EV(4); if (one) fill(1);
            WAIT_EV(5); if (one) fill(3);
            if (VRS < 2) { WAIT_EV(6); if (one) fill(2); }
            if (VRS < 1) { WAIT_EV(7); if (one) fill(4); }
            WAIT_EV(12);
            if (one) {
                fence_async_smem();
#pragma unroll
                for (int kb = 0; kb < 4; kb++)
                    asm volatile("cp.async.bulk.tensor.2d.global.shared::cta.bulk_group [%0,{%2,%3}],[%1];"
                                 ::"l"(&tm_ot), "r"(sb + OFF_T + kb * 10240), "r"(kb * 64), "r"(b * TILE) : "memory");
                asm volatile("cp.async.bulk.commit_group;" ::: "memory");
                asm volatile("cp.async.bulk.wait_group 0;" ::: "memory");
                fence_async_gmem();
            }
        } else {
            if (one) {
                bar_arrive(&sc->bar[2 * 64]);
                bar_poll(sc, 2);
                fence_async_gmem(); fence_async_smem();
                for (int i = 0; i < 5; i++) fill(i);
            }
        }
        if (one) {
            bar_arrive_relaxed(&sc->bar[1 * 64]);
            mbar_arrive(bar_t);
            STAMPT(512, 26);
            bar_poll(sc, 1);
            fence_async_gmem();
            STAMPT(512, 27);
#pragma unroll 1
            for (int r = 0; r < 9; r++) {
                mbar_wait(bar_rd + 8 * r);
                fence_async_smem();
                tma_reduce(&tm_o256, sb + OFF_STG + r * 4096, slice * 8, (g0 + 16 * r) * 16);
            }
            mbar_wait(bar_rd + 72);
            STAMPT(512, 14);
            fence_async_smem();
            for (int i = 144; i < g1 - g0; i++) tma_reduce(&tm_o16, sb + OFF_STG + i * 256, slice * 8, (g0 + i) * 16);
            asm volatile("cp.async.bulk.commit_group;" ::: "memory");
            asm volatile("cp.async.bulk.wait_group.read 0;" ::: "memory");
            STAMPT(512, 13);
        }
    }
    } else {
    if (tid < 32) {
        unsigned bad = 0;
        uint4 xd[3];
#pragma unroll
        for (int k = 0; k < 3; k++) xd[k] = ldg_na((const uint4*)edst + min(b * TILE + k * 32 + lane, NN - 1u));
#pragma unroll
        for (int k = 0; k < 3; k++) { const unsigned n = min(b * TILE + k * 32 + lane, NN - 1u); bad |= (xd[k].x ^ n) | (xd[k].y ^ n) | (xd[k].z ^ n) | (xd[k].w ^ n); }
        bad = __any_sync(~0u, bad);
        if (lane == 0) sts32(sb + OFF_MISC + 20, bad);
        __syncwarp();
        nb_arrive<13, 160>();
    } else if (tid < 64) {
        const uint4* ep = (const uint4*)esrc + (min(b, NT - 1u) * TILE + lane);
        cp16(sb + OFF_EIDX + lane * 16, ep); cp16(sb + OFF_EIDX + 512 + lane * 16, ep + 32);
        if (lane < 16) cp16(sb + OFF_EIDX + 1024 + lane * 16, ep + 64);
        if (lane < 10) cp16(sb + OFF_DIS + lane * 16, dis + (min(b, NT - 1u) * 10 + lane));
        cp_commit();
        cp_wait<0>();
        nb_arrive<13, 160>();
    } else if (tid >= 192) {
        if (rowcta) {
            const unsigned bt = tid - 192;
            if (ED0) { const unsigned t0 = clock(); while ((unsigned)clock() - t0 < ED0 + 1) {} }
            const uint4 ed = ldg_na(dst4 + (b * 320 + bt)), es = ldg_na(src4 + (b * 320 + bt));
            const unsigned pad = (PADBIN + 4 * ((bt & 3) + ((b * 4) & 28))) << 16;
#pragma unroll
            for (int k = 0; k < 4; k++) if ((k & 1) == 0 || bt < 180) sts128(sb + OFF_MAIL + (k >> 1) * 9216 + (bt + (k & 1) * 320) * 16, make_uint4(pad, pad, pad, pad));
            const unsigned cz = bt < (512 + PADBIN) / 16 ? 0 : 0x40000000;
            if (bt < (512 + 2688) / 16) sts128(sb + OFF_CNT1 + bt * 16, make_uint4(cz, cz, cz, cz));
            if (bt == 319) sts128(sb + OFF_MISC, make_uint4(0, 0, 0, 0));
            unsigned z;
            asm volatile("{.reg .pred p; setp.eq.u32 p,%1,0xFFFFFFFF; bar.red.popc.u32 %0,4,320,p;}" : "=r"(z) : "r"(bt) : "memory");
            const unsigned dd[4] = {ed.x + z, ed.y + z, ed.z + z, ed.w + z}, ss[4] = {es.x + z, es.y + z, es.z + z, es.w + z};
            unsigned rk[4], ow[4];
#pragma unroll
            for (int i = 0; i < 4; i++) { ow[i] = dd[i] / TILE; rk[i] = atoms_inc(sb + OFF_CNT1 + ow[i] * 4); }
#pragma unroll
            for (int i = 0; i < 4; i++) {
                const unsigned dl = dd[i] - ow[i] * TILE;
                const unsigned e = bitsel(ss[i] << 20, bitsel(dl << 21, dl << 18, 0xFF800000u), 0x00700000u) + (ss[i] >> 3);
                asm volatile("{.reg .pred p; setp.lt.u32 p,%2,%3; @p st.shared.u32 [%0],%1;}" ::"r"(sb + OFF_MAIL + ow[i] * 64 + rk[i] * 4 + (rk[i] >> 4) * (9216 - 64)), "r"(e), "r"(rk[i]), "n"(CELL) : "memory");
            }
            if (__builtin_expect((rk[0] | rk[1] | rk[2] | rk[3]) >= CELL, 0)) {
#pragma unroll
                for (int i = 0; i < 4; i++) if (rk[i] >= CELL) push_overflow(sc, dd[i], ss[i]);
            }
        }
        STAMPT(416, 44);
        nb_arrive<2, 352>();
    } else {
        const unsigned fw = b >> 3, hq = b & 7, q = (tid >> 5) - 2;
        const unsigned ma = sb + OFF_S + 4 * 32768 + 8192 + q * 6144;
        {
            const unsigned r = lane >> 3, da = ma + r * 128 + (((lane ^ r) & 7) << 4);
            const uint4* pa = wq + ((16 * fw + r) * 32 + q * 8 + (lane & 7));
            const uint4* pb = wk + ((32 * hq + r) * 32 + q * 8 + (lane & 7));
#pragma unroll
            for (int u = 0; u < 12; u++) cp16((da ^ ((u & 1) << 6)) + u * 512, u < 4 ? pa + u * 128 : pb + (u - 4) * 128);
            cp_commit();
        }
        const unsigned aa = ma + (lane & 15) * 128 + ((((lane >> 4) ^ lane) & 7) << 4);
        const unsigned br = 4 * ((lane & 7) >> 1) + 2 * (lane >> 4) + (lane & 1);
        const unsigned ba = ma + 2048 + br * 128 + (((((lane >> 3) & 1) ^ br) & 7) << 4);
        float c[4][4];
#pragma unroll
        for (int u = 0; u < 4; u++) c[u][0] = c[u][1] = c[u][2] = c[u][3] = 0.f;
        STAMPT(64, 38);
        cp_wait<0>();
        __syncwarp();
        STAMPT(64, 39);
#pragma unroll
        for (int k = 0; k < 4; k++) {
            const uint4 a = ldsm4(aa ^ (k << 5)), b0 = ldsm4(ba ^ (k << 5)), b1 = ldsm4((ba ^ (k << 5)) + 2048);
            mma16816(c[0], a.x, a.y, a.z, a.w, b0.x, b0.y); mma16816(c[1], a.x, a.y, a.z, a.w, b0.z, b0.w);
            mma16816(c[2], a.x, a.y, a.z, a.w, b1.x, b1.y); mma16816(c[3], a.x, a.y, a.z, a.w, b1.z, b1.w);
        }
        const unsigned ra = sb + OFF_S + 4 * 32768 + lane * 16;
#pragma unroll
        for (int i = 0; i < 4; i++)
            sts128(ra + q * 2048 + i * 512, make_uint4(__float_as_uint(c[2 * (i & 1)][2 * (i >> 1)]), __float_as_uint(c[2 * (i & 1)][2 * (i >> 1) + 1]),
                                                       __float_as_uint(c[2 * (i & 1) + 1][2 * (i >> 1)]), __float_as_uint(c[2 * (i & 1) + 1][2 * (i >> 1) + 1])));
        STAMPT(64, 42);
        nb_sync<8, 128>();
        float m[4] = {0, 0, 0, 0};
#pragma unroll
        for (int i = 0; i < 4; i++) {
            const uint4 u = lds128(ra + i * 2048 + q * 512);
            m[0] += __uint_as_float(u.x); m[1] += __uint_as_float(u.y); m[2] += __uint_as_float(u.z); m[3] += __uint_as_float(u.w);
        }
        const float k = 0.0625f * 1.4426950408889634f;
        asm volatile("st.shared.v2.u32 [%0],{%1,%2};" ::"r"(sb + OFF_MAIL + 8064 + (8 * (q >> 1) + g) * 64 + (q & 1) * 32 + t * 8),
                     "r"(pack2(m[0] * k, m[1] * k)), "r"(pack2(m[2] * k, m[3] * k)) : "memory");
        fence_async_smem();
        STAMPT(64, 43);
        nb_arrive<14, 192>();
    }
    asm volatile("setmaxnreg.inc.sync.aligned.u32 %0;" ::"n"(REG_W));
    const int w = __shfl_sync(~0u, tid >> 5, 0), wg = w >> 2;
    const int grp0 = g0 + w;
    const uint4* lp = sc->lists + (grp0 * 32 + lane);
    uint4 L0, L1;
    nb_sync<3, 544>();

    if (__builtin_expect(rowcta, 1)) {
        const unsigned descA = 0x10000u + (SB0 + OFF_S) / 16 + wg * 512;
        const unsigned greg = sb + OFF_S + w * 2048 + lane * 16;
        float d[40];
        unsigned pk[20];
        unsigned* hp = (unsigned*)(sc->hs + (2 * w * NN + b * TILE)) + lane;
        auto mma_k = [&](int Q, int slot, int st, int k0, int k1) {
            if (st < 0) wg_fence();
#pragma unroll
            for (int k = k0; k < k1; k++) {
                if (st >= 0) wg_fence();
                wg80(d, descA + slot * 2048 + k * 128, 0x10000u + (SB0 + OFF_T) / 16 + (Q & 3) * 640 + k * 2, st == -2 ? k != 0 : st == -3 || ((Q & 3) | k) != 0);
                if (st >= 0) {
#pragma unroll
                    for (int j = st + k; j < st + k + 1; j++)
                        if (j < 20) asm volatile("st.global.u32 [%0],%1;" ::"l"(hp + (j >> 1) * 32 + (j & 1) * (NN * 4)), "r"(pk[j]) : "memory");
                }
            }
            wg_commit();
        };
        auto mma_q = [&](int Q, int slot, int st) { mma_k(Q, slot, st, 0, 4); };
        auto mma_head = [&](int Q, int slot, int st) { mma_k(Q, slot, st, 0, KH); wg_wait<1>(); };
        auto mma_tail = [&](int Q, int slot, int st) { mma_k(Q, slot, st, KH, 4); };
        const uint4* xl = x + lane;
        auto eidx = [&](int i) { return lds128(sb + OFF_EIDX + (w * 5 + i) * 16); };
        auto gather = [&](const uint4& ix, int slot) {
            cp16(greg + slot * 32768, xl + ix.x * 32u); cp16(greg + slot * 32768 + 512, xl + ix.y * 32u);
            cp16(greg + slot * 32768 + 1024, xl + ix.z * 32u); cp16(greg + slot * 32768 + 1536, xl + ix.w * 32u);
            cp_commit();
        };
        const uint4 ix0 = eidx(0), ix1 = eidx(1), ix2 = eidx(2), ix3 = eidx(3), ix4 = eidx(4);
        uint4 gv[5][4];
        const unsigned gld = sb + OFF_S + w * 2048 + ((lane >> 3) & 1) * 512 + (lane >> 4) * 128 + (lane & 7) * 16;
        auto to_regs = [&](int i, int slot) {
            __syncwarp();
#pragma unroll
            for (int j = 0; j < 4; j++) gv[i][j] = ldsm4(gld + slot * 32768 + (j & 1) * 256 + (j >> 1) * 1024);
        };
        float ds[20];
#pragma unroll
        for (int j = 0; j < 10; j++) { const unsigned v = lds32(sb + OFF_DIS + (4 * j + t) * 4); ds[2 * j] = blo_v(v); ds[2 * j + 1] = bhi_v(v); }
        STAMPT(288, 2);
        mbar_wait(bar_full);
        STAMPT(288, 3);
        mma_q(0, 0, -1);
        mbar_wait(bar_full + 8);
        STAMPT(288, 50);
        mma_q(1, 1, -1);
        mbar_wait(bar_full + 16);
        STAMPT(288, 51);
        mma_head(2, 2, -1);
        EV(5);
        mma_tail(2, 2, -1);
        mbar_wait(bar_full + 24);
        STAMP(5);
        mma_q(3, 3, -1);
        mbar_wait(bar_go);
        gather(ix0, 4);
        wg_wait<0>();
        EV(6);
        STAMP(6);
#pragma unroll
        for (int j = 0; j < 20; j++) pk[j] = movm(pack2(d[2 * j] * ds[2 * (j >> 1)], d[2 * j + 1] * ds[2 * (j >> 1) + 1]));
#pragma unroll
        for (int j = 0; j < STPRE; j++) asm volatile("st.global.u32 [%0],%1;" ::"l"(hp + (j >> 1) * 32 + (j & 1) * (NN * 4)), "r"(pk[j]) : "memory");
        STAMP(7);
        nb_sync_id(8 + wg, 128);
        if (G1POS == 0) gather(ix1, 2);
        mbar_wait(bar_full + 32);
        if (G1POS == 1) gather(ix1, 2);
        STAMP(21);
        mma_q(4, 0, STPRE);
        STAMP(28);
        mbar_wait(bar_full + 40);
        mma_head(5, 1, STPRE + 4);
        EV(7);
        mma_tail(5, 1, STPRE + 4);
        STAMP(29);
        mbar_wait(bar_full + 48);
        STAMP(30);
        mma_head(6, 3, STPRE + 8);
        nb_sync_id(8 + wg, 128);
        gather(ix2, 1);
        mma_tail(6, 3, STPRE + 8);
        STAMP(31);
        mbar_wait(bar_full + 56);
        STAMP(32);
        mma_head(7, 0, STPRE + 12);
        nb_sync_id(8 + wg, 128);
        gather(ix3, 3);
        mma_tail(7, 0, STPRE + 12);
        EV(12);
        wg_wait<0>();
        STAMP(20);
        pack_acc(pk, d);
        nb_sync<0, 512>();
        acc_to_tile(pk, w, lane);
        gather(ix4, 0);
        cp_wait<3>();
        to_regs(0, 4);
        nb_sync<0, 512>();
        STAMP(8);
        uint4 vf[8];
        {
            const unsigned delta = t ^ (g >> 1), alsm = sb + OFF_ALPHA + w * 128;
            const bool par = g & 1;
            unsigned ta[5];
#pragma unroll
            for (int i = 0; i < 5; i++) ta[i] = tile_addr(w * 5 + i, lane);
            float v[4], u[4];
            to_regs(1, 2);
            EV(14);
            attn_scores(v, true, par, gv[0], ta[0]);
            attn_scores(v, delta == 1, par, gv[1], ta[1] ^ 32);
            cp_wait<2>();
            to_regs(2, 1);
            attn_scores(v, delta == 2, par, gv[2], ta[2] ^ 64);
            STAMP(33);
            cp_wait<1>();
            to_regs(3, 3);
            EV(15);
            STAMP(34);
            attn_scores(v, delta == 3, par, gv[3], ta[3] ^ 96);
            cp_wait<0>();
            to_regs(4, 0);
            STAMP(35);
            attn_scores(u, true, par, gv[4], ta[4]);
            attn_softmax(v, u, lane, alsm + ((lane & 4) + delta) * 16 + (lane >> 3) * 4);
            STAMP(49);
            const unsigned va = sb + OFF_S + wg * 8192 + ((lane & 7) + (lane >> 4) * 8) * 128 + (((2 * (w & 3) + ((lane >> 3) & 1)) ^ (lane & 7)) << 4);
            if (VRS > 0) mbar_wait(bar_full + 64);
            if (VRS > 1) mbar_wait(bar_full + 72);
            uint4 al = lds128(alsm);
#pragma unroll
            for (int i = 0; i < 5; i++) {
                const uint4 a = al;
                if (i < 4) al = lds128(alsm + (i + 1) * 16);
                attn_mix(gv[i], a, ta[i]);
                if (i >= 1 && i <= VRS) {
#pragma unroll
                    for (int k = 0; k < 4; k++) vf[4 * (i - 1) + k] = ldsm4t(va + (i == 1 ? 4 : 2) * 32768 + k * 2048);
                }
            }
        }
        STAMP(36);
        mbar_wait(bar_full + 80);
        fence_async_smem();
        STAMP(22);
        EV(2);
        nb_sync<0, 512>();
        mma_k(10, 1, -2, 0, 4);
        mbar_wait(bar_full + 88);
        mma_head(11, 3, -1);
        EV(4);
        mma_tail(11, 3, -1);
        auto mma_r = [&](int k0, int k1) {
            wg_fence();
#pragma unroll
            for (int k = k0; k < k1; k++) wg80r(d, vf[k], 0x10000u + (SB0 + OFF_T) / 16 + (k >> 2) * 640 + (k & 3) * 2);
            wg_commit();
        };
        if (VRS < 2) {
            mbar_wait(bar_full + 72);
            mma_head(9, 2, -1);
            EV(5);
            mma_tail(9, 2, -1);
        } else {
            mma_r(4, 5); wg_wait<1>(); EV(5); mma_r(5, 8);
        }
        if (VRS < 1) {
            mbar_wait(bar_full + 64);
            mma_k(8, 4, -3, 0, KH); wg_wait<1>();
            EV(6);
            mma_tail(8, 4, -1);
        } else if (VRS == 1) {
            mma_r(0, 1); wg_wait<1>(); EV(6); mma_r(1, 4);
        } else {
            mma_r(0, 4);
        }
        mbar_wait(bar_c);
        L0 = ldg_na(lp); L1 = ldg_na(lp + LSTR);
        wg_wait<0>();
        if (VRS < 1) EV(7);
        STAMP(9);
        pack_acc(pk, d);
        nb_sync<0, 512>();
        STAMP(10);
        if (__builtin_expect(lds32(sb + OFF_MISC + 28) & 2, 0)) {
            for (int i = 0; i < 5; i++) sts128(tile_addr(w * 5 + i, lane), attn_generic(b * TILE + w * 5 + i, x, esrc, edst, wq, wk, wv));
        } else {
            acc_to_tile(pk, w, lane);
        }
        EV(12);
    } else {
        mbar_wait(bar_c);
        L0 = ldg_na(lp); L1 = ldg_na(lp + LSTR);
    }

    const unsigned flags = lds32(sb + OFF_MISC + 28);
    const bool anyovf = flags & 1;
    const unsigned zero = flags >> 8;
    const unsigned selA = 0x4140 + zero, selB = 0x4342 + zero, m128 = 0x80000080u + zero;
    if (lane < 8) sts128(sb + OFF_S + NN * 16 + lane * 16, make_uint4(0, 0, 0, 0));
    const unsigned lb = sb + OFF_S + (lane & 7) * 16;
    const unsigned dummy = anyovf ? 0 : lb + 1250 * 128;
    const float zmask = (lane >= 28) ? 0.f : -1.f;
    unsigned stg = sb + OFF_STG + w * 256 + (((lane & 7) * 2 + ((lane >> 3) & 1)) ^ ((lane >> 2) & 1)) * 16;
    unsigned rdb = bar_rd;
    const unsigned rde = bar_rd + 8 * ((g1 - grp0 + 15) >> 4);
    __syncwarp();
    mbar_wait(bar_fill);
    STAMP(11);
    CLK0(64);
    struct Dec { unsigned ad[12], sA, nB; float dA, dB; };
    auto decode = [&](Dec& D, const uint4& L0, const uint4& L1) {
        D.ad[0] = dp2lo(L0.z, m128, lb); D.ad[1] = dp2hi(L0.z, m128, lb); D.ad[2] = dp2lo(L0.w, m128, lb); D.ad[3] = dp2hi(L0.w, m128, lb);
        D.ad[4] = dp2lo(L1.x, m128, lb); D.ad[5] = dp2hi(L1.x, m128, lb); D.ad[6] = dp2lo(L1.y, m128, lb); D.ad[7] = dp2hi(L1.y, m128, lb);
        D.ad[8] = dp2lo(L1.z, m128, lb); D.ad[9] = dp2hi(L1.z, m128, lb); D.ad[10] = dp2lo(L1.w, m128, lb); D.ad[11] = dp2hi(L1.w, m128, lb);
        asm volatile("prmt.b32 %0,%1,0x64646464,%2;" : "=r"(D.sA) : "r"(L0.x), "r"(selA));
        asm volatile("prmt.b32 %0,%1,0xE4E4E4E4,%2;" : "=r"(D.nB) : "r"(L0.x), "r"(selB));
        D.dA = blo_v(L0.y); D.dB = bhi_v(L0.y);
    };
    auto group = [&](Dec& D) {
            unsigned* ad = D.ad;
            const unsigned sA = D.sA, nB = D.nB;
            const float dA = D.dA, dB = D.dB;
            const unsigned p9 = __any_sync(~0u, ad[9] != dummy), p10 = __any_sync(~0u, ad[10] != dummy);
            uint4 C2;
            asm volatile("{.reg .pred p; setp.ne.u32 p,%5,0; @p ld.global.L1::no_allocate.v4.u32 {%0,%1,%2,%3},[%4];}"
                         : "=r"(C2.x), "=r"(C2.y), "=r"(C2.z), "=r"(C2.w) : "l"(lp + 2 * LSTR), "r"(ad[11] & 0x400000) : "memory");
            float acc0[4] = {0, 0, 0, 0}, acc1[4] = {0, 0, 0, 0};
            uint4 v[11], a0, a1;
            float acc2[4] = {0, 0, 0, 0}, acc3[4] = {0, 0, 0, 0};
#pragma unroll
            for (int s = 0; s < LA; s++) v[s] = ldsm4t(ad[s]);
            a0 = p3_sel(0, sA, nB); a1 = p3_sel(1, sA, nB);
#pragma unroll
            for (int s = 0; s < 9; s++) {
                if (s % FENCE_EVERY == 0) sched_fence(zero);
                const uint4 n0 = p3_sel(2 * s + 2, sA, nB);
                mma16816(CHAINS == 4 ? ((s & 1) ? acc0 : acc2) : CHAINS == 3 ? ((2 * s) % 3 == 0 ? acc0 : (2 * s) % 3 == 1 ? acc1 : acc2) : acc0, a0.x, a0.y, a0.z, a0.w, v[s].x, v[s].y);
                if (s + LA < 9) v[s + LA] = ldsm4t(ad[s + LA]);
                else if (s + LA < 11) v[s + LA] = ldsm4t_if(ad[s + LA], s + LA == 9 ? p9 : p10);
                const uint4 n1 = p3_sel(2 * s + 3, sA, nB);
                mma16816(CHAINS == 4 ? ((s & 1) ? acc1 : acc3) : CHAINS == 3 ? ((2 * s + 1) % 3 == 0 ? acc0 : (2 * s + 1) % 3 == 1 ? acc1 : acc2) : acc1, a1.x, a1.y, a1.z, a1.w, v[s].z, v[s].w);
                a0 = n0; a1 = n1;
            }
            const uint4 v10 = v[10];
            if (p9) {
                mma16816(acc0, a0.x, a0.y, a0.z, a0.w, v[9].x, v[9].y);
                mma16816(acc1, a1.x, a1.y, a1.z, a1.w, v[9].z, v[9].w);
                if (p10) {
                    p3_mma(CHAINS > 2 ? acc2 : acc0, CHAINS == 4 ? acc3 : CHAINS == 3 ? acc0 : acc1, v10, 10, sA, nB);
                    if (__any_sync(~0u, ad[11] != dummy)) {
                        p3_mma(acc0, acc1, ldsm4t(ad[11] & ~0x400000u), 11, sA, nB);
                        if (__any_sync(~0u, (ad[11] & 0x400000) || anyovf)) {
                            if (anyovf) C2 = ldg_na(lp + 2 * LSTR);
                            const unsigned e2[4] = {C2.x, C2.y, C2.z, C2.w};
#pragma unroll
                            for (int s = 12; s < 20; s++) {
                                const unsigned a = (s & 1) ? dp2hi(e2[(s - 12) >> 1], m128, lb) : dp2lo(e2[(s - 12) >> 1], m128, lb);
                                if ((s == 13 || s == 14) && !__any_sync(~0u, a != dummy)) break;
                                p3_mma(acc0, acc1, ldsm4t(a), s, sA, nB);
                            }
                            if (anyovf) {
                                float4 e = p3_overflow(sc, grp0 + 2 * (rdb - bar_rd), sb + OFF_S);
                                float s0 = e.x + e.z, s1 = e.y + e.w;
                                for (int k = 4; k < 32; k <<= 1) {
                                    float u0 = __shfl_down_sync(~0u, s0, k), u1 = __shfl_down_sync(~0u, s1, k);
                                    if (lane + k < 32) { s0 += u0; s1 += u1; }
                                }
                                acc0[0] += s0; acc0[1] += s1; acc0[2] += s0 - e.x; acc0[3] += s1 - e.y;
                            }
                        }
                    }
                }
            }
            if (CHAINS == 4) { acc2[0] += acc3[0]; acc2[1] += acc3[1]; acc2[2] += acc3[2]; acc2[3] += acc3[3]; }
            float c0 = acc0[0] + acc1[0], c1 = acc0[1] + acc1[1], c2 = acc0[2] + acc1[2], c3 = acc0[3] + acc1[3];
            if (CHAINS > 2) { c0 += acc2[0]; c1 += acc2[1]; c2 += acc2[2]; c3 += acc2[3]; }
            float n0 = __shfl_down_sync(~0u, c0, 4), n1 = __shfl_down_sync(~0u, c1, 4);
            float o0 = c0 - c2, o1 = c1 - c3, o2 = fmaf(n0, zmask, c2), o3 = fmaf(n1, zmask, c3);
            asm volatile("stmatrix.sync.aligned.m8n8.x2.shared.b16 [%0],{%1,%2};" ::"r"(stg), "r"(pack2(o0 * dA, o1 * dA)), "r"(pack2(o2 * dB, o3 * dB)) : "memory");
            __syncwarp();
            asm volatile("{.reg .pred p; setp.eq.u32 p,%1,0; @p mbarrier.arrive.shared.b64 _,[%0];}" ::"r"(rdb), "r"(lane) : "memory");
            stg += 4096;
            rdb += 8;
            lp += 16 * 32;
    };
#pragma unroll 1
    while (true) {
        if (rdb == bar_rd + 48) mbar_wait(bar_t);
        Dec D0;
        decode(D0, L0, L1);
        L0 = ldg_na(lp + 16 * 32); L1 = ldg_na(lp + 16 * 32 + LSTR);
        group(D0);
        if (rdb == rde) break;
    }
    STAMP(12);
    CLK1(64, 60); STAMPT(0, 61); STAMPT(352, 62); STAMPT(480, 63);
    }
}

typedef CUresult (*EncodeFn)(CUtensorMap*, CUtensorMapDataType, cuuint32_t, void*, const cuuint64_t*, const cuuint64_t*,
                             const cuuint32_t*, const cuuint32_t*, CUtensorMapInterleave, CUtensorMapSwizzle,
                             CUtensorMapL2promotion, CUtensorMapFloatOOBfill);

}

extern "C" void kernel_launch(void* const* d_in, const int* in_sizes, int n_in, void* d_out, int out_size) {
    (void)in_sizes; (void)n_in; (void)out_size;
    static EncodeFn enc = nullptr;
    static void* scratch = nullptr;
    if (!enc) {
        cudaGetSymbolAddress(&scratch, g_scratch);
        void* fn = nullptr;
        cudaDriverEntryPointQueryResult qr;
        cudaGetDriverEntryPoint("cuTensorMapEncodeTiled", &fn, cudaEnableDefault, &qr);
        enc = (EncodeFn)fn;
        cudaFuncSetAttribute(exphormer_kernel, cudaFuncAttributeMaxDynamicSharedMemorySize, SMEM_BYTES);
    }
    CUtensorMap tm_m, tm_ms, tm_mail, tm_x, tm_wl, tm_wv, tm_ot, tm_o256, tm_o16;
    auto mk = [&](CUtensorMap* tm, void* p, int rows, int bc, int br, CUtensorMapSwizzle sw, CUtensorMapL2promotion pr) {
        cuuint64_t gd[2] = {256, (cuuint64_t)rows}, gs[1] = {512};
        cuuint32_t es[2] = {1, 1}, bx[2] = {(cuuint32_t)bc, (cuuint32_t)br};
        enc(tm, CU_TENSOR_MAP_DATA_TYPE_BFLOAT16, 2, p, gd, gs, bx, es, CU_TENSOR_MAP_INTERLEAVE_NONE, sw, pr, CU_TENSOR_MAP_FLOAT_OOB_FILL_NONE);
    };
    for (int i = 0; i < 3; i++) {
        cuuint64_t gd[3] = {64, 256, 4}, gs[2] = {512, 128};
        cuuint32_t es[3] = {1, 1, 1}, bx[3] = {64, 64, 4};
        enc(i == 2 ? &tm_m : i ? &tm_wv : &tm_wl, CU_TENSOR_MAP_DATA_TYPE_BFLOAT16, 3, i == 2 ? scratch : d_in[i ? 9 : 6], gd, gs, bx, es, CU_TENSOR_MAP_INTERLEAVE_NONE,
            CU_TENSOR_MAP_SWIZZLE_128B, CU_TENSOR_MAP_L2_PROMOTION_L2_128B, CU_TENSOR_MAP_FLOAT_OOB_FILL_NONE);
    }
    {
        cuuint64_t gd[2] = {2048, NT}, gs[1] = {8192};
        cuuint32_t es[2] = {1, 1}, bx[2] = {16, NT};
        enc(&tm_mail, CU_TENSOR_MAP_DATA_TYPE_UINT32, 2, ((Scratch*)scratch)->mail, gd, gs, bx, es, CU_TENSOR_MAP_INTERLEAVE_NONE,
            CU_TENSOR_MAP_SWIZZLE_NONE, CU_TENSOR_MAP_L2_PROMOTION_NONE, CU_TENSOR_MAP_FLOAT_OOB_FILL_NONE);
    }
    mk(&tm_ms, scratch, 256, 32, 16, CU_TENSOR_MAP_SWIZZLE_NONE, CU_TENSOR_MAP_L2_PROMOTION_NONE);
    mk(&tm_x, d_in[0], NN, 64, TILE, CU_TENSOR_MAP_SWIZZLE_128B, CU_TENSOR_MAP_L2_PROMOTION_L2_128B);
    mk(&tm_ot, d_out, NN, 64, TILE, CU_TENSOR_MAP_SWIZZLE_128B, CU_TENSOR_MAP_L2_PROMOTION_NONE);
    mk(&tm_o256, d_out, NN, 8, 256, CU_TENSOR_MAP_SWIZZLE_NONE, CU_TENSOR_MAP_L2_PROMOTION_NONE);
    mk(&tm_o16, d_out, NN, 8, 16, CU_TENSOR_MAP_SWIZZLE_NONE, CU_TENSOR_MAP_L2_PROMOTION_NONE);
    exphormer_kernel<<<NCTA, 640, SMEM_BYTES>>>(
        (const uint4*)d_in[0], (const uint4*)d_in[2], (const uint4*)d_in[1], (const uint4*)d_in[7], (const uint4*)d_in[8], (const int*)d_in[3],
        (const int*)d_in[4], (Scratch*)scratch, (const uint4*)d_in[5], (const uint4*)d_in[9],
        tm_x, tm_wl, tm_wv, tm_m, tm_ms, tm_mail, tm_ot, tm_o256, tm_o16);
}
```

```cpp
#include <cuda_runtime.h>
#include <cuda_bf16.h>
#include <cuda.h>
#include <stdint.h>

namespace {

constexpr int NN = 10000, NE = 160000, NEE = 40000;
constexpr int TILE = 80, NT = 125, NCTA = 128, NG = 625, EPC = 1280;
constexpr int CELL = 32;
constexpr int LCAP = 80;
constexpr int OVCAP = EPC + NT * CELL;
#define XD0 700
#define XD1 1100
#define XD2 1900
#define REG_W 104
#define REG_H 64
#define KH 1
#define POLLNS 0
#define STPRE 4
#define G0POS 1
#define G1POS 1
#define GATE2 0
#define LA 3
#define FENCE_EVERY 1
#define CHAINS 2
#define ED0 0
#define VRS 0
#define POLL2 0
#define SELMODE 1
#define M128UR 0
#define PACE 650
#define PBOX 256
constexpr unsigned DUMMY2 = 1250u | (1250u << 16);

constexpr unsigned SB0 = 1024;
constexpr unsigned sb = SB0;
constexpr int OFF_S = 0;
constexpr int OFF_R = 163840;
constexpr int OFF_BAR = OFF_R;
constexpr int OFF_MISC = OFF_R + 256;
constexpr int OFF_DIS = OFF_R + 320;
constexpr int OFF_PROF = OFF_R + 512;
constexpr int OFF_EIDX = OFF_R + 1024;
constexpr int OFF_ALPHA = OFF_R + 1024;
constexpr int OFF_STG = OFF_R + 3072;
constexpr int OFF_CNT1 = OFF_R + 2560;
constexpr int OFF_CNT2 = OFF_R + 3072;
constexpr int OFF_MAIL = OFF_R + 5760;
constexpr int OFF_IMG = OFF_MAIL + 9216;
constexpr int OFF_T = OFF_R + 27648;
constexpr int SMEM_BYTES = OFF_T + 40960;
static_assert(SMEM_BYTES <= 232448 && OFF_T % 1024 == 0 && OFF_STG + 3 * 8192 == OFF_T && OFF_IMG + 10752 <= OFF_T, "smem");
#define bar_fill (sb + OFF_BAR)
#define bar_t (sb + OFF_BAR + 8)
#define bar_mail (sb + OFF_BAR + 16)
#define bar_c (sb + OFF_BAR + 24)
#define bar_rd (sb + OFF_BAR + 32)
#define bar_go (sb + OFF_BAR + 112)
#define bar_am (sb + OFF_BAR + 216)
#define bar_full (sb + OFF_BAR + 120)
constexpr int LSTR = (NG + 48) * 32;

struct __align__(256) Scratch {
    uint4 mimg[8192];
    uint4 hs[32 * NN];
    uint4 mail[2 * NT * 512];
    uint4 lists[3 * LSTR];
    uint2 ovfn[NCTA];
    unsigned bar[5 * 64];
    unsigned ovf[NCTA * OVCAP];
};
__device__ Scratch g_scratch;
#define STAMPT(th, i)
#define CLK0(th)
#define CLK1(th, i)
#define STAMP(i) STAMPT(64, i)
#define STAMP2(i) STAMPT(416, i)

extern __shared__ __align__(1024) unsigned char smem_raw[];
__device__ __forceinline__ void bar_arrive(unsigned* p) {
    asm volatile("red.release.gpu.global.add.u32 [%0],1;" ::"l"(p) : "memory");
}
__device__ __forceinline__ void bar_arrive_relaxed(unsigned* p) {
    asm volatile("red.relaxed.gpu.global.add.u32 [%0],1;" ::"l"(p) : "memory");
}
__device__ __forceinline__ void bar_poll(const Scratch* sc, int i) {
    unsigned v, target;
    int lim = 0;
    asm volatile("ld.shared.u32 %0,[%1];" : "=r"(target) : "r"(sb + OFF_MISC + 32 + 4 * i) : "memory");
    while (true) {
        asm volatile("ld.acquire.gpu.global.u32 %0,[%1];" : "=r"(v) : "l"(&sc->bar[i * 64]) : "memory");
        if ((int)(v - target) >= 0) break;
        if (++lim > (1 << 22)) __trap();
        if (POLLNS) __nanosleep(POLLNS);
    }
}
__device__ __forceinline__ unsigned bar_poll2(const unsigned* p, unsigned target) {
    unsigned long long v;
    int lim = 0;
    do {
        asm volatile("ld.acquire.gpu.global.u64 %0,[%1];" : "=l"(v) : "l"(p) : "memory");
        if (++lim > (1 << 22)) __trap();
    } while ((int)((unsigned)v - target) < 0);
    unsigned f = (unsigned)(v >> 32);
    return (f & ~3u) == target ? f & 3 : 0;
}
__device__ __noinline__ void raise_flag(unsigned* p, unsigned target, unsigned bit) {
    unsigned old = atomicCAS(p, 0, 0), seen;
    do {
        seen = old;
        old = atomicCAS(p, seen, ((seen & ~3u) == target ? seen : target) | bit);
    } while (old != seen);
}
__device__ __forceinline__ void mbar_wait(unsigned a) {
    asm volatile("{.reg .pred p; .reg .u32 n;\n"
                 "mov.u32 n,0x400000;\n"
                 "W: mbarrier.try_wait.parity.shared.b64 p,[%0],0;\n"
                 "add.u32 n,n,-1; setp.ne.and.u32 p,n,0,!p; @p bra W;}" ::"r"(a) : "memory");
}
__device__ __forceinline__ bool elect() {
    unsigned r;
    asm volatile("{.reg .pred p; elect.sync _|p,0xFFFFFFFF; selp.u32 %0,1,0,p;}" : "=r"(r));
    return r;
}
__device__ __forceinline__ uint4 ldg_na(const uint4* p) {
    uint4 v;
    asm volatile("ld.global.L1::no_allocate.v4.u32 {%0,%1,%2,%3},[%4];" : "=r"(v.x), "=r"(v.y), "=r"(v.z), "=r"(v.w) : "l"(p) : "memory");
    return v;
}
__device__ __forceinline__ uint4 lds128(unsigned a) {
    uint4 v;
    asm volatile("ld.shared.v4.u32 {%0,%1,%2,%3},[%4];" : "=r"(v.x), "=r"(v.y), "=r"(v.z), "=r"(v.w) : "r"(a) : "memory");
    return v;
}
__device__ __forceinline__ uint4 ldsm4(unsigned a) {
    uint4 v;
    asm volatile("ldmatrix.sync.aligned.m8n8.x4.shared.b16 {%0,%1,%2,%3},[%4];" : "=r"(v.x), "=r"(v.y), "=r"(v.z), "=r"(v.w) : "r"(a) : "memory");
    return v;
}
__device__ __forceinline__ void sts128(unsigned a, uint4 v) {
    asm volatile("st.shared.v4.u32 [%0],{%1,%2,%3,%4};" ::"r"(a), "r"(v.x), "r"(v.y), "r"(v.z), "r"(v.w) : "memory");
}
__device__ __forceinline__ void sts32(unsigned a, unsigned v) { asm volatile("st.shared.u32 [%0],%1;" ::"r"(a), "r"(v) : "memory"); }
__device__ __forceinline__ unsigned lds32(unsigned a) { unsigned v; asm volatile("ld.shared.u32 %0,[%1];" : "=r"(v) : "r"(a) : "memory"); return v; }
__device__ __forceinline__ unsigned atoms_add(unsigned a, unsigned k) { unsigned v; asm volatile("atom.shared.add.u32 %0,[%1],%2;" : "=r"(v) : "r"(a), "r"(k) : "memory"); return v; }
__device__ __forceinline__ unsigned bitsel(unsigned a, unsigned b, unsigned m) { unsigned r; asm("lop3.b32 %0,%1,%2,%3,0xE4;" : "=r"(r) : "r"(a), "r"(b), "r"(m)); return r; }
__device__ __forceinline__ unsigned atoms_inc(unsigned a) { unsigned v; asm volatile("atom.shared.add.u32 %0,[%1],1;" : "=r"(v) : "r"(a) : "memory"); return v; }
__device__ __forceinline__ float blo(unsigned v) { return __uint_as_float(v << 16); }
__device__ __forceinline__ float bhi(unsigned v) { return __uint_as_float(v & 0xFFFF0000u); }
__device__ __forceinline__ float blo_v(unsigned v) { float r; asm volatile("shl.b32 %0,%1,16;" : "=f"(r) : "r"(v)); return r; }
__device__ __forceinline__ float bhi_v(unsigned v) { float r; asm volatile("and.b32 %0,%1,0xFFFF0000;" : "=f"(r) : "r"(v)); return r; }
__device__ __forceinline__ unsigned pack2(float lo, float hi) { unsigned r; asm("cvt.rn.bf16x2.f32 %0,%1,%2;" : "=r"(r) : "f"(hi), "f"(lo)); return r; }

__device__ __forceinline__ void mma16816(float* d, unsigned a0, unsigned a1, unsigned a2, unsigned a3, unsigned b0, unsigned b1) {
    asm volatile("mma.sync.aligned.m16n8k16.row.col.f32.bf16.bf16.f32 {%0,%1,%2,%3},{%4,%5,%6,%7},{%8,%9},{%0,%1,%2,%3};"
                 : "+f"(d[0]), "+f"(d[1]), "+f"(d[2]), "+f"(d[3]) : "r"(a0), "r"(a1), "r"(a2), "r"(a3), "r"(b0), "r"(b1));
}
#define R10(b) "+f"(d[b + 0]), "+f"(d[b + 1]), "+f"(d[b + 2]), "+f"(d[b + 3]), "+f"(d[b + 4]), "+f"(d[b + 5]), "+f"(d[b + 6]), "+f"(d[b + 7]), "+f"(d[b + 8]), "+f"(d[b + 9])
__device__ __forceinline__ void wg80(float* d, unsigned da, unsigned db, int sc) {
    asm volatile("{.reg .pred p; .reg .b64 a, b; setp.ne.b32 p,%42,0; mov.b64 a,{%40,%43}; mov.b64 b,{%41,%43};\n"
                 "wgmma.mma_async.sync.aligned.m64n80k16.f32.bf16.bf16 "
                 "{%0,%1,%2,%3,%4,%5,%6,%7,%8,%9,%10,%11,%12,%13,%14,%15,%16,%17,%18,%19,%20,%21,%22,%23,%24,%25,%26,%27,%28,%29,%30,%31,%32,%33,%34,%35,%36,%37,%38,%39},"
                 "a,b,p,1,1,1,0;}"
                 : R10(0), R10(10), R10(20), R10(30) : "r"(da), "r"(db), "r"(sc), "r"(0x40000040));
}
__device__ __forceinline__ void wg80r(float* d, const uint4& a, unsigned db) {
    asm volatile("{.reg .b64 b; mov.b64 b,{%44,%45};\n"
                 "wgmma.mma_async.sync.aligned.m64n80k16.f32.bf16.bf16 "
                 "{%0,%1,%2,%3,%4,%5,%6,%7,%8,%9,%10,%11,%12,%13,%14,%15,%16,%17,%18,%19,%20,%21,%22,%23,%24,%25,%26,%27,%28,%29,%30,%31,%32,%33,%34,%35,%36,%37,%38,%39},"
                 "{%40,%41,%42,%43},b,1,1,1,0;}"
                 : R10(0), R10(10), R10(20), R10(30) : "r"(a.x), "r"(a.y), "r"(a.z), "r"(a.w), "r"(db), "r"(0x40000040));
}
__device__ __forceinline__ void wg_fence() { asm volatile("wgmma.fence.sync.aligned;" ::: "memory"); }
__device__ __forceinline__ void wg_commit() { asm volatile("wgmma.commit_group.sync.aligned;" ::: "memory"); }
template <int N> __device__ __forceinline__ void wg_wait() { asm volatile("wgmma.wait_group.sync.aligned %0;" ::"n"(N) : "memory"); }
__device__ __forceinline__ void bulk_g2s(unsigned dst, const void* src, unsigned bytes, unsigned bar) {
    asm volatile("cp.async.bulk.shared::cluster.global.mbarrier::complete_tx::bytes [%0],[%1],%2,[%3];" ::"r"(dst), "l"(src), "r"(bytes), "r"(bar) : "memory");
}
__device__ __forceinline__ void fence_async_smem() { asm volatile("fence.proxy.async.shared::cta;" ::: "memory"); }
__device__ __forceinline__ void fence_async_gmem() { asm volatile("fence.proxy.async.global;" ::: "memory"); }

__device__ __forceinline__ unsigned hsat(unsigned a, unsigned c) { unsigned r; asm("add.sat.f16x2 %0,%1,%2;" : "=r"(r) : "r"(a), "r"(c)); return r; }
__device__ __forceinline__ unsigned hset(unsigned a, unsigned c) { unsigned r; asm("set.le.f16x2.f16x2 %0,%1,%2;" : "=r"(r) : "r"(a), "r"(c)); return r; }
__host__ __device__ constexpr unsigned h2c(int v) { return (0x6400u | v) | ((0x6400u | v) << 16); }
__device__ __forceinline__ unsigned dp2lo(unsigned a, unsigned m, unsigned c) { unsigned r; asm volatile("dp2a.lo.u32.u32 %0,%1,%2,%3;" : "=r"(r) : "r"(a), "r"(m), "r"(c)); return r; }
__device__ __forceinline__ unsigned dp2hi(unsigned a, unsigned m, unsigned c) { unsigned r; asm volatile("dp2a.hi.u32.u32 %0,%1,%2,%3;" : "=r"(r) : "r"(a), "r"(m), "r"(c)); return r; }
__device__ __forceinline__ uint4 ldsm4t(unsigned addr) {
    uint4 v;
    asm volatile("ldmatrix.sync.aligned.m8n8.x4.trans.shared.b16 {%0,%1,%2,%3},[%4];" : "=r"(v.x), "=r"(v.y), "=r"(v.z), "=r"(v.w) : "r"(addr));
    return v;
}
__device__ __forceinline__ uint4 ldsm4t_if(unsigned addr, unsigned p) {
    uint4 v;
    asm volatile("{.reg .pred p; setp.ne.u32 p,%5,0; @p ldmatrix.sync.aligned.m8n8.x4.trans.shared.b16 {%0,%1,%2,%3},[%4];}"
                 : "=r"(v.x), "=r"(v.y), "=r"(v.z), "=r"(v.w) : "r"(addr), "r"(p));
    return v;
}
__device__ __forceinline__ void p3_mma(float* acc0, float* acc1, const uint4& v, int s, unsigned sA, unsigned nB) {
    mma16816(acc0, hset(sA, h2c(4 * s + 0)), hsat(nB, h2c(4 * s + 1)), hset(sA, h2c(4 * s + 1)), hsat(nB, h2c(4 * s + 2)), v.x, v.y);
    mma16816(acc1, hset(sA, h2c(4 * s + 2)), hsat(nB, h2c(4 * s + 3)), hset(sA, h2c(4 * s + 3)), hsat(nB, h2c(4 * s + 4)), v.z, v.w);
}
__device__ __forceinline__ void sched_fence(unsigned zero) { asm volatile("{.reg .pred p; setp.ne.u32 p,%0,0; @p exit;}" ::"r"(zero)); }
__device__ __forceinline__ uint4 p3_sel(int i, unsigned sA, unsigned nB) {
    uint4 a;
    asm volatile("set.le.f16x2.f16x2 %0,%4,%6;\n sub.sat.f16x2 %2,%8,%4;\n set.ge.f16x2.f16x2 %1,%5,%7;\n add.sat.f16x2 %3,%5,%8;"
                 : "=r"(a.x), "=r"(a.y), "=r"(a.z), "=r"(a.w) : "r"(sA), "r"(nB), "r"(h2c(2 * i)), "r"(h2c(2 * i) | 0x80008000u), "r"(h2c(2 * i + 2)));
    return a;
}
__device__ __noinline__ float4 p3_overflow(const Scratch* sc, int grp, unsigned sS) {
    const unsigned tag = lds32(sb + OFF_MISC + 48);
    int lane = threadIdx.x & 31, g = lane >> 2, t = lane & 3;
    float4 r = make_float4(0.f, 0.f, 0.f, 0.f);
    for (int c = 0; c < NT; c++) {
        const uint2 tn = __ldcg(&sc->ovfn[c]);
        const int n = tn.x == tag ? (int)tn.y : 0;
        for (int i0 = 0; i0 < n; i0 += 32) {
            unsigned e = (i0 + lane < n) ? __ldcg(&sc->ovf[c * OVCAP + i0 + lane]) : 0xFFFFFFFFu;
            unsigned m = __ballot_sync(~0u, (int)(e >> 18) == grp);
            while (m) {
                int j = __ffs(m) - 1;
                m &= m - 1;
                unsigned ee = __shfl_sync(~0u, e, j);
                int row = (ee >> 14) & 15;
                row ^= row >> 3;
                unsigned v = lds32(sS + (ee & 0x3FFF) * 16 + t * 4);
                if ((row >> 1) == g) {
                    if (!(row & 1)) { r.x += blo(v); r.y += bhi(v); } else { r.z += blo(v); r.w += bhi(v); }
                }
            }
        }
    }
    const float k = 1.f / 128.f;
    r.x *= k; r.y *= k; r.z *= k; r.w *= k;
    return r;
}
__device__ __forceinline__ void unpack8(float* f, uint4 v) {
    f[0] = blo(v.x); f[1] = bhi(v.x); f[2] = blo(v.y); f[3] = bhi(v.y); f[4] = blo(v.z); f[5] = bhi(v.z); f[6] = blo(v.w); f[7] = bhi(v.w);
}
__device__ __forceinline__ void vec_mat(float* o, const float* v, const uint4* __restrict__ W, int lane) {
    for (int k = 0; k < 8; k++) o[k] = 0.f;
    for (int l = 0; l < 32; l++) {
#pragma unroll
        for (int i = 0; i < 8; i++) {
            float a = __shfl_sync(~0u, v[i], l), wr[8];
            unpack8(wr, W[(l * 8 + i) * 32 + lane]);
#pragma unroll
            for (int k = 0; k < 8; k++) o[k] = fmaf(a, wr[k], o[k]);
        }
    }
}
__device__ __noinline__ uint4 attn_generic(int node, const uint4* __restrict__ x, const int* __restrict__ esrc, const int* __restrict__ edst,
                                           const uint4* __restrict__ wq, const uint4* __restrict__ wk, const uint4* __restrict__ wv) {
    int lane = threadIdx.x & 31;
    float xr[8], q[8], y[8], o[8];
    unpack8(xr, x[node * 32 + lane]);
    vec_mat(q, xr, wq, lane);
    for (int l = 0; l < 32; l++) {
#pragma unroll
        for (int i = 0; i < 8; i++) {
            float wr[8], p = 0.f;
            unpack8(wr, wk[(l * 8 + i) * 32 + lane]);
#pragma unroll
            for (int k = 0; k < 8; k++) p = fmaf(q[k], wr[k], p);
            for (int k = 16; k; k >>= 1) p += __shfl_xor_sync(~0u, p, k);
            if (lane == l) y[i] = p;
        }
    }
    for (int k = 0; k < 8; k++) o[k] = 0.f;
    float den = 0.f;
    for (int i0 = 0; i0 < NEE; i0 += 32) {
        unsigned m = __ballot_sync(~0u, edst[i0 + lane] == node);
        while (m) {
            int j = __ffs(m) - 1;
            m &= m - 1;
            float gq[8], p = 0.f;
            unpack8(gq, x[esrc[i0 + j] * 32 + lane]);
#pragma unroll
            for (int k = 0; k < 8; k++) p = fmaf(y[k], gq[k], p);
            for (int k = 16; k; k >>= 1) p += __shfl_xor_sync(~0u, p, k);
            float ex = __expf(p * 0.0625f);
            den += ex;
#pragma unroll
            for (int k = 0; k < 8; k++) o[k] = fmaf(ex, gq[k], o[k]);
        }
    }
    float inv = 1.f / (den + 1e-9f);
    for (int k = 0; k < 8; k++) o[k] *= inv;
    vec_mat(q, o, wv, lane);
    return make_uint4(pack2(q[0], q[1]), pack2(q[2], q[3]), pack2(q[4], q[5]), pack2(q[6], q[7]));
}

__device__ __forceinline__ unsigned hfma2(unsigned a, unsigned b, unsigned c) { unsigned r; asm("fma.rn.bf16x2 %0,%1,%2,%3;" : "=r"(r) : "r"(a), "r"(b), "r"(c)); return r; }
__device__ __forceinline__ unsigned hmul2(unsigned a, unsigned b) { unsigned r; asm("mul.rn.bf16x2 %0,%1,%2;" : "=r"(r) : "r"(a), "r"(b)); return r; }

__device__ __forceinline__ unsigned tile_addr(int n, unsigned chunk) { return sb + OFF_T + (chunk >> 3) * 10240 + n * 128 + (((chunk ^ n) & 7) << 4); }
__device__ __forceinline__ void attn_scores(float* v, bool mine, bool par, const uint4* gv, unsigned yaddr) {
    const uint4 y = ldsm4(yaddr);
    float c[4] = {0, 0, 0, 0}, e[4] = {0, 0, 0, 0};
    mma16816(c, gv[0].x, gv[0].y, gv[0].z, gv[0].w, y.x, y.y);
    mma16816(e, gv[2].x, gv[2].y, gv[2].z, gv[2].w, y.x, y.y);
    mma16816(c, gv[1].x, gv[1].y, gv[1].z, gv[1].w, y.z, y.w);
    mma16816(e, gv[3].x, gv[3].y, gv[3].z, gv[3].w, y.z, y.w);
    if (mine) { v[0] = par ? c[1] : c[0]; v[1] = par ? c[3] : c[2]; v[2] = par ? e[1] : e[0]; v[3] = par ? e[3] : e[2]; }
}
__device__ __forceinline__ void attn_softmax(const float* v, const float* u, unsigned lane, unsigned aladdr) {
    const bool hA = lane & 4, hB = lane & 8, hC = lane & 16;
    float a[4];
#pragma unroll
    for (int e = 0; e < 4; e++) a[e] = (hA ? u[e] : v[e]) + __shfl_xor_sync(~0u, hA ? v[e] : u[e], 4);
    float b0 = (hB ? a[1] : a[0]) + __shfl_xor_sync(~0u, hB ? a[0] : a[1], 9);
    float b1 = (hB ? a[3] : a[2]) + __shfl_xor_sync(~0u, hB ? a[2] : a[3], 9);
    float sc = (hC ? b1 : b0) + __shfl_xor_sync(~0u, hC ? b0 : b1, 18);
    float ex, inv;
    asm("ex2.approx.ftz.f32 %0,%1;" : "=f"(ex) : "f"(sc));
    float den = ex + __shfl_xor_sync(~0u, ex, 9);
    den += __shfl_xor_sync(~0u, den, 18);
    asm("rcp.approx.ftz.f32 %0,%1;" : "=f"(inv) : "f"(den + 1e-9f));
    sts32(aladdr, pack2(ex * inv, ex * inv));
    __syncwarp();
}
__device__ __forceinline__ void attn_mix(const uint4* gv, const uint4& a, unsigned oaddr) {
    const unsigned o0 = hfma2(a.w, gv[2].y, hfma2(a.z, gv[2].x, hfma2(a.y, gv[0].y, hmul2(a.x, gv[0].x))));
    const unsigned o1 = hfma2(a.w, gv[2].w, hfma2(a.z, gv[2].z, hfma2(a.y, gv[0].w, hmul2(a.x, gv[0].z))));
    const unsigned o2 = hfma2(a.w, gv[3].y, hfma2(a.z, gv[3].x, hfma2(a.y, gv[1].y, hmul2(a.x, gv[1].x))));
    const unsigned o3 = hfma2(a.w, gv[3].w, hfma2(a.z, gv[3].z, hfma2(a.y, gv[1].w, hmul2(a.x, gv[1].z))));
    asm volatile("stmatrix.sync.aligned.m8n8.x4.shared.b16 [%0],{%1,%2,%3,%4};" ::"r"(oaddr), "r"(o0), "r"(o1), "r"(o2), "r"(o3) : "memory");
}
__device__ __forceinline__ void pack_acc(unsigned* pk, const float* d) {
#pragma unroll
    for (int j = 0; j < 20; j++) pk[j] = pack2(d[2 * j], d[2 * j + 1]);
}
__device__ __forceinline__ void acc_to_tile(const unsigned* pk, int w, int lane) {
    const unsigned a = sb + OFF_T + (w >> 2) * 10240 + (lane >> 4) * 1024 + (lane & 7) * 128 + (((2 * (w & 3) + ((lane >> 3) & 1)) ^ (lane & 7)) << 4);
#pragma unroll
    for (int j = 0; j < 5; j++)
        asm volatile("stmatrix.sync.aligned.m8n8.x4.trans.shared.b16 [%0],{%1,%2,%3,%4};" ::"r"(a + j * 2048), "r"(pk[4 * j]), "r"(pk[4 * j + 1]), "r"(pk[4 * j + 2]), "r"(pk[4 * j + 3]) : "memory");
}
__device__ __forceinline__ unsigned movm(unsigned a) { unsigned d; asm volatile("movmatrix.sync.aligned.m8n8.trans.b16 %0,%1;" : "=r"(d) : "r"(a)); return d; }
__device__ __forceinline__ void tma_load2d(unsigned dst, const CUtensorMap* tm, int c0, int c1, unsigned bar) {
    asm volatile("cp.async.bulk.tensor.2d.shared::cluster.global.mbarrier::complete_tx::bytes [%0],[%1,{%3,%4}],[%2];"
                 ::"r"(dst), "l"(tm), "r"(bar), "r"(c0), "r"(c1) : "memory");
}
__device__ __forceinline__ void tma_load3d(unsigned dst, const CUtensorMap* tm, int row, unsigned bar) {
    asm volatile("cp.async.bulk.tensor.3d.shared::cluster.global.mbarrier::complete_tx::bytes [%0],[%1,{%4,%3,%4}],[%2];"
                 ::"r"(dst), "l"(tm), "r"(bar), "r"(row), "r"(0) : "memory");
}
__device__ __forceinline__ void cp16(unsigned dst, const void* src) { asm volatile("cp.async.cg.shared.global [%0],[%1],16;" ::"r"(dst), "l"(src) : "memory"); }
__device__ __forceinline__ void cp_commit() { asm volatile("cp.async.commit_group;" ::: "memory"); }
template <int N> __device__ __forceinline__ void cp_wait() { asm volatile("cp.async.wait_group %0;" ::"n"(N) : "memory"); }
__device__ __forceinline__ void nb_sync_id(int id, int n) { asm volatile("bar.sync %0,%1;" ::"r"(id), "r"(n) : "memory"); }
__device__ __forceinline__ void nb_arrive_id(int id, int n) { asm volatile("bar.arrive %0,%1;" ::"r"(id), "r"(n) : "memory"); }
template <int ID, int N> __device__ __forceinline__ void nb_sync() { asm volatile("bar.sync %0,%1;" ::"n"(ID), "n"(N) : "memory"); }
template <int ID, int N> __device__ __forceinline__ void nb_arrive() { asm volatile("bar.arrive %0,%1;" ::"n"(ID), "n"(N) : "memory"); }
__device__ __forceinline__ void mbar_init(unsigned a, int n) { asm volatile("mbarrier.init.shared.b64 [%0],%1;" ::"r"(a), "r"(n) : "memory"); }
__device__ __forceinline__ void mbar_expect(unsigned a, int n) { asm volatile("mbarrier.arrive.expect_tx.shared.b64 _,[%0],%1;" ::"r"(a), "r"(n) : "memory"); }
__device__ __forceinline__ void mbar_arrive(unsigned a) { asm volatile("mbarrier.arrive.shared.b64 _,[%0];" ::"r"(a) : "memory"); }

constexpr unsigned PADBIN = 2560, CU = 0x101;
__device__ __noinline__ void push_overflow(Scratch* sc, unsigned dst, unsigned src) {
    sc->ovf[blockIdx.x * OVCAP + atoms_inc(sb + OFF_MISC)] = (dst << 14) | src;
}
__device__ __noinline__ void bin_overflow(Scratch* sc, unsigned mask, unsigned ht) {
    for (int i = 0; i < 24 + 6 * 16; i++) {
        unsigned e;
        if (i < 24) {
            if (!(mask >> i & 1)) continue;
            e = lds32(sb + OFF_MAIL + (ht + (i >> 2) * 96) * 16 + (i & 3) * 4) & 0x7FFFFFFFu;
        } else {
            const int k = (i - 24) >> 4;
            if (!(mask >> (24 + k) & 1)) continue;
            e = __ldcg((const unsigned*)(sc->mail + ((NT + blockIdx.x) * 512 + ((ht + k * 96) & ~3u))) + ((i - 24) & 15));
        }
        if (e < (PADBIN << 16))
            push_overflow(sc, blockIdx.x * TILE + ((e >> 21) & ~3u) + ((e >> 18) & 3), ((e & 2047) << 3) | ((e >> 20) & 7));
    }
}
__device__ __forceinline__ void place(unsigned e, unsigned h) {
    asm volatile("{.reg .pred p; setp.lt.u32 p,%2,%3; @p st.shared.u16 [%0],%1;}"
                 ::"r"(sb + OFF_IMG + bitsel(h >> 1, e >> 16, 0x318E)), "h"((unsigned short)e), "r"(h), "n"((LCAP + 16) * CU) : "memory");
}
__device__ __forceinline__ void bulk_s2g(void* dst, unsigned src, unsigned bytes) {
    asm volatile("cp.async.bulk.global.shared::cta.bulk_group [%0],[%1],%2;" ::"l"(dst), "r"(src), "r"(bytes) : "memory");
}
__device__ __forceinline__ void tma_reduce(const CUtensorMap* tm, unsigned src, int c0, int c1) {
    asm volatile("cp.reduce.async.bulk.tensor.2d.global.shared::cta.add.tile.bulk_group [%0,{%2,%3}],[%1];" ::"l"(tm), "r"(src), "r"(c0), "r"(c1) : "memory");
}
#define EV(id) nb_arrive<id, 544>()
#define WAIT_EV(id) do { __syncwarp(); nb_sync<id, 544>(); } while (0)

__global__ void __launch_bounds__(640, 1)
exphormer_kernel(const uint4* __restrict__ x, const uint4* __restrict__ dst4, const uint4* __restrict__ src4,
                 const uint4* __restrict__ wq, const uint4* __restrict__ wk, const int* __restrict__ esrc,
                 const int* __restrict__ edst, Scratch* __restrict__ sc, const uint4* __restrict__ dis, const uint4* __restrict__ wv,
                 const __grid_constant__ CUtensorMap tm_x, const __grid_constant__ CUtensorMap tm_wl, const __grid_constant__ CUtensorMap tm_wv,
                 const __grid_constant__ CUtensorMap tm_m, const __grid_constant__ CUtensorMap tm_ms,
                 const __grid_constant__ CUtensorMap tm_mail, const __grid_constant__ CUtensorMap tm_ot, const __grid_constant__ CUtensorMap tm_o256, const __grid_constant__ CUtensorMap tm_o16) {
    const unsigned tid = threadIdx.x, lane = tid & 31, g = lane >> 2, t = lane & 3;
    const unsigned b = blockIdx.x;
    const bool rowcta = b < NT;
    const int slice = b >> 2, range = b & 3;
    const int g0 = (range * NG) >> 2, g1 = ((range + 1) * NG) >> 2;
    STAMP(0);

    if (tid >= 512) {
    asm volatile("setmaxnreg.dec.sync.aligned.u32 %0;" ::"n"(REG_H));
    if (tid >= 544) {
        const unsigned ht = tid - 544;
        if (ht < 32) {
            if (lane == 0) asm volatile("prefetch.tensormap [%0];" ::"l"(&tm_mail) : "memory");
            __syncwarp();
            nb_sync<13, 160>();
            nb_sync<2, 352>();
            if (rowcta) {
                const uint4 c = lds128(sb + OFF_CNT1 + lane * 16);
                const unsigned cc[4] = {c.x, c.y, c.z, c.w};
#pragma unroll
                for (int i = 0; i < 4; i++)
                    if (cc[i] > 16) asm volatile("red.shared.or.b32 [%0],0x80000000;" ::"r"(sb + OFF_MAIL + (lane * 4 + i) * 64 + 60) : "memory");
                fence_async_smem();
                __syncwarp();
                if (elect())
                    asm volatile("cp.async.bulk.tensor.2d.global.shared::cta.bulk_group [%0,{%2,%3}],[%1];" ::"l"(&tm_mail), "r"(sb + OFF_MAIL), "r"(b * 16), "r"(0) : "memory");
                for (int i = 0; i < 4; i++)
                    if (lds32(sb + OFF_CNT1 + lane * 16 + i * 4) > 16) bulk_s2g(sc->mail + ((NT + lane * 4 + i) * 512 + b * 4), sb + OFF_IMG + (lane * 4 + i) * 64, 64);
                asm volatile("cp.async.bulk.commit_group;" ::: "memory");
                asm volatile("cp.async.bulk.wait_group 0;" ::: "memory");
                fence_async_gmem();
                __syncwarp();
            }
            if (rowcta) nb_arrive<1, 96>();
            if (elect()) {
                bar_arrive_relaxed(&sc->bar[0]);
                STAMPT(544, 47);
                if (rowcta) {
                    bar_poll(sc, 0);
                    fence_async_gmem();
                    mbar_expect(bar_mail, 8000);
                    bulk_g2s(sb + OFF_MAIL, sc->mail + b * 512, 8000, bar_mail);
                    if (GATE2) mbar_arrive(bar_go);
                }
            }
            __syncwarp();
        } else if (ht < 64) {
            if (lane == 0) asm volatile("prefetch.tensormap [%0];" ::"l"(&tm_ms) : "memory");
            nb_sync<14, 192>();
            if (elect()) {
                asm volatile("cp.async.bulk.tensor.2d.global.shared::cta.bulk_group [%0,{%2,%3}],[%1];" ::"l"(&tm_ms), "r"(sb + OFF_MAIL + 8064), "r"((b & 7) * 32), "r"((b >> 3) * 16) : "memory");
                asm volatile("cp.async.bulk.commit_group;" ::: "memory");
                asm volatile("cp.async.bulk.wait_group 0;" ::: "memory");
                fence_async_gmem();
                bar_arrive_relaxed(&sc->bar[3 * 64]);
                STAMPT(576, 46);
            }
            __syncwarp();
        } else {
            if (lane < 5) {
                unsigned epoch;
                asm volatile("ld.relaxed.gpu.global.u32 %0,[%1];" : "=r"(epoch) : "l"(&sc->bar[lane * 64]) : "memory");
                sts32(sb + OFF_MISC + 32 + lane * 4, (epoch & ~(NCTA - 1)) + NCTA);
            }
            if (lane == 5) sts32(sb + OFF_MISC + 56, 0);
            __syncwarp();
            nb_arrive<14, 192>();
            nb_arrive<15, 64>();
            nb_arrive<13, 160>();
        }
        if (rowcta) {
            if (ht >= 32) {
                nb_sync<1, 96>();
                const unsigned pad = (PADBIN + 4 * lane) << 16, h2 = ht - 32;
                sts128(sb + OFF_MAIL + 8000 + h2 * 16, make_uint4(pad, pad, pad, pad));
                if (h2 < 12) sts128(sb + OFF_MAIL + 9024 + h2 * 16, make_uint4(pad, pad, pad, pad));
#pragma unroll
                for (int k = 0; k < 9; k++) if (k % 3 < 2 || h2 < 32) sts128(sb + OFF_IMG + (k / 3) * 4096 + (k % 3) * 1024 + h2 * 16, make_uint4(DUMMY2, DUMMY2, DUMMY2, DUMMY2));
            }
            nb_sync<13, 96>();
            mbar_wait(bar_mail);
            STAMPT(576, 16);
            uint4 e[6], h[6];
            unsigned flagged = 0, late = 0, longg = 0;
#pragma unroll
            for (int k = 0; k < 6; k++) e[k] = lds128(sb + OFF_MAIL + (ht + k * 96) * 16);
#pragma unroll
            for (int k = 0; k < 6; k++) { flagged |= (e[k].w >> 31) << k; e[k].w &= 0x7FFFFFFFu; }
            while (flagged) {
                const unsigned f = __ffs(flagged) - 1, k = atoms_add(sb + OFF_MISC + 4, 4);
                const uint4* sp = sc->mail + ((NT + b) * 512 + ((ht + f * 96) & ~3u));
                flagged &= flagged - 1;
                if (k < 76) {
#pragma unroll
                    for (int j = 0; j < 4; j++) cp16(sb + OFF_MAIL + 8000 + (k + j) * 16, sp + j);
                } else {
                    late |= 1u << (24 + f);
                }
            }
            cp_commit();
            __syncwarp();
#pragma unroll
            for (int k = 0; k < 6; k++) {
                if (k == 5) { cp_wait<0>(); nb_sync<1, 96>(); if (ht >= 20) e[5] = lds128(sb + OFF_MAIL + (ht + 480) * 16); }
                h[k] = make_uint4(atoms_add(sb + OFF_CNT2 + (e[k].x >> 16), CU), atoms_add(sb + OFF_CNT2 + (e[k].y >> 16), CU),
                                  atoms_add(sb + OFF_CNT2 + (e[k].z >> 16), CU), atoms_add(sb + OFF_CNT2 + (e[k].w >> 16), CU));
            }
            nb_sync<1, 96>();
            STAMPT(576, 17);
            {
                const bool sw = lane >= 16;
                const unsigned G0 = ht >> 5, G1 = min(G0 + 3, 4u);
                uint4 c[2];
                unsigned inc[2], word[2], dp[2];
#pragma unroll
                for (int j = 0; j < 2; j++) c[j] = lds128(sb + OFF_CNT2 + (j ? G1 : G0) * 512 + lane * 16);
#pragma unroll
                for (int j = 0; j < 2; j++) dp[j] = lds32(sb + OFF_DIS + ((j ? G1 : G0) * 8 + g) * 4);
#pragma unroll
                for (int j = 0; j < 2; j++) { inc[j] = c[j].x + c[j].y + c[j].z + c[j].w; const unsigned u = __shfl_up_sync(~0u, inc[j], 8); if (lane >= 8) inc[j] += u; }
#pragma unroll
                for (int j = 0; j < 2; j++) { const unsigned u = __shfl_up_sync(~0u, inc[j], 16); if (sw) inc[j] += u; }
#pragma unroll
                for (int j = 0; j < 2; j++) {
                    const unsigned s2 = c[j].x + c[j].y, base = inc[j] - s2 - c[j].z - c[j].w;
                    const unsigned p0 = min(base, LCAP * CU), p1 = min(base + (sw ? c[j].y : c[j].x), LCAP * CU);
                    const unsigned p2 = min(base + s2, LCAP * CU), p3 = min(base + s2 + (sw ? c[j].w : c[j].z), LCAP * CU);
                    if (j == 0 || ht < 64)
                        sts128(sb + OFF_CNT2 + (j ? G1 : G0) * 512 + lane * 16,
                               make_uint4((sw ? p1 : p0) + 16 * CU, (sw ? p0 : p1) + 16 * CU, (sw ? p3 : p2) + 16 * CU, (sw ? p2 : p3) + 16 * CU));
                    word[j] = __byte_perm(__byte_perm(p0, p1, 0x0040), __byte_perm(p2, p3, 0x0040), 0x5410);
                }
                nb_sync<1, 96>();
#pragma unroll
                for (int j = 0; j < 2; j++) {
                    const unsigned wa = __shfl_sync(~0u, word[j], (g >> 1) * 8 + 2 * t), wb = __shfl_sync(~0u, word[j], (g >> 1) * 8 + 2 * t + 1);
                    const unsigned d128 = hmul2(dp[j], 0x43004300u);
                    if (j == 0 || ht < 64) {
                        asm volatile("st.shared.v2.u32 [%0],{%1,%2};" ::"r"(sb + OFF_IMG + (j ? G1 : G0) * 512 + lane * 16),
                                     "r"(__byte_perm(wa, wb, (g & 1) ? 0x7362 : 0x5140)), "r"(__byte_perm(d128, d128, sw ? 0x1032 : 0x3210)) : "memory");
                        if (__any_sync(~0u, inc[j] > 48 * CU)) longg |= 1u << (j ? G1 : G0);
                    }
                }
            }
            int hmax = 0;
#pragma unroll
            for (int k0 = 0; k0 < 6; k0 += 3) {
#pragma unroll
                for (int k = k0; k < k0 + 3; k++) { e[k] = lds128(sb + OFF_MAIL + (ht + k * 96) * 16); e[k].w &= 0x7FFFFFFFu; }
#pragma unroll
                for (int k = k0; k < k0 + 3; k++) {
                    h[k].x += lds32(sb + OFF_CNT2 + (e[k].x >> 16)); h[k].y += lds32(sb + OFF_CNT2 + (e[k].y >> 16));
                    h[k].z += lds32(sb + OFF_CNT2 + (e[k].z >> 16)); h[k].w += lds32(sb + OFF_CNT2 + (e[k].w >> 16));
                }
#pragma unroll
                for (int k = k0; k < k0 + 3; k++) {
                    place(e[k].x, h[k].x); place(e[k].y, h[k].y); place(e[k].z, h[k].z); place(e[k].w, h[k].w);
                    hmax = max(hmax, max(max((int)h[k].x, (int)h[k].y), max((int)h[k].z, (int)h[k].w)));
                }
            }
            if (__builtin_expect(hmax >= (int)((LCAP + 16) * CU), 0)) {
#pragma unroll
                for (int k = 0; k < 6; k++)
                    late |= ((h[k].x >= (LCAP + 16) * CU) | (h[k].y >= (LCAP + 16) * CU) << 1 | (h[k].z >= (LCAP + 16) * CU) << 2 | (h[k].w >= (LCAP + 16) * CU) << 3) << (4 * k);
            }
            if (__builtin_expect(late, 0)) bin_overflow(sc, late, ht);
            unsigned anylong;
            asm volatile("{.reg .pred p; setp.ne.u32 p,%1,0; bar.red.popc.u32 %0,1,96,p;}" : "=r"(anylong) : "r"(longg) : "memory");
            if (anylong) {
                for (; longg; longg &= longg - 1)
                    asm volatile("red.shared.or.b32 [%0],0x80000000;" ::"r"(sb + OFF_IMG + 4096 + (__ffs(longg) - 1) * 512 + lane * 16 + 12) : "memory");
                nb_sync<1, 96>();
            }
            STAMPT(576, 18);
        }
        if (ht < 32 && elect()) {
            if (rowcta) {
                fence_async_smem();
                for (int c = 0; c < 3; c++) bulk_s2g(sc->lists + (c * LSTR + b * 160), sb + OFF_IMG + c * 4096, 2560);
                asm volatile("cp.async.bulk.commit_group;" ::: "memory");
                const unsigned novf = lds32(sb + OFF_MISC), bad = lds32(sb + OFF_MISC + 20);
                if (__builtin_expect(novf | bad, 0)) {
                    sc->ovfn[b] = make_uint2(lds32(sb + OFF_MISC + 48), novf);
                    raise_flag(&sc->bar[4 * 64 + 1], lds32(sb + OFF_MISC + 48), (novf ? 1 : 0) | (bad ? 2 : 0));
                    __threadfence();
                }
                asm volatile("cp.async.bulk.wait_group 0;" ::: "memory");
                fence_async_gmem();
            }
            bar_arrive_relaxed(&sc->bar[4 * 64]);
            STAMPT(544, 19);
            sts32(sb + OFF_MISC + 28, bar_poll2(&sc->bar[4 * 64], lds32(sb + OFF_MISC + 48)));
            mbar_arrive(bar_c);
            STAMPT(544, 23);
        }
    } else {
        const bool one = elect();
        auto load_xl = [&](int i) {
            mbar_expect(bar_full + 8 * i, 32768 + 10240);
            tma_load2d(sb + OFF_T + i * 10240, &tm_x, i * 64, b * TILE, bar_full + 8 * i);
            tma_load3d(sb + OFF_S + i * 32768, &tm_wl, i * 64, bar_full + 8 * i);
        };
        auto load_m = [&](int i, int slot) {
            mbar_expect(bar_full + 32 + 8 * i, 32768);
            tma_load3d(sb + OFF_S + slot * 32768, &tm_m, i * 64, bar_full + 32 + 8 * i);
        };
        auto load_v = [&](int i, int slot) {
            mbar_expect(bar_full + 64 + 8 * i, 32768);
            tma_load3d(sb + OFF_S + slot * 32768, &tm_wv, i * 64, bar_full + 64 + 8 * i);
        };
        const char* hsl = (const char*)(sc->hs + slice * NN);
        auto fill = [&](int slot) { bulk_g2s(sb + OFF_S + slot * 32768, hsl + slot * 32768, slot == 4 ? NN * 16 - 4 * 32768 : 32768, bar_fill); };
        const unsigned t0 = clock();
        if (one) {
            for (int i = 0; i < 2; i++) mbar_init(bar_full + 8 * i, 1);
            asm volatile("fence.mbarrier_init.release.cluster;" ::: "memory");
            while ((unsigned)clock() - t0 < XD0) {}
            if (rowcta) load_xl(0);
            STAMPT(512, 41);
            for (int i = 2; i < 12; i++) mbar_init(bar_full + 8 * i, 1);
            mbar_init(bar_go, 1 + GATE2); mbar_init(bar_am, 1);
            for (int i = 0; i < 4; i++) mbar_init(bar_fill + 8 * i, 1);
            for (int i = 0; i < 10; i++) mbar_init(bar_rd + 8 * i, i < 9 ? 16 : g1 - g0 - 144);
            asm volatile("fence.mbarrier_init.release.cluster;" ::: "memory");
            if ((unsigned)__cvta_generic_to_shared(smem_raw) != sb) __trap();
            mbar_expect(bar_fill, NN * 16);
        }
        __syncwarp();
        nb_arrive<3, 544>();
        nb_arrive<13, 160>();
        if (one && rowcta) {
            while ((unsigned)clock() - t0 < XD1) {}
            load_xl(1);
            STAMPT(512, 40);
        }
        __syncwarp();
        nb_sync<15, 64>();
        if (rowcta) {
            if (one) {
                if (XD2) { while ((unsigned)clock() - t0 < XD2 + 1) {} } else mbar_wait(bar_full);
                load_xl(2);
                STAMPT(512, 52);
                mbar_wait(bar_full + (XD2 ? 0 : 8)); load_xl(3);
                STAMPT(512, 53);
                asm volatile("cp.async.bulk.prefetch.L2.global [%0],%1;" ::"l"(wv + b * 64), "r"(b == NT - 1 ? 4096 : 1024) : "memory");
                asm volatile("prefetch.tensormap [%0];" ::"l"(&tm_m) : "memory");
                asm volatile("prefetch.tensormap [%0];" ::"l"(&tm_wv) : "memory");
                if (POLL2) mbar_wait(bar_am); else bar_poll(sc, 3);
                STAMPT(512, 48);
                fence_async_gmem();
            }
            WAIT_EV(5); if (one) { load_m(0, 0); load_m(1, 1); mbar_arrive(bar_go); }
            WAIT_EV(6); if (one) load_m(2, 3);
            WAIT_EV(7); if (one) load_m(3, 0);
            WAIT_EV(12); if (one) bar_arrive(&sc->bar[2 * 64]);
            STAMPT(512, 24);
            WAIT_EV(14); if (one) { fence_async_smem(); load_v(0, 4); load_v(1, 2); }
            WAIT_EV(15);
            if (one) {
                fence_async_smem();
                load_v(2, 1); load_v(3, 3);
                bar_poll(sc, 2);
                fence_async_gmem();
            }
            STAMPT(512, 25);
            WAIT_EV(2); STAMPT(512, 1); if (one) { fill(0); if (VRS > 0) fill(4); if (VRS > 1) fill(2); }
            WAIT_EV(4); if (one) fill(1);
            WAIT_EV(5); if (one) fill(3);
            if (VRS < 2) { WAIT_EV(6); if (one) fill(2); }
            if (VRS < 1) { WAIT_EV(7); if (one) fill(4); }
            WAIT_EV(12);
            STAMPT(512, 15);
            if (one) {
                fence_async_smem();
#pragma unroll
                for (int kb = 0; kb < 4; kb++)
                    asm volatile("cp.async.bulk.tensor.2d.global.shared::cta.bulk_group [%0,{%2,%3}],[%1];"
                                 ::"l"(&tm_ot), "r"(sb + OFF_T + kb * 10240), "r"(kb * 64), "r"(b * TILE) : "memory");
                asm volatile("cp.async.bulk.commit_group;" ::: "memory");
                asm volatile("cp.async.bulk.wait_group 0;" ::: "memory");
                fence_async_gmem();
            }
        } else {
            if (one) {
                bar_arrive(&sc->bar[2 * 64]);
                bar_poll(sc, 2);
                fence_async_gmem(); fence_async_smem();
                for (int i = 0; i < 5; i++) fill(i);
            }
        }
        if (one) {
            bar_arrive_relaxed(&sc->bar[1 * 64]);
            mbar_arrive(bar_t);
            STAMPT(512, 26);
            bar_poll(sc, 1);
            fence_async_gmem();
            STAMPT(512, 27);
            unsigned tn = clock();
#pragma unroll 1
            for (int r = 0; r < 9; r++) {
                mbar_wait(bar_rd + 8 * r);
                fence_async_smem();
#pragma unroll
                for (int i = 0; i < 256 / PBOX; i++) {
                    while ((int)(clock() - tn) < 0) __nanosleep(20);
                    tn = clock() + PACE;
                    tma_reduce(&tm_o256, sb + OFF_STG + r * 4096 + i * PBOX * 16, slice * 8, (g0 + 16 * r) * 16 + i * PBOX);
                }
            }
            mbar_wait(bar_rd + 72);
            STAMPT(512, 14);
            fence_async_smem();
            for (int i = 144; i < g1 - g0; i++) tma_reduce(&tm_o16, sb + OFF_STG + i * 256, slice * 8, (g0 + i) * 16);
            asm volatile("cp.async.bulk.commit_group;" ::: "memory");
            asm volatile("cp.async.bulk.wait_group.read 0;" ::: "memory");
            STAMPT(512, 13);
        }
    }
    } else {
    if (tid < 32) {
        unsigned bad = 0;
        uint4 xd[3];
#pragma unroll
        for (int k = 0; k < 3; k++) xd[k] = ldg_na((const uint4*)edst + min(b * TILE + k * 32 + lane, NN - 1u));
#pragma unroll
        for (int k = 0; k < 3; k++) { const unsigned n = min(b * TILE + k * 32 + lane, NN - 1u); bad |= (xd[k].x ^ n) | (xd[k].y ^ n) | (xd[k].z ^ n) | (xd[k].w ^ n); }
        bad = __any_sync(~0u, bad);
        if (lane == 0) sts32(sb + OFF_MISC + 20, bad);
        __syncwarp();
        nb_arrive<13, 160>();
    } else if (tid < 64) {
        const uint4* ep = (const uint4*)esrc + (min(b, NT - 1u) * TILE + lane);
        cp16(sb + OFF_EIDX + lane * 16, ep); cp16(sb + OFF_EIDX + 512 + lane * 16, ep + 32);
        if (lane < 16) cp16(sb + OFF_EIDX + 1024 + lane * 16, ep + 64);
        if (lane < 10) cp16(sb + OFF_DIS + lane * 16, dis + (min(b, NT - 1u) * 10 + lane));
        cp_commit();
        cp_wait<0>();
        nb_arrive<13, 160>();
    } else if (tid >= 192) {
        if (rowcta) {
            const unsigned bt = tid - 192;
            if (ED0) { const unsigned t0 = clock(); while ((unsigned)clock() - t0 < ED0 + 1) {} }
            const uint4 ed = ldg_na(dst4 + (b * 320 + bt)), es = ldg_na(src4 + (b * 320 + bt));
            const unsigned pad = (PADBIN + 4 * ((bt & 3) + ((b * 4) & 28))) << 16;
#pragma unroll
            for (int k = 0; k < 4; k++) if ((k & 1) == 0 || bt < 180) sts128(sb + OFF_MAIL + (k >> 1) * 9216 + (bt + (k & 1) * 320) * 16, make_uint4(pad, pad, pad, pad));
            const unsigned cz = bt < (512 + PADBIN) / 16 ? 0 : 0x40000000;
            if (bt < (512 + 2688) / 16) sts128(sb + OFF_CNT1 + bt * 16, make_uint4(cz, cz, cz, cz));
            if (bt == 319) sts128(sb + OFF_MISC, make_uint4(0, 0, 0, 0));
            unsigned z;
            asm volatile("{.reg .pred p; setp.eq.u32 p,%1,0xFFFFFFFF; bar.red.popc.u32 %0,4,320,p;}" : "=r"(z) : "r"(bt) : "memory");
            const unsigned dd[4] = {ed.x + z, ed.y + z, ed.z + z, ed.w + z}, ss[4] = {es.x + z, es.y + z, es.z + z, es.w + z};
            unsigned rk[4], ow[4];
#pragma unroll
            for (int i = 0; i < 4; i++) { ow[i] = dd[i] / TILE; rk[i] = atoms_inc(sb + OFF_CNT1 + ow[i] * 4); }
#pragma unroll
            for (int i = 0; i < 4; i++) {
                const unsigned dl = dd[i] - ow[i] * TILE;
                const unsigned e = bitsel(ss[i] << 20, bitsel(dl << 21, dl << 18, 0xFF800000u), 0x00700000u) + (ss[i] >> 3);
                asm volatile("{.reg .pred p; setp.lt.u32 p,%2,%3; @p st.shared.u32 [%0],%1;}" ::"r"(sb + OFF_MAIL + ow[i] * 64 + rk[i] * 4 + (rk[i] >> 4) * (9216 - 64)), "r"(e), "r"(rk[i]), "n"(CELL) : "memory");
            }
            if (__builtin_expect((rk[0] | rk[1] | rk[2] | rk[3]) >= CELL, 0)) {
#pragma unroll
                for (int i = 0; i < 4; i++) if (rk[i] >= CELL) push_overflow(sc, dd[i], ss[i]);
            }
        }
        STAMPT(416, 44);
        nb_arrive<2, 352>();
    } else {
        const unsigned fw = b >> 3, hq = b & 7, q = (tid >> 5) - 2;
        const unsigned ma = sb + OFF_S + 4 * 32768 + 8192 + q * 6144;
        {
            const unsigned r = lane >> 3, da = ma + r * 128 + (((lane ^ r) & 7) << 4);
            const uint4* pa = wq + ((16 * fw + r) * 32 + q * 8 + (lane & 7));
            const uint4* pb = wk + ((32 * hq + r) * 32 + q * 8 + (lane & 7));
#pragma unroll
            for (int u = 0; u < 12; u++) cp16((da ^ ((u & 1) << 6)) + u * 512, u < 4 ? pa + u * 128 : pb + (u - 4) * 128);
            cp_commit();
        }
        const unsigned aa = ma + (lane & 15) * 128 + ((((lane >> 4) ^ lane) & 7) << 4);
        const unsigned br = 4 * ((lane & 7) >> 1) + 2 * (lane >> 4) + (lane & 1);
        const unsigned ba = ma + 2048 + br * 128 + (((((lane >> 3) & 1) ^ br) & 7) << 4);
        float c[4][4];
#pragma unroll
        for (int u = 0; u < 4; u++) c[u][0] = c[u][1] = c[u][2] = c[u][3] = 0.f;
        STAMPT(64, 38);
        cp_wait<0>();
        __syncwarp();
        STAMPT(64, 39);
#pragma unroll
        for (int k = 0; k < 4; k++) {
            const uint4 a = ldsm4(aa ^ (k << 5)), b0 = ldsm4(ba ^ (k << 5)), b1 = ldsm4((ba ^ (k << 5)) + 2048);
            mma16816(c[0], a.x, a.y, a.z, a.w, b0.x, b0.y); mma16816(c[1], a.x, a.y, a.z, a.w, b0.z, b0.w);
            mma16816(c[2], a.x, a.y, a.z, a.w, b1.x, b1.y); mma16816(c[3], a.x, a.y, a.z, a.w, b1.z, b1.w);
        }
        const unsigned ra = sb + OFF_S + 4 * 32768 + lane * 16;
#pragma unroll
        for (int i = 0; i < 4; i++)
            sts128(ra + q * 2048 + i * 512, make_uint4(__float_as_uint(c[2 * (i & 1)][2 * (i >> 1)]), __float_as_uint(c[2 * (i & 1)][2 * (i >> 1) + 1]),
                                                       __float_as_uint(c[2 * (i & 1) + 1][2 * (i >> 1)]), __float_as_uint(c[2 * (i & 1) + 1][2 * (i >> 1) + 1])));
        STAMPT(64, 42);
        nb_sync<8, 128>();
        float m[4] = {0, 0, 0, 0};
#pragma unroll
        for (int i = 0; i < 4; i++) {
            const uint4 u = lds128(ra + i * 2048 + q * 512);
            m[0] += __uint_as_float(u.x); m[1] += __uint_as_float(u.y); m[2] += __uint_as_float(u.z); m[3] += __uint_as_float(u.w);
        }
        const float k = 0.0625f * 1.4426950408889634f;
        asm volatile("st.shared.v2.u32 [%0],{%1,%2};" ::"r"(sb + OFF_MAIL + 8064 + (8 * (q >> 1) + g) * 64 + (q & 1) * 32 + t * 8),
                     "r"(pack2(m[0] * k, m[1] * k)), "r"(pack2(m[2] * k, m[3] * k)) : "memory");
        fence_async_smem();
        STAMPT(64, 43);
        nb_arrive<14, 192>();
    }
    asm volatile("setmaxnreg.inc.sync.aligned.u32 %0;" ::"n"(REG_W));
    const int w = __shfl_sync(~0u, tid >> 5, 0), wg = w >> 2;
    const int grp0 = g0 + w;
    const uint4* lp = sc->lists + (grp0 * 32 + lane);
    uint4 L0, L1;
    nb_sync<3, 544>();

    if (__builtin_expect(rowcta, 1)) {
        const unsigned descA = 0x10000u + (SB0 + OFF_S) / 16 + wg * 512;
        const unsigned greg = sb + OFF_S + w * 2048 + lane * 16;
        float d[40];
        unsigned pk[20];
        unsigned* hp = (unsigned*)(sc->hs + (2 * w * NN + b * TILE)) + lane;
        auto mma_k = [&](int Q, int slot, int st, int k0, int k1) {
            if (st < 0) wg_fence();
#pragma unroll
            for (int k = k0; k < k1; k++) {
                if (st >= 0) wg_fence();
                wg80(d, descA + slot * 2048 + k * 128, 0x10000u + (SB0 + OFF_T) / 16 + (Q & 3) * 640 + k * 2, st == -2 ? k != 0 : st == -3 || ((Q & 3) | k) != 0);
                if (st >= 0) {
#pragma unroll
                    for (int j = st + k; j < st + k + 1; j++)
                        if (j < 20) asm volatile("st.global.u32 [%0],%1;" ::"l"(hp + (j >> 1) * 32 + (j & 1) * (NN * 4)), "r"(pk[j]) : "memory");
                }
            }
            wg_commit();
        };
        auto mma_q = [&](int Q, int slot, int st) { mma_k(Q, slot, st, 0, 4); };
        auto mma_head = [&](int Q, int slot, int st) { mma_k(Q, slot, st, 0, KH); wg_wait<1>(); };
        auto mma_tail = [&](int Q, int slot, int st) { mma_k(Q, slot, st, KH, 4); };
        const uint4* xl = x + lane;
        auto eidx = [&](int i) { return lds128(sb + OFF_EIDX + (w * 5 + i) * 16); };
        auto gather = [&](const uint4& ix, int slot) {
            cp16(greg + slot * 32768, xl + ix.x * 32u); cp16(greg + slot * 32768 + 512, xl + ix.y * 32u);
            cp16(greg + slot * 32768 + 1024, xl + ix.z * 32u); cp16(greg + slot * 32768 + 1536, xl + ix.w * 32u);
            cp_commit();
        };
        const uint4 ix0 = eidx(0), ix1 = eidx(1), ix2 = eidx(2), ix3 = eidx(3), ix4 = eidx(4);
        uint4 gv[5][4];
        const unsigned gld = sb + OFF_S + w * 2048 + ((lane >> 3) & 1) * 512 + (lane >> 4) * 128 + (lane & 7) * 16;
        auto to_regs = [&](int i, int slot) {
            __syncwarp();
#pragma unroll
            for (int j = 0; j < 4; j++) gv[i][j] = ldsm4(gld + slot * 32768 + (j & 1) * 256 + (j >> 1) * 1024);
        };
        unsigned ds[10];
#pragma unroll
        for (int j = 0; j < 10; j++) ds[j] = lds32(sb + OFF_DIS + (4 * j + t) * 4);
        STAMPT(288, 2);
        mbar_wait(bar_full);
        STAMPT(288, 3);
        mma_q(0, 0, -1);
        mbar_wait(bar_full + 8);
        STAMPT(288, 50);
        mma_q(1, 1, -1);
        mbar_wait(bar_full + 16);
        STAMPT(288, 51);
        mma_head(2, 2, -1);
        EV(5);
        mma_tail(2, 2, -1);
        mbar_wait(bar_full + 24);
        STAMP(5);
        mma_q(3, 3, -1);
        mbar_wait(bar_go);
        gather(ix0, 4);
        wg_wait<0>();
        EV(6);
        STAMP(6);
#pragma unroll
        for (int j = 0; j < 20; j++) pk[j] = movm(hmul2(pack2(d[2 * j], d[2 * j + 1]), ds[j >> 1]));
#pragma unroll
        for (int j = 0; j < STPRE; j++) asm volatile("st.global.u32 [%0],%1;" ::"l"(hp + (j >> 1) * 32 + (j & 1) * (NN * 4)), "r"(pk[j]) : "memory");
        STAMP(7);
        if (G1POS < 2) nb_sync_id(8 + wg, 128);
        if (G1POS == 0) gather(ix1, 2);
        mbar_wait(bar_full + 32);
        if (G1POS == 1) { if (G0POS == 2) gather(ix0, 4); gather(ix1, 2); }
        STAMP(21);
        if (G1POS == 2) {
            mma_k(4, 0, STPRE, 0, 1);
            if (G0POS == 2) gather(ix0, 4);
            nb_sync_id(8 + wg, 128);
            gather(ix1, 2);
            mma_k(4, 0, STPRE, 1, 4);
        } else {
            mma_q(4, 0, STPRE);
        }
        STAMP(28);
        mbar_wait(bar_full + 40);
        mma_head(5, 1, STPRE + 4);
        EV(7);
        mma_tail(5, 1, STPRE + 4);
        STAMP(29);
        mbar_wait(bar_full + 48);
        STAMP(30);
        mma_head(6, 3, STPRE + 8);
        nb_sync_id(8 + wg, 128);
        gather(ix2, 1);
        mma_tail(6, 3, STPRE + 8);
        STAMP(31);
        mbar_wait(bar_full + 56);
        STAMP(32);
        mma_head(7, 0, STPRE + 12);
        nb_sync_id(8 + wg, 128);
        gather(ix3, 3);
        mma_tail(7, 0, STPRE + 12);
        EV(12);
        wg_wait<0>();
        STAMP(20);
        pack_acc(pk, d);
        nb_sync<0, 512>();
        acc_to_tile(pk, w, lane);
        gather(ix4, 0);
        cp_wait<3>();
        to_regs(0, 4);
        nb_sync<0, 512>();
        STAMP(8);
        uint4 vf[8];
        {
            const unsigned delta = t ^ (g >> 1), alsm = sb + OFF_ALPHA + w * 128;
            const bool par = g & 1;
            unsigned ta[5];
#pragma unroll
            for (int i = 0; i < 5; i++) ta[i] = tile_addr(w * 5 + i, lane);
            float v[4], u[4];
            to_regs(1, 2);
            EV(14);
            attn_scores(v, true, par, gv[0], ta[0]);
            attn_scores(v, delta == 1, par, gv[1], ta[1] ^ 32);
            cp_wait<2>();
            to_regs(2, 1);
            attn_scores(v, delta == 2, par, gv[2], ta[2] ^ 64);
            STAMP(33);
            cp_wait<1>();
            to_regs(3, 3);
            EV(15);
            STAMP(34);
            attn_scores(v, delta == 3, par, gv[3], ta[3] ^ 96);
            cp_wait<0>();
            to_regs(4, 0);
            STAMP(35);
            attn_scores(u, true, par, gv[4], ta[4]);
            attn_softmax(v, u, lane, alsm + ((lane & 4) + delta) * 16 + (lane >> 3) * 4);
            STAMP(49);
            const unsigned va = sb + OFF_S + wg * 8192 + ((lane & 7) + (lane >> 4) * 8) * 128 + (((2 * (w & 3) + ((lane >> 3) & 1)) ^ (lane & 7)) << 4);
            if (VRS > 0) mbar_wait(bar_full + 64);
            if (VRS > 1) mbar_wait(bar_full + 72);
            uint4 al = lds128(alsm);
#pragma unroll
            for (int i = 0; i < 5; i++) {
                const uint4 a = al;
                if (i < 4) al = lds128(alsm + (i + 1) * 16);
                attn_mix(gv[i], a, ta[i]);
                if (i >= 1 && i <= VRS) {
#pragma unroll
                    for (int k = 0; k < 4; k++) vf[4 * (i - 1) + k] = ldsm4t(va + (i == 1 ? 4 : 2) * 32768 + k * 2048);
                }
            }
        }
        STAMP(36);
        mbar_wait(bar_full + 80);
        fence_async_smem();
        STAMP(22);
        EV(2);
        nb_sync<0, 512>();
        mma_k(10, 1, -2, 0, 4);
        mbar_wait(bar_full + 88);
        mma_head(11, 3, -1);
        EV(4);
        mma_tail(11, 3, -1);
        auto mma_r = [&](int k0, int k1) {
            wg_fence();
#pragma unroll
            for (int k = k0; k < k1; k++) wg80r(d, vf[k], 0x10000u + (SB0 + OFF_T) / 16 + (k >> 2) * 640 + (k & 3) * 2);
            wg_commit();
        };
        if (VRS < 2) {
            mbar_wait(bar_full + 72);
            mma_head(9, 2, -1);
            EV(5);
            mma_tail(9, 2, -1);
        } else {
            mma_r(4, 5); wg_wait<1>(); EV(5); mma_r(5, 8);
        }
        if (VRS < 1) {
            mbar_wait(bar_full + 64);
            mma_k(8, 4, -3, 0, KH); wg_wait<1>();
            EV(6);
            mma_tail(8, 4, -1);
        } else if (VRS == 1) {
            mma_r(0, 1); wg_wait<1>(); EV(6); mma_r(1, 4);
        } else {
            mma_r(0, 4);
        }
        mbar_wait(bar_c);
        L0 = ldg_na(lp); L1 = ldg_na(lp + LSTR);
        wg_wait<0>();
        if (VRS < 1) EV(7);
        STAMP(9);
        pack_acc(pk, d);
        nb_sync<0, 512>();
        STAMP(10);
        if (__builtin_expect(lds32(sb + OFF_MISC + 28) & 2, 0)) {
            for (int i = 0; i < 5; i++) sts128(tile_addr(w * 5 + i, lane), attn_generic(b * TILE + w * 5 + i, x, esrc, edst, wq, wk, wv));
        } else {
            acc_to_tile(pk, w, lane);
        }
        EV(12);
    } else {
        mbar_wait(bar_c);
        L0 = ldg_na(lp); L1 = ldg_na(lp + LSTR);
    }

    const unsigned flags = lds32(sb + OFF_MISC + 28);
    const bool anyovf = flags & 1;
    const unsigned zero = flags >> 8;
    const unsigned selA = 0x4140 + zero, selB = 0x4342 + zero, m128 = 0x80000080u + (M128UR ? 0 : zero);
    if (lane < 8) sts128(sb + OFF_S + NN * 16 + lane * 16, make_uint4(0, 0, 0, 0));
    const unsigned lb = sb + OFF_S + (lane & 7) * 16;
    const unsigned dummy = anyovf ? 0 : lb + 1250 * 128;
    const float zmask = (lane >= 28) ? 0.f : -1.f;
    unsigned stg = sb + OFF_STG + w * 256 + (((lane & 7) * 2 + ((lane >> 3) & 1)) ^ ((lane >> 2) & 1)) * 16;
    unsigned rdb = bar_rd;
    const unsigned rde = bar_rd + 8 * ((g1 - grp0 + 15) >> 4);
    __syncwarp();
    mbar_wait(bar_fill);
    STAMP(11);
    CLK0(64);
    struct Dec { unsigned ad[12], sA, nB; float dA, dB; };
    auto decode = [&](Dec& D, const uint4& L0, const uint4& L1) {
        D.ad[0] = dp2lo(L0.z, m128, lb); D.ad[1] = dp2hi(L0.z, m128, lb); D.ad[2] = dp2lo(L0.w, m128, lb); D.ad[3] = dp2hi(L0.w, m128, lb);
        D.ad[4] = dp2lo(L1.x, m128, lb); D.ad[5] = dp2hi(L1.x, m128, lb); D.ad[6] = dp2lo(L1.y, m128, lb); D.ad[7] = dp2hi(L1.y, m128, lb);
        D.ad[8] = dp2lo(L1.z, m128, lb); D.ad[9] = dp2hi(L1.z, m128, lb); D.ad[10] = dp2lo(L1.w, m128, lb); D.ad[11] = dp2hi(L1.w, m128, lb);
        asm volatile("prmt.b32 %0,%1,0x64646464,%2;" : "=r"(D.sA) : "r"(L0.x), "r"(selA));
        asm volatile("prmt.b32 %0,%1,0xE4E4E4E4,%2;" : "=r"(D.nB) : "r"(L0.x), "r"(selB));
        D.dA = blo_v(L0.y); D.dB = bhi_v(L0.y);
    };
    auto group = [&](Dec& D) {
            unsigned* ad = D.ad;
            const unsigned sA = D.sA, nB = D.nB;
            const float dA = D.dA, dB = D.dB;
            const unsigned p9 = __any_sync(~0u, ad[9] != dummy), p10 = __any_sync(~0u, ad[10] != dummy);
            uint4 C2;
            asm volatile("{.reg .pred p; setp.ne.u32 p,%5,0; @p ld.global.L1::no_allocate.v4.u32 {%0,%1,%2,%3},[%4];}"
                         : "=r"(C2.x), "=r"(C2.y), "=r"(C2.z), "=r"(C2.w) : "l"(lp + 2 * LSTR), "r"(ad[11] & 0x400000) : "memory");
            float acc0[4] = {0, 0, 0, 0}, acc1[4] = {0, 0, 0, 0};
            uint4 v[11], a0, a1;
            float acc2[4] = {0, 0, 0, 0}, acc3[4] = {0, 0, 0, 0};
#pragma unroll
            for (int s = 0; s < LA; s++) v[s] = ldsm4t(ad[s]);
            a0 = p3_sel(0, sA, nB); a1 = p3_sel(1, sA, nB);
#pragma unroll
            for (int s = 0; s < 9; s++) {
                if (s % FENCE_EVERY == 0) sched_fence(zero);
                const uint4 n0 = p3_sel(2 * s + 2, sA, nB);
                mma16816(CHAINS == 4 ? ((s & 1) ? acc0 : acc2) : CHAINS == 3 ? ((2 * s) % 3 == 0 ? acc0 : (2 * s) % 3 == 1 ? acc1 : acc2) : acc0, a0.x, a0.y, a0.z, a0.w, v[s].x, v[s].y);
                if (s + LA < 9) v[s + LA] = ldsm4t(ad[s + LA]);
                else if (s + LA < 11) v[s + LA] = ldsm4t_if(ad[s + LA], s + LA == 9 ? p9 : p10);
                const uint4 n1 = p3_sel(2 * s + 3, sA, nB);
                mma16816(CHAINS == 4 ? ((s & 1) ? acc1 : acc3) : CHAINS == 3 ? ((2 * s + 1) % 3 == 0 ? acc0 : (2 * s + 1) % 3 == 1 ? acc1 : acc2) : acc1, a1.x, a1.y, a1.z, a1.w, v[s].z, v[s].w);
                a0 = n0; a1 = n1;
            }
            const uint4 v10 = v[10];
            if (p9) {
                mma16816(acc0, a0.x, a0.y, a0.z, a0.w, v[9].x, v[9].y);
                mma16816(acc1, a1.x, a1.y, a1.z, a1.w, v[9].z, v[9].w);
                if (p10) {
                    p3_mma(CHAINS > 2 ? acc2 : acc0, CHAINS == 4 ? acc3 : CHAINS == 3 ? acc0 : acc1, v10, 10, sA, nB);
                    if (__any_sync(~0u, ad[11] != dummy)) {
                        p3_mma(acc0, acc1, ldsm4t(ad[11] & ~0x400000u), 11, sA, nB);
                        if (__any_sync(~0u, (ad[11] & 0x400000) || anyovf)) {
                            if (anyovf) C2 = ldg_na(lp + 2 * LSTR);
                            const unsigned e2[4] = {C2.x, C2.y, C2.z, C2.w};
#pragma unroll
                            for (int s = 12; s < 20; s++) {
                                const unsigned a = (s & 1) ? dp2hi(e2[(s - 12) >> 1], m128, lb) : dp2lo(e2[(s - 12) >> 1], m128, lb);
                                if ((s == 13 || s == 14) && !__any_sync(~0u, a != dummy)) break;
                                p3_mma(acc0, acc1, ldsm4t(a), s, sA, nB);
                            }
                            if (anyovf) {
                                float4 e = p3_overflow(sc, grp0 + 2 * (rdb - bar_rd), sb + OFF_S);
                                float s0 = e.x + e.z, s1 = e.y + e.w;
                                for (int k = 4; k < 32; k <<= 1) {
                                    float u0 = __shfl_down_sync(~0u, s0, k), u1 = __shfl_down_sync(~0u, s1, k);
                                    if (lane + k < 32) { s0 += u0; s1 += u1; }
                                }
                                acc0[0] += s0; acc0[1] += s1; acc0[2] += s0 - e.x; acc0[3] += s1 - e.y;
                            }
                        }
                    }
                }
            }
            if (CHAINS == 4) { acc2[0] += acc3[0]; acc2[1] += acc3[1]; acc2[2] += acc3[2]; acc2[3] += acc3[3]; }
            float c0 = acc0[0] + acc1[0], c1 = acc0[1] + acc1[1], c2 = acc0[2] + acc1[2], c3 = acc0[3] + acc1[3];
            if (CHAINS > 2) { c0 += acc2[0]; c1 += acc2[1]; c2 += acc2[2]; c3 += acc2[3]; }
            float n0 = __shfl_down_sync(~0u, c0, 4), n1 = __shfl_down_sync(~0u, c1, 4);
            float o0 = c0 - c2, o1 = c1 - c3, o2 = fmaf(n0, zmask, c2), o3 = fmaf(n1, zmask, c3);
            asm volatile("stmatrix.sync.aligned.m8n8.x2.shared.b16 [%0],{%1,%2};" ::"r"(stg), "r"(pack2(o0 * dA, o1 * dA)), "r"(pack2(o2 * dB, o3 * dB)) : "memory");
            __syncwarp();
            asm volatile("{.reg .pred p; setp.eq.u32 p,%1,0; @p mbarrier.arrive.shared.b64 _,[%0];}" ::"r"(rdb), "r"(lane) : "memory");
            stg += 4096;
            rdb += 8;
            lp += 16 * 32;
    };
#pragma unroll 1
    while (true) {
        if (rdb == bar_rd + 48) mbar_wait(bar_t);
        Dec D0;
        decode(D0, L0, L1);
        L0 = ldg_na(lp + 16 * 32); L1 = ldg_na(lp + 16 * 32 + LSTR);
        group(D0);
        if (rdb == rde) break;
    }
    STAMP(12);
    CLK1(64, 60); STAMPT(0, 61); STAMPT(352, 62); STAMPT(480, 63);
    }
}

typedef CUresult (*EncodeFn)(CUtensorMap*, CUtensorMapDataType, cuuint32_t, void*, const cuuint64_t*, const cuuint64_t*,
                             const cuuint32_t*, const cuuint32_t*, CUtensorMapInterleave, CUtensorMapSwizzle,
                             CUtensorMapL2promotion, CUtensorMapFloatOOBfill);

}

extern "C" void kernel_launch(void* const* d_in, const int* in_sizes, int n_in, void* d_out, int out_size) {
    (void)in_sizes; (void)n_in; (void)out_size;
    static EncodeFn enc = nullptr;
    static void* scratch = nullptr;
    if (!enc) {
        cudaGetSymbolAddress(&scratch, g_scratch);
        void* fn = nullptr;
        cudaDriverEntryPointQueryResult qr;
        cudaGetDriverEntryPoint("cuTensorMapEncodeTiled", &fn, cudaEnableDefault, &qr);
        enc = (EncodeFn)fn;
        cudaFuncSetAttribute(exphormer_kernel, cudaFuncAttributeMaxDynamicSharedMemorySize, SMEM_BYTES);
    }
    CUtensorMap tm_m, tm_ms, tm_mail, tm_x, tm_wl, tm_wv, tm_ot, tm_o256, tm_o16;
    auto mk = [&](CUtensorMap* tm, void* p, int rows, int bc, int br, CUtensorMapSwizzle sw, CUtensorMapL2promotion pr) {
        cuuint64_t gd[2] = {256, (cuuint64_t)rows}, gs[1] = {512};
        cuuint32_t es[2] = {1, 1}, bx[2] = {(cuuint32_t)bc, (cuuint32_t)br};
        enc(tm, CU_TENSOR_MAP_DATA_TYPE_BFLOAT16, 2, p, gd, gs, bx, es, CU_TENSOR_MAP_INTERLEAVE_NONE, sw, pr, CU_TENSOR_MAP_FLOAT_OOB_FILL_NONE);
    };
    for (int i = 0; i < 3; i++) {
        cuuint64_t gd[3] = {64, 256, 4}, gs[2] = {512, 128};
        cuuint32_t es[3] = {1, 1, 1}, bx[3] = {64, 64, 4};
        enc(i == 2 ? &tm_m : i ? &tm_wv : &tm_wl, CU_TENSOR_MAP_DATA_TYPE_BFLOAT16, 3, i == 2 ? scratch : d_in[i ? 9 : 6], gd, gs, bx, es, CU_TENSOR_MAP_INTERLEAVE_NONE,
            CU_TENSOR_MAP_SWIZZLE_128B, CU_TENSOR_MAP_L2_PROMOTION_L2_128B, CU_TENSOR_MAP_FLOAT_OOB_FILL_NONE);
    }
    {
        cuuint64_t gd[2] = {2048, NT}, gs[1] = {8192};
        cuuint32_t es[2] = {1, 1}, bx[2] = {16, NT};
        enc(&tm_mail, CU_TENSOR_MAP_DATA_TYPE_UINT32, 2, ((Scratch*)scratch)->mail, gd, gs, bx, es, CU_TENSOR_MAP_INTERLEAVE_NONE,
            CU_TENSOR_MAP_SWIZZLE_NONE, CU_TENSOR_MAP_L2_PROMOTION_NONE, CU_TENSOR_MAP_FLOAT_OOB_FILL_NONE);
    }
    mk(&tm_ms, scratch, 256, 32, 16, CU_TENSOR_MAP_SWIZZLE_NONE, CU_TENSOR_MAP_L2_PROMOTION_NONE);
    mk(&tm_x, d_in[0], NN, 64, TILE, CU_TENSOR_MAP_SWIZZLE_128B, CU_TENSOR_MAP_L2_PROMOTION_L2_128B);
    mk(&tm_ot, d_out, NN, 64, TILE, CU_TENSOR_MAP_SWIZZLE_128B, CU_TENSOR_MAP_L2_PROMOTION_NONE);
    mk(&tm_o256, d_out, NN, 8, PBOX, CU_TENSOR_MAP_SWIZZLE_NONE, CU_TENSOR_MAP_L2_PROMOTION_NONE);
    mk(&tm_o16, d_out, NN, 8, 16, CU_TENSOR_MAP_SWIZZLE_NONE, CU_TENSOR_MAP_L2_PROMOTION_NONE);
    exphormer_kernel<<<NCTA, 640, SMEM_BYTES>>>(
        (const uint4*)d_in[0], (const uint4*)d_in[2], (const uint4*)d_in[1], (const uint4*)d_in[7], (const uint4*)d_in[8], (const int*)d_in[3],
        (const int*)d_in[4], (Scratch*)scratch, (const uint4*)d_in[5], (const uint4*)d_in[9],
        tm_x, tm_wl, tm_wv, tm_m, tm_ms, tm_mail, tm_ot, tm_o256, tm_o16);
}
```

```cpp
#include <cuda_runtime.h>
#include <cuda_bf16.h>
#include <cuda.h>
#include <stdint.h>

namespace {

constexpr int NN = 10000, NE = 160000, NEE = 40000;
constexpr int TILE = 80, NT = 125, NCTA = 128, NG = 625, EPC = 1280;
constexpr int CELL = 32;
constexpr int QCAP = 192;
constexpr int OVCAP = EPC + NT * CELL;
#define XD0 700
#define XD1 1100
#define XD2 1900
#define REG_W 104
#define REG_H 64
#define KH 1
#define POLLNS 0
#define STPRE 4
#define G0POS 1
#define G1POS 1
#define LA 3
#define ED0 0
#define VRS 0
#define PACE 650
#define PBOX 256
constexpr unsigned DUMMY2 = NN | (NN << 16);

constexpr unsigned SB0 = 1024;
constexpr unsigned sb = SB0;
constexpr int OFF_S = 0;
constexpr int OFF_R = 163840;
constexpr int OFF_BAR = OFF_R;
constexpr int OFF_MISC = OFF_R + 256;
constexpr int OFF_DIS = OFF_R + 320;
constexpr int OFF_PROF = OFF_R + 512;
constexpr int OFF_EIDX = OFF_R + 1024;
constexpr int OFF_ALPHA = OFF_R + 1024;
constexpr int OFF_STG = OFF_R + 3072;
constexpr int OFF_CNT1 = OFF_R + 2560;
constexpr int OFF_CNT2 = OFF_R + 3072;
constexpr int OFF_MAIL = OFF_R + 5760;
constexpr int OFF_IMG = OFF_MAIL + 9216;
constexpr int OFF_T = OFF_R + 27648;
constexpr int SMEM_BYTES = OFF_T + 40960;
static_assert(SMEM_BYTES <= 232448 && OFF_T % 1024 == 0 && OFF_STG + 3 * 8192 == OFF_T && OFF_IMG + 10752 <= OFF_T, "smem");
#define bar_fill (sb + OFF_BAR)
#define bar_t (sb + OFF_BAR + 8)
#define bar_mail (sb + OFF_BAR + 16)
#define bar_c (sb + OFF_BAR + 24)
#define bar_rd (sb + OFF_BAR + 32)
#define bar_go (sb + OFF_BAR + 112)
#define bar_full (sb + OFF_BAR + 120)
constexpr int LSTR = (NG + 48) * 32;

struct __align__(256) Scratch {
    uint4 mimg[8192];
    uint4 hs[32 * NN];
    uint4 mail[2 * NT * 512];
    uint4 lists[3 * LSTR];
    uint2 ovfn[NCTA];
    unsigned bar[5 * 64];
    unsigned ovf[NCTA * OVCAP];
};
__device__ Scratch g_scratch;
#define STAMPT(th, i)
#define CLK0(th)
#define CLK1(th, i)
#define STAMP(i) STAMPT(64, i)
#define STAMP2(i) STAMPT(416, i)

extern __shared__ __align__(1024) unsigned char smem_raw[];
__device__ __forceinline__ void bar_arrive(unsigned* p) {
    asm volatile("red.release.gpu.global.add.u32 [%0],1;" ::"l"(p) : "memory");
}
__device__ __forceinline__ void bar_arrive_relaxed(unsigned* p) {
    asm volatile("red.relaxed.gpu.global.add.u32 [%0],1;" ::"l"(p) : "memory");
}
__device__ __forceinline__ void bar_poll(const Scratch* sc, int i) {
    unsigned v, target;
    int lim = 0;
    asm volatile("ld.shared.u32 %0,[%1];" : "=r"(target) : "r"(sb + OFF_MISC + 32 + 4 * i) : "memory");
    while (true) {
        asm volatile("ld.acquire.gpu.global.u32 %0,[%1];" : "=r"(v) : "l"(&sc->bar[i * 64]) : "memory");
        if ((int)(v - target) >= 0) break;
        if (++lim > (1 << 22)) __trap();
        if (POLLNS) __nanosleep(POLLNS);
    }
}
__device__ __forceinline__ unsigned bar_poll2(const unsigned* p, unsigned target) {
    unsigned long long v;
    int lim = 0;
    do {
        asm volatile("ld.acquire.gpu.global.u64 %0,[%1];" : "=l"(v) : "l"(p) : "memory");
        if (++lim > (1 << 22)) __trap();
    } while ((int)((unsigned)v - target) < 0);
    unsigned f = (unsigned)(v >> 32);
    return (f & ~3u) == target ? f & 3 : 0;
}
__device__ __noinline__ void raise_flag(unsigned* p, unsigned target, unsigned bit) {
    unsigned old = atomicCAS(p, 0, 0), seen;
    do {
        seen = old;
        old = atomicCAS(p, seen, ((seen & ~3u) == target ? seen : target) | bit);
    } while (old != seen);
}
__device__ __forceinline__ void mbar_wait(unsigned a) {
    asm volatile("{.reg .pred p; .reg .u32 n;\n"
                 "mov.u32 n,0x400000;\n"
                 "W: mbarrier.try_wait.parity.shared.b64 p,[%0],0;\n"
                 "add.u32 n,n,-1; setp.ne.and.u32 p,n,0,!p; @p bra W;}" ::"r"(a) : "memory");
}
__device__ __forceinline__ bool elect() {
    unsigned r;
    asm volatile("{.reg .pred p; elect.sync _|p,0xFFFFFFFF; selp.u32 %0,1,0,p;}" : "=r"(r));
    return r;
}
__device__ __forceinline__ uint4 ldg_na(const uint4* p) {
    uint4 v;
    asm volatile("ld.global.L1::no_allocate.v4.u32 {%0,%1,%2,%3},[%4];" : "=r"(v.x), "=r"(v.y), "=r"(v.z), "=r"(v.w) : "l"(p) : "memory");
    return v;
}
__device__ __forceinline__ uint4 lds128(unsigned a) {
    uint4 v;
    asm volatile("ld.shared.v4.u32 {%0,%1,%2,%3},[%4];" : "=r"(v.x), "=r"(v.y), "=r"(v.z), "=r"(v.w) : "r"(a) : "memory");
    return v;
}
__device__ __forceinline__ uint4 ldsm4(unsigned a) {
    uint4 v;
    asm volatile("ldmatrix.sync.aligned.m8n8.x4.shared.b16 {%0,%1,%2,%3},[%4];" : "=r"(v.x), "=r"(v.y), "=r"(v.z), "=r"(v.w) : "r"(a) : "memory");
    return v;
}
__device__ __forceinline__ void sts128(unsigned a, uint4 v) {
    asm volatile("st.shared.v4.u32 [%0],{%1,%2,%3,%4};" ::"r"(a), "r"(v.x), "r"(v.y), "r"(v.z), "r"(v.w) : "memory");
}
__device__ __forceinline__ void sts32(unsigned a, unsigned v) { asm volatile("st.shared.u32 [%0],%1;" ::"r"(a), "r"(v) : "memory"); }
__device__ __forceinline__ unsigned lds32(unsigned a) { unsigned v; asm volatile("ld.shared.u32 %0,[%1];" : "=r"(v) : "r"(a) : "memory"); return v; }
__device__ __forceinline__ unsigned atoms_add(unsigned a, unsigned k) { unsigned v; asm volatile("atom.shared.add.u32 %0,[%1],%2;" : "=r"(v) : "r"(a), "r"(k) : "memory"); return v; }
__device__ __forceinline__ unsigned bitsel(unsigned a, unsigned b, unsigned m) { unsigned r; asm("lop3.b32 %0,%1,%2,%3,0xE4;" : "=r"(r) : "r"(a), "r"(b), "r"(m)); return r; }
__device__ __forceinline__ unsigned atoms_inc(unsigned a) { unsigned v; asm volatile("atom.shared.add.u32 %0,[%1],1;" : "=r"(v) : "r"(a) : "memory"); return v; }
__device__ __forceinline__ float blo(unsigned v) { return __uint_as_float(v << 16); }
__device__ __forceinline__ float bhi(unsigned v) { return __uint_as_float(v & 0xFFFF0000u); }
__device__ __forceinline__ float blo_v(unsigned v) { float r; asm volatile("shl.b32 %0,%1,16;" : "=f"(r) : "r"(v)); return r; }
__device__ __forceinline__ float bhi_v(unsigned v) { float r; asm volatile("and.b32 %0,%1,0xFFFF0000;" : "=f"(r) : "r"(v)); return r; }
__device__ __forceinline__ unsigned pack2(float lo, float hi) { unsigned r; asm("cvt.rn.bf16x2.f32 %0,%1,%2;" : "=r"(r) : "f"(hi), "f"(lo)); return r; }

__device__ __forceinline__ void mma16816(float* d, unsigned a0, unsigned a1, unsigned a2, unsigned a3, unsigned b0, unsigned b1) {
    asm volatile("mma.sync.aligned.m16n8k16.row.col.f32.bf16.bf16.f32 {%0,%1,%2,%3},{%4,%5,%6,%7},{%8,%9},{%0,%1,%2,%3};"
                 : "+f"(d[0]), "+f"(d[1]), "+f"(d[2]), "+f"(d[3]) : "r"(a0), "r"(a1), "r"(a2), "r"(a3), "r"(b0), "r"(b1));
}
#define R10(b) "+f"(d[b + 0]), "+f"(d[b + 1]), "+f"(d[b + 2]), "+f"(d[b + 3]), "+f"(d[b + 4]), "+f"(d[b + 5]), "+f"(d[b + 6]), "+f"(d[b + 7]), "+f"(d[b + 8]), "+f"(d[b + 9])
__device__ __forceinline__ void wg80(float* d, unsigned da, unsigned db, int sc) {
    asm volatile("{.reg .pred p; .reg .b64 a, b; setp.ne.b32 p,%42,0; mov.b64 a,{%40,%43}; mov.b64 b,{%41,%43};\n"
                 "wgmma.mma_async.sync.aligned.m64n80k16.f32.bf16.bf16 "
                 "{%0,%1,%2,%3,%4,%5,%6,%7,%8,%9,%10,%11,%12,%13,%14,%15,%16,%17,%18,%19,%20,%21,%22,%23,%24,%25,%26,%27,%28,%29,%30,%31,%32,%33,%34,%35,%36,%37,%38,%39},"
                 "a,b,p,1,1,1,0;}"
                 : R10(0), R10(10), R10(20), R10(30) : "r"(da), "r"(db), "r"(sc), "r"(0x40000040));
}
__device__ __forceinline__ void wg80r(float* d, const uint4& a, unsigned db) {
    asm volatile("{.reg .b64 b; mov.b64 b,{%44,%45};\n"
                 "wgmma.mma_async.sync.aligned.m64n80k16.f32.bf16.bf16 "
                 "{%0,%1,%2,%3,%4,%5,%6,%7,%8,%9,%10,%11,%12,%13,%14,%15,%16,%17,%18,%19,%20,%21,%22,%23,%24,%25,%26,%27,%28,%29,%30,%31,%32,%33,%34,%35,%36,%37,%38,%39},"
                 "{%40,%41,%42,%43},b,1,1,1,0;}"
                 : R10(0), R10(10), R10(20), R10(30) : "r"(a.x), "r"(a.y), "r"(a.z), "r"(a.w), "r"(db), "r"(0x40000040));
}
__device__ __forceinline__ void wg_fence() { asm volatile("wgmma.fence.sync.aligned;" ::: "memory"); }
__device__ __forceinline__ void wg_commit() { asm volatile("wgmma.commit_group.sync.aligned;" ::: "memory"); }
template <int N> __device__ __forceinline__ void wg_wait() { asm volatile("wgmma.wait_group.sync.aligned %0;" ::"n"(N) : "memory"); }
__device__ __forceinline__ void bulk_g2s(unsigned dst, const void* src, unsigned bytes, unsigned bar) {
    asm volatile("cp.async.bulk.shared::cluster.global.mbarrier::complete_tx::bytes [%0],[%1],%2,[%3];" ::"r"(dst), "l"(src), "r"(bytes), "r"(bar) : "memory");
}
__device__ __forceinline__ void fence_async_smem() { asm volatile("fence.proxy.async.shared::cta;" ::: "memory"); }
__device__ __forceinline__ void fence_async_gmem() { asm volatile("fence.proxy.async.global;" ::: "memory"); }

__host__ __device__ constexpr unsigned h2c(int v) { return (0x6400u | v) | ((0x6400u | v) << 16); }
__device__ __forceinline__ unsigned row_lo(unsigned a) { unsigned r; asm volatile("dp2a.lo.u32.u32 %0,%1,0x10000010,0;" : "=r"(r) : "r"(a)); return r; }
__device__ __forceinline__ unsigned row_hi(unsigned a) { unsigned r; asm volatile("dp2a.hi.u32.u32 %0,%1,0x10000010,0;" : "=r"(r) : "r"(a)); return r; }
__device__ __forceinline__ uint4 ldsm4t(unsigned addr) {
    uint4 v;
    asm volatile("ldmatrix.sync.aligned.m8n8.x4.trans.shared.b16 {%0,%1,%2,%3},[%4];" : "=r"(v.x), "=r"(v.y), "=r"(v.z), "=r"(v.w) : "r"(addr));
    return v;
}
__device__ __forceinline__ void sched_fence(unsigned zero) { asm volatile("{.reg .pred p; setp.ne.u32 p,%0,0; @p exit;}" ::"r"(zero)); }
__device__ __forceinline__ uint4 p3_sel(int i, unsigned sA, unsigned sB) {
    uint4 a;
    asm volatile("set.le.f16x2.f16x2 %0,%4,%6;\n sub.sat.f16x2 %2,%7,%4;\n set.le.f16x2.f16x2 %1,%5,%6;\n sub.sat.f16x2 %3,%7,%5;"
                 : "=r"(a.x), "=r"(a.y), "=r"(a.z), "=r"(a.w) : "r"(sA), "r"(sB), "r"(h2c(2 * i)), "r"(h2c(2 * i + 2)));
    return a;
}
__device__ __forceinline__ void p3_step(float* acc0, float* acc1, unsigned row, int s, unsigned sA, unsigned sB) {
    const uint4 v = ldsm4t(sb + OFF_S + row), a0 = p3_sel(2 * s, sA, sB), a1 = p3_sel(2 * s + 1, sA, sB);
    mma16816(acc0, a0.x, a0.y, a0.z, a0.w, v.x, v.y);
    mma16816(acc1, a1.x, a1.y, a1.z, a1.w, v.z, v.w);
}
__device__ __noinline__ float4 p3_overflow(const Scratch* sc, int grp, unsigned sS) {
    const unsigned tag = lds32(sb + OFF_MISC + 48);
    int lane = threadIdx.x & 31, g = lane >> 2, t = lane & 3;
    float4 r = make_float4(0.f, 0.f, 0.f, 0.f);
    for (int c = 0; c < NT; c++) {
        const uint2 tn = __ldcg(&sc->ovfn[c]);
        const int n = tn.x == tag ? (int)tn.y : 0;
        for (int i0 = 0; i0 < n; i0 += 32) {
            unsigned e = (i0 + lane < n) ? __ldcg(&sc->ovf[c * OVCAP + i0 + lane]) : 0xFFFFFFFFu;
            unsigned m = __ballot_sync(~0u, (int)(e >> 18) == grp);
            while (m) {
                int j = __ffs(m) - 1;
                m &= m - 1;
                unsigned ee = __shfl_sync(~0u, e, j);
                int row = (ee >> 14) & 15;
                row ^= row >> 3;
                unsigned v = lds32(sS + (ee & 0x3FFF) * 16 + t * 4);
                if ((row >> 1) == g) {
                    if (!(row & 1)) { r.x += blo(v); r.y += bhi(v); } else { r.z += blo(v); r.w += bhi(v); }
                }
            }
        }
    }
    const float k = 1.f / 128.f;
    r.x *= k; r.y *= k; r.z *= k; r.w *= k;
    return r;
}
__device__ __forceinline__ void unpack8(float* f, uint4 v) {
    f[0] = blo(v.x); f[1] = bhi(v.x); f[2] = blo(v.y); f[3] = bhi(v.y); f[4] = blo(v.z); f[5] = bhi(v.z); f[6] = blo(v.w); f[7] = bhi(v.w);
}
__device__ __forceinline__ void vec_mat(float* o, const float* v, const uint4* __restrict__ W, int lane) {
    for (int k = 0; k < 8; k++) o[k] = 0.f;
    for (int l = 0; l < 32; l++) {
#pragma unroll
        for (int i = 0; i < 8; i++) {
            float a = __shfl_sync(~0u, v[i], l), wr[8];
            unpack8(wr, W[(l * 8 + i) * 32 + lane]);
#pragma unroll
            for (int k = 0; k < 8; k++) o[k] = fmaf(a, wr[k], o[k]);
        }
    }
}
__device__ __noinline__ uint4 attn_generic(int node, const uint4* __restrict__ x, const int* __restrict__ esrc, const int* __restrict__ edst,
                                           const uint4* __restrict__ wq, const uint4* __restrict__ wk, const uint4* __restrict__ wv) {
    int lane = threadIdx.x & 31;
    float xr[8], q[8], y[8], o[8];
    unpack8(xr, x[node * 32 + lane]);
    vec_mat(q, xr, wq, lane);
    for (int l = 0; l < 32; l++) {
#pragma unroll
        for (int i = 0; i < 8; i++) {
            float wr[8], p = 0.f;
            unpack8(wr, wk[(l * 8 + i) * 32 + lane]);
#pragma unroll
            for (int k = 0; k < 8; k++) p = fmaf(q[k], wr[k], p);
            for (int k = 16; k; k >>= 1) p += __shfl_xor_sync(~0u, p, k);
            if (lane == l) y[i] = p;
        }
    }
    for (int k = 0; k < 8; k++) o[k] = 0.f;
    float den = 0.f;
    for (int i0 = 0; i0 < NEE; i0 += 32) {
        unsigned m = __ballot_sync(~0u, edst[i0 + lane] == node);
        while (m) {
            int j = __ffs(m) - 1;
            m &= m - 1;
            float gq[8], p = 0.f;
            unpack8(gq, x[esrc[i0 + j] * 32 + lane]);
#pragma unroll
            for (int k = 0; k < 8; k++) p = fmaf(y[k], gq[k], p);
            for (int k = 16; k; k >>= 1) p += __shfl_xor_sync(~0u, p, k);
            float ex = __expf(p * 0.0625f);
            den += ex;
#pragma unroll
            for (int k = 0; k < 8; k++) o[k] = fmaf(ex, gq[k], o[k]);
        }
    }
    float inv = 1.f / (den + 1e-9f);
    for (int k = 0; k < 8; k++) o[k] *= inv;
    vec_mat(q, o, wv, lane);
    return make_uint4(pack2(q[0], q[1]), pack2(q[2], q[3]), pack2(q[4], q[5]), pack2(q[6], q[7]));
}

__device__ __forceinline__ unsigned hfma2(unsigned a, unsigned b, unsigned c) { unsigned r; asm("fma.rn.bf16x2 %0,%1,%2,%3;" : "=r"(r) : "r"(a), "r"(b), "r"(c)); return r; }
__device__ __forceinline__ unsigned hmul2(unsigned a, unsigned b) { unsigned r; asm("mul.rn.bf16x2 %0,%1,%2;" : "=r"(r) : "r"(a), "r"(b)); return r; }

__device__ __forceinline__ unsigned tile_addr(int n, unsigned chunk) { return sb + OFF_T + (chunk >> 3) * 10240 + n * 128 + (((chunk ^ n) & 7) << 4); }
__device__ __forceinline__ void attn_scores(float* v, bool mine, bool par, const uint4* gv, unsigned yaddr) {
    const uint4 y = ldsm4(yaddr);
    float c[4] = {0, 0, 0, 0}, e[4] = {0, 0, 0, 0};
    mma16816(c, gv[0].x, gv[0].y, gv[0].z, gv[0].w, y.x, y.y);
    mma16816(e, gv[2].x, gv[2].y, gv[2].z, gv[2].w, y.x, y.y);
    mma16816(c, gv[1].x, gv[1].y, gv[1].z, gv[1].w, y.z, y.w);
    mma16816(e, gv[3].x, gv[3].y, gv[3].z, gv[3].w, y.z, y.w);
    if (mine) { v[0] = par ? c[1] : c[0]; v[1] = par ? c[3] : c[2]; v[2] = par ? e[1] : e[0]; v[3] = par ? e[3] : e[2]; }
}
__device__ __forceinline__ void attn_softmax(const float* v, const float* u, unsigned lane, unsigned aladdr) {
    const bool hA = lane & 4, hB = lane & 8, hC = lane & 16;
    float a[4];
#pragma unroll
    for (int e = 0; e < 4; e++) a[e] = (hA ? u[e] : v[e]) + __shfl_xor_sync(~0u, hA ? v[e] : u[e], 4);
    float b0 = (hB ? a[1] : a[0]) + __shfl_xor_sync(~0u, hB ? a[0] : a[1], 9);
    float b1 = (hB ? a[3] : a[2]) + __shfl_xor_sync(~0u, hB ? a[2] : a[3], 9);
    float sc = (hC ? b1 : b0) + __shfl_xor_sync(~0u, hC ? b0 : b1, 18);
    float ex, inv;
    asm("ex2.approx.ftz.f32 %0,%1;" : "=f"(ex) : "f"(sc));
    float den = ex + __shfl_xor_sync(~0u, ex, 9);
    den += __shfl_xor_sync(~0u, den, 18);
    asm("rcp.approx.ftz.f32 %0,%1;" : "=f"(inv) : "f"(den + 1e-9f));
    sts32(aladdr, pack2(ex * inv, ex * inv));
    __syncwarp();
}
__device__ __forceinline__ void attn_mix(const uint4* gv, const uint4& a, unsigned oaddr) {
    const unsigned o0 = hfma2(a.w, gv[2].y, hfma2(a.z, gv[2].x, hfma2(a.y, gv[0].y, hmul2(a.x, gv[0].x))));
    const unsigned o1 = hfma2(a.w, gv[2].w, hfma2(a.z, gv[2].z, hfma2(a.y, gv[0].w, hmul2(a.x, gv[0].z))));
    const unsigned o2 = hfma2(a.w, gv[3].y, hfma2(a.z, gv[3].x, hfma2(a.y, gv[1].y, hmul2(a.x, gv[1].x))));
    const unsigned o3 = hfma2(a.w, gv[3].w, hfma2(a.z, gv[3].z, hfma2(a.y, gv[1].w, hmul2(a.x, gv[1].z))));
    asm volatile("stmatrix.sync.aligned.m8n8.x4.shared.b16 [%0],{%1,%2,%3,%4};" ::"r"(oaddr), "r"(o0), "r"(o1), "r"(o2), "r"(o3) : "memory");
}
__device__ __forceinline__ void pack_acc(unsigned* pk, const float* d) {
#pragma unroll
    for (int j = 0; j < 20; j++) pk[j] = pack2(d[2 * j], d[2 * j + 1]);
}
__device__ __forceinline__ void acc_to_tile(const unsigned* pk, int w, int lane) {
    const unsigned a = sb + OFF_T + (w >> 2) * 10240 + (lane >> 4) * 1024 + (lane & 7) * 128 + (((2 * (w & 3) + ((lane >> 3) & 1)) ^ (lane & 7)) << 4);
#pragma unroll
    for (int j = 0; j < 5; j++)
        asm volatile("stmatrix.sync.aligned.m8n8.x4.trans.shared.b16 [%0],{%1,%2,%3,%4};" ::"r"(a + j * 2048), "r"(pk[4 * j]), "r"(pk[4 * j + 1]), "r"(pk[4 * j + 2]), "r"(pk[4 * j + 3]) : "memory");
}
__device__ __forceinline__ unsigned movm(unsigned a) { unsigned d; asm volatile("movmatrix.sync.aligned.m8n8.trans.b16 %0,%1;" : "=r"(d) : "r"(a)); return d; }
__device__ __forceinline__ void tma_load2d(unsigned dst, const CUtensorMap* tm, int c0, int c1, unsigned bar) {
    asm volatile("cp.async.bulk.tensor.2d.shared::cluster.global.mbarrier::complete_tx::bytes [%0],[%1,{%3,%4}],[%2];"
                 ::"r"(dst), "l"(tm), "r"(bar), "r"(c0), "r"(c1) : "memory");
}
__device__ __forceinline__ void tma_load3d(unsigned dst, const CUtensorMap* tm, int row, unsigned bar) {
    asm volatile("cp.async.bulk.tensor.3d.shared::cluster.global.mbarrier::complete_tx::bytes [%0],[%1,{%4,%3,%4}],[%2];"
                 ::"r"(dst), "l"(tm), "r"(bar), "r"(row), "r"(0) : "memory");
}
__device__ __forceinline__ void cp16(unsigned dst, const void* src) { asm volatile("cp.async.cg.shared.global [%0],[%1],16;" ::"r"(dst), "l"(src) : "memory"); }
__device__ __forceinline__ void cp_commit() { asm volatile("cp.async.commit_group;" ::: "memory"); }
template <int N> __device__ __forceinline__ void cp_wait() { asm volatile("cp.async.wait_group %0;" ::"n"(N) : "memory"); }
__device__ __forceinline__ void nb_sync_id(int id, int n) { asm volatile("bar.sync %0,%1;" ::"r"(id), "r"(n) : "memory"); }
__device__ __forceinline__ void nb_arrive_id(int id, int n) { asm volatile("bar.arrive %0,%1;" ::"r"(id), "r"(n) : "memory"); }
template <int ID, int N> __device__ __forceinline__ void nb_sync() { asm volatile("bar.sync %0,%1;" ::"n"(ID), "n"(N) : "memory"); }
template <int ID, int N> __device__ __forceinline__ void nb_arrive() { asm volatile("bar.arrive %0,%1;" ::"n"(ID), "n"(N) : "memory"); }
__device__ __forceinline__ void mbar_init(unsigned a, int n) { asm volatile("mbarrier.init.shared.b64 [%0],%1;" ::"r"(a), "r"(n) : "memory"); }
__device__ __forceinline__ void mbar_expect(unsigned a, int n) { asm volatile("mbarrier.arrive.expect_tx.shared.b64 _,[%0],%1;" ::"r"(a), "r"(n) : "memory"); }
__device__ __forceinline__ void mbar_arrive(unsigned a) { asm volatile("mbarrier.arrive.shared.b64 _,[%0];" ::"r"(a) : "memory"); }

constexpr unsigned PADBIN = 2560;
__device__ __noinline__ void push_overflow(Scratch* sc, unsigned dst, unsigned src) {
    sc->ovf[blockIdx.x * OVCAP + atoms_inc(sb + OFF_MISC)] = (dst << 14) | src;
}
__device__ __noinline__ void bin_overflow(Scratch* sc, unsigned mask, unsigned ht) {
    for (int i = 0; i < 24 + 6 * 16; i++) {
        unsigned e;
        if (i < 24) {
            if (!(mask >> i & 1)) continue;
            e = lds32(sb + OFF_MAIL + (ht + (i >> 2) * 96) * 16 + (i & 3) * 4) & 0x7FFFFFFFu;
        } else {
            const int k = (i - 24) >> 4;
            if (!(mask >> (24 + k) & 1)) continue;
            e = __ldcg((const unsigned*)(sc->mail + ((NT + blockIdx.x) * 512 + ((ht + k * 96) & ~3u))) + ((i - 24) & 15));
        }
        if (e < (PADBIN << 16))
            push_overflow(sc, blockIdx.x * TILE + ((e >> 21) & ~3u) + ((e >> 18) & 3), e & 0xFFFF);
    }
}
__device__ __forceinline__ void place(unsigned e, unsigned r, unsigned w) {
    const unsigned p = r + (w >> 16), t2 = r * 0x801 + w;
    const unsigned tt = p < 32 ? p * 0x808 : t2, bin = p < 32 ? e >> 16 : bitsel(t2 << 2, e >> 16, 0x1070);
    asm volatile("{.reg .pred p; setp.lt.u32 p,%2,%3; @p st.shared.u16 [%0],%1;}"
                 ::"r"(sb + OFF_IMG + bitsel(tt >> 4, bin, 0x18E)), "h"((unsigned short)e), "r"(e), "n"(PADBIN << 16) : "memory");
}
__device__ __forceinline__ unsigned place_slow(unsigned e, unsigned r, unsigned w, unsigned broken) {
    if (r + (w >> 16) < 32) { place(e, r, w); return 0; }
    if (e >= (PADBIN << 16)) return 0;
    if (broken >> (e >> 25) & 1) return 1;
    const unsigned q = (r + w) & 0xFF;
    asm volatile("st.shared.u16 [%0],%1;" ::"r"(sb + OFF_IMG + (q < 192 ? 8192 : 4096) + (e >> 25) * 512 + (q & 3) * 128 + (q & 28) * 4 + (q >> 5) * 2), "h"((unsigned short)e) : "memory");
    return 0;
}
__device__ __forceinline__ void bulk_s2g(void* dst, unsigned src, unsigned bytes) {
    asm volatile("cp.async.bulk.global.shared::cta.bulk_group [%0],[%1],%2;" ::"l"(dst), "r"(src), "r"(bytes) : "memory");
}
__device__ __forceinline__ void tma_reduce(const CUtensorMap* tm, unsigned src, int c0, int c1) {
    asm volatile("cp.reduce.async.bulk.tensor.2d.global.shared::cta.add.tile.bulk_group [%0,{%2,%3}],[%1];" ::"l"(tm), "r"(src), "r"(c0), "r"(c1) : "memory");
}
#define EV(id) nb_arrive<id, 544>()
#define WAIT_EV(id) do { __syncwarp(); nb_sync<id, 544>(); } while (0)

__global__ void __launch_bounds__(640, 1)
exphormer_kernel(const uint4* __restrict__ x, const uint4* __restrict__ dst4, const uint4* __restrict__ src4,
                 const uint4* __restrict__ wq, const uint4* __restrict__ wk, const int* __restrict__ esrc,
                 const int* __restrict__ edst, Scratch* __restrict__ sc, const uint4* __restrict__ dis, const uint4* __restrict__ wv,
                 const __grid_constant__ CUtensorMap tm_x, const __grid_constant__ CUtensorMap tm_wl, const __grid_constant__ CUtensorMap tm_wv,
                 const __grid_constant__ CUtensorMap tm_m, const __grid_constant__ CUtensorMap tm_ms,
                 const __grid_constant__ CUtensorMap tm_mail, const __grid_constant__ CUtensorMap tm_ot, const __grid_constant__ CUtensorMap tm_o256, const __grid_constant__ CUtensorMap tm_o16) {
    const unsigned tid = threadIdx.x, lane = tid & 31, g = lane >> 2, t = lane & 3;
    const unsigned b = blockIdx.x;
    const bool rowcta = b < NT;
    const int slice = b >> 2, range = b & 3;
    const int g0 = (range * NG) >> 2, g1 = ((range + 1) * NG) >> 2;
    STAMP(0);

    if (tid >= 512) {
    asm volatile("setmaxnreg.dec.sync.aligned.u32 %0;" ::"n"(REG_H));
    if (tid >= 544) {
        const unsigned ht = tid - 544;
        if (ht < 32) {
            if (lane == 0) asm volatile("prefetch.tensormap [%0];" ::"l"(&tm_mail) : "memory");
            __syncwarp();
            nb_sync<13, 160>();
            nb_sync<2, 352>();
            if (rowcta) {
                const uint4 c = lds128(sb + OFF_CNT1 + lane * 16);
                const unsigned cc[4] = {c.x, c.y, c.z, c.w};
#pragma unroll
                for (int i = 0; i < 4; i++)
                    if (cc[i] > 16) asm volatile("red.shared.or.b32 [%0],0x80000000;" ::"r"(sb + OFF_MAIL + (lane * 4 + i) * 64 + 60) : "memory");
                fence_async_smem();
                __syncwarp();
                if (elect())
                    asm volatile("cp.async.bulk.tensor.2d.global.shared::cta.bulk_group [%0,{%2,%3}],[%1];" ::"l"(&tm_mail), "r"(sb + OFF_MAIL), "r"(b * 16), "r"(0) : "memory");
                for (int i = 0; i < 4; i++)
                    if (lds32(sb + OFF_CNT1 + lane * 16 + i * 4) > 16) bulk_s2g(sc->mail + ((NT + lane * 4 + i) * 512 + b * 4), sb + OFF_IMG + (lane * 4 + i) * 64, 64);
                asm volatile("cp.async.bulk.commit_group;" ::: "memory");
                asm volatile("cp.async.bulk.wait_group 0;" ::: "memory");
                fence_async_gmem();
                __syncwarp();
            }
            if (rowcta) nb_arrive<1, 96>();
            if (elect()) {
                bar_arrive_relaxed(&sc->bar[0]);
                STAMPT(544, 47);
                if (rowcta) {
                    bar_poll(sc, 0);
                    fence_async_gmem();
                    mbar_expect(bar_mail, 8000);
                    bulk_g2s(sb + OFF_MAIL, sc->mail + b * 512, 8000, bar_mail);
                }
            }
            __syncwarp();
        } else if (ht < 64) {
            if (lane == 0) asm volatile("prefetch.tensormap [%0];" ::"l"(&tm_ms) : "memory");
            nb_sync<14, 192>();
            if (elect()) {
                asm volatile("cp.async.bulk.tensor.2d.global.shared::cta.bulk_group [%0,{%2,%3}],[%1];" ::"l"(&tm_ms), "r"(sb + OFF_MAIL + 8064), "r"((b & 7) * 32), "r"((b >> 3) * 16) : "memory");
                asm volatile("cp.async.bulk.commit_group;" ::: "memory");
                asm volatile("cp.async.bulk.wait_group 0;" ::: "memory");
                fence_async_gmem();
                bar_arrive_relaxed(&sc->bar[3 * 64]);
                STAMPT(576, 46);
            }
            __syncwarp();
        } else {
            if (lane < 5) {
                unsigned epoch;
                asm volatile("ld.relaxed.gpu.global.u32 %0,[%1];" : "=r"(epoch) : "l"(&sc->bar[lane * 64]) : "memory");
                sts32(sb + OFF_MISC + 32 + lane * 4, (epoch & ~(NCTA - 1)) + NCTA);
            }
            __syncwarp();
            nb_arrive<14, 192>();
            nb_arrive<15, 64>();
            nb_arrive<13, 160>();
        }
        if (rowcta) {
            if (ht >= 32) {
                nb_sync<1, 96>();
                const unsigned pad = (PADBIN + 4 * lane) << 16, h2 = ht - 32;
                sts128(sb + OFF_MAIL + 8000 + h2 * 16, make_uint4(pad, pad, pad, pad));
                if (h2 < 12) sts128(sb + OFF_MAIL + 9024 + h2 * 16, make_uint4(pad, pad, pad, pad));
#pragma unroll
                for (int k = 0; k < 9; k++) {
                    const unsigned dm = k < 3 ? DUMMY2 + (lane & 7) * 0x10001u : DUMMY2;
                    if (k % 3 < 2 || h2 < 32) sts128(sb + OFF_IMG + (k / 3) * 4096 + (k % 3) * 1024 + h2 * 16, make_uint4(dm, dm, dm, dm));
                }
            }
            nb_sync<13, 96>();
            mbar_wait(bar_mail);
            STAMPT(576, 16);
            uint4 e[6], h[6];
            unsigned flagged = 0, late = 0, longg = 0;
#pragma unroll
            for (int k = 0; k < 6; k++) e[k] = lds128(sb + OFF_MAIL + (ht + k * 96) * 16);
#pragma unroll
            for (int k = 0; k < 6; k++) { flagged |= (e[k].w >> 31) << k; e[k].w &= 0x7FFFFFFFu; }
            while (flagged) {
                const unsigned f = __ffs(flagged) - 1, k = atoms_add(sb + OFF_MISC + 4, 4);
                const uint4* sp = sc->mail + ((NT + b) * 512 + ((ht + f * 96) & ~3u));
                flagged &= flagged - 1;
                if (k < 76) {
#pragma unroll
                    for (int j = 0; j < 4; j++) cp16(sb + OFF_MAIL + 8000 + (k + j) * 16, sp + j);
                } else {
                    late |= 1u << (24 + f);
                }
            }
            cp_commit();
            __syncwarp();
#pragma unroll
            for (int k = 0; k < 6; k++) {
                if (k == 5) { cp_wait<0>(); nb_sync<1, 96>(); if (ht >= 20) e[5] = lds128(sb + OFF_MAIL + (ht + 480) * 16); }
                h[k] = make_uint4(atoms_inc(sb + OFF_CNT2 + (e[k].x >> 16)), atoms_inc(sb + OFF_CNT2 + (e[k].y >> 16)),
                                  atoms_inc(sb + OFF_CNT2 + (e[k].z >> 16)), atoms_inc(sb + OFF_CNT2 + (e[k].w >> 16)));
            }
            nb_sync<1, 96>();
            STAMPT(576, 17);
            unsigned rare;
            {
                const bool sw = lane >= 16;
                const unsigned G0 = ht >> 5, G1 = min(G0 + 3, 4u);
                uint4 c[2];
                unsigned inc[2], st[2][4], lf[2], ex[2], xs[2], word[2], s2w[2], dp[2];
#pragma unroll
                for (int j = 0; j < 2; j++) c[j] = lds128(sb + OFF_CNT2 + (j ? G1 : G0) * 512 + lane * 16);
#pragma unroll
                for (int j = 0; j < 2; j++) dp[j] = lds32(sb + OFF_DIS + ((j ? G1 : G0) * 8 + g) * 4);
#pragma unroll
                for (int j = 0; j < 2; j++) { inc[j] = c[j].x + c[j].y + c[j].z + c[j].w; const unsigned u = __shfl_up_sync(~0u, inc[j], 8); if (lane >= 8) inc[j] += u; }
#pragma unroll
                for (int j = 0; j < 2; j++) { const unsigned u = __shfl_up_sync(~0u, inc[j], 16); if (sw) inc[j] += u; }
#pragma unroll
                for (int j = 0; j < 2; j++) {
                    const unsigned s2 = c[j].x + c[j].y;
                    st[j][0] = inc[j] - s2 - c[j].z - c[j].w; st[j][1] = st[j][0] + (sw ? c[j].y : c[j].x);
                    st[j][2] = st[j][0] + s2; st[j][3] = st[j][2] + (sw ? c[j].w : c[j].z);
                    const unsigned m0 = max(st[j][0], 32u), m1 = max(st[j][1], 32u), m2 = max(st[j][2], 32u), m3 = max(st[j][3], 32u), m4 = max(inc[j], 32u);
                    const unsigned Q = __reduce_add_sync(~0u, m4 - m0);
                    lf[j] = Q <= QCAP ? (m1 - m0) | (m2 - m1) << 8 | (m3 - m2) << 16 | (m4 - m3) << 24 : 0;
                    xs[j] = __reduce_add_sync(~0u, Q <= QCAP ? (m4 - m0) << (lane & 24) : 0);
                    if (Q > 64 && (j == 0 || ht < 64)) longg |= (Q <= QCAP ? 1u : 0x100u) << (j ? G1 : G0);
                    word[j] = min(st[j][0], 32u) | min(st[j][1], 32u) << 8 | min(st[j][2], 32u) << 16 | min(st[j][3], 32u) << 24;
                    ex[j] = lf[j];
                }
#pragma unroll
                for (int d = 1; d < 8; d <<= 1)
#pragma unroll
                    for (int j = 0; j < 2; j++) { const unsigned u = __shfl_up_sync(~0u, ex[j], d); if ((lane & 7) >= d) ex[j] += u; }
#pragma unroll
                for (int j = 0; j < 2; j++) {
                    const unsigned tot = __shfl_sync(~0u, ex[j], lane | 7);
                    s2w[j] = tot * 0x01010100u + (((xs[j] * 0x01010100u) >> (lane & 24)) & 255) * 0x01010101u;
                    const unsigned q0 = s2w[j] + ex[j] - lf[j];
                    unsigned w4[4];
#pragma unroll
                    for (int i = 0; i < 4; i++)
                        w4[i] = __byte_perm((((q0 >> (8 * i)) & 255) + 192 + st[j][i] - max(st[j][i], 32u)) * 0x801 + 0x400, min(st[j][i], 32u), 0x5410);
                    if (j == 0 || ht < 64)
                        sts128(sb + OFF_CNT2 + (j ? G1 : G0) * 512 + lane * 16, make_uint4(sw ? w4[1] : w4[0], sw ? w4[0] : w4[1], sw ? w4[3] : w4[2], sw ? w4[2] : w4[3]));
                }
                if (longg && lane == 0) asm volatile("red.shared.or.b32 [%0],%1;" ::"r"(sb + OFF_MISC + 8), "r"(longg) : "memory");
                asm volatile("{.reg .pred p; setp.ne.u32 p,%1,0; bar.red.popc.u32 %0,1,96,p;}" : "=r"(rare) : "r"(longg) : "memory");
#pragma unroll
                for (int j = 0; j < 2; j++) {
                    const unsigned wa = __shfl_sync(~0u, word[j], (g >> 1) * 8 + 2 * t), wb = __shfl_sync(~0u, word[j], (g >> 1) * 8 + 2 * t + 1);
                    const unsigned w2 = s2w[j];
                    const unsigned d128 = hmul2(dp[j], 0x43004300u);
                    const unsigned ha = sb + OFF_IMG + 4096 + (j ? G1 : G0) * 512 + lane * 16;
                    if (j == 0 || ht < 64) {
                        asm volatile("st.shared.v2.u32 [%0],{%1,%2};" ::"r"(ha), "r"(__byte_perm(wa, wb, (g & 1) ? 0x7362 : 0x5140)),
                                     "r"(__byte_perm(w2, w2, (g & 1) ? 0x3322 : 0x1100) + 0x1C201C20u - t * 0x08080808u) : "memory");
                        sts32(ha + 8, __byte_perm(d128, d128, lane >= 16 ? 0x1032 : 0x3210));
                    }
                }
            }
            if (__builtin_expect(!rare, 1)) {
#pragma unroll
                for (int k0 = 0; k0 < 6; k0 += 2) {
                    uint4 w[2];
#pragma unroll
                    for (int k = k0; k < k0 + 2; k++) { e[k] = lds128(sb + OFF_MAIL + (ht + k * 96) * 16); e[k].w &= 0x7FFFFFFFu; }
#pragma unroll
                    for (int k = k0; k < k0 + 2; k++)
                        w[k - k0] = make_uint4(lds32(sb + OFF_CNT2 + (e[k].x >> 16)), lds32(sb + OFF_CNT2 + (e[k].y >> 16)),
                                               lds32(sb + OFF_CNT2 + (e[k].z >> 16)), lds32(sb + OFF_CNT2 + (e[k].w >> 16)));
#pragma unroll
                    for (int k = k0; k < k0 + 2; k++) {
                        place(e[k].x, h[k].x, w[k - k0].x); place(e[k].y, h[k].y, w[k - k0].y); place(e[k].z, h[k].z, w[k - k0].z); place(e[k].w, h[k].w, w[k - k0].w);
                    }
                }
            } else {
                const unsigned broken = lds32(sb + OFF_MISC + 8) >> 8;
#pragma unroll
                for (int k = 0; k < 6; k++) {
                    uint4 v = lds128(sb + OFF_MAIL + (ht + k * 96) * 16);
                    v.w &= 0x7FFFFFFFu;
                    late |= place_slow(v.x, h[k].x, lds32(sb + OFF_CNT2 + (v.x >> 16)), broken) << (4 * k);
                    late |= place_slow(v.y, h[k].y, lds32(sb + OFF_CNT2 + (v.y >> 16)), broken) << (4 * k + 1);
                    late |= place_slow(v.z, h[k].z, lds32(sb + OFF_CNT2 + (v.z >> 16)), broken) << (4 * k + 2);
                    late |= place_slow(v.w, h[k].w, lds32(sb + OFF_CNT2 + (v.w >> 16)), broken) << (4 * k + 3);
                }
                nb_sync<1, 96>();
                for (longg &= 255; longg; longg &= longg - 1)
                    asm volatile("red.shared.or.b32 [%0],0x80000000;" ::"r"(sb + OFF_IMG + 4096 + (__ffs(longg) - 1) * 512 + lane * 16 + 12) : "memory");
            }
            if (__builtin_expect(late, 0)) bin_overflow(sc, late, ht);
            nb_sync<1, 96>();
            STAMPT(576, 18);
        }
        if (ht < 32 && elect()) {
            if (rowcta) {
                fence_async_smem();
                for (int c = 0; c < 3; c++) bulk_s2g(sc->lists + (c * LSTR + b * 160), sb + OFF_IMG + c * 4096, 2560);
                asm volatile("cp.async.bulk.commit_group;" ::: "memory");
                const unsigned novf = lds32(sb + OFF_MISC), bad = lds32(sb + OFF_MISC + 20);
                if (__builtin_expect(novf | bad, 0)) {
                    sc->ovfn[b] = make_uint2(lds32(sb + OFF_MISC + 48), novf);
                    raise_flag(&sc->bar[4 * 64 + 1], lds32(sb + OFF_MISC + 48), (novf ? 1 : 0) | (bad ? 2 : 0));
                    __threadfence();
                }
                asm volatile("cp.async.bulk.wait_group 0;" ::: "memory");
                fence_async_gmem();
            }
            bar_arrive_relaxed(&sc->bar[4 * 64]);
            STAMPT(544, 19);
            sts32(sb + OFF_MISC + 28, bar_poll2(&sc->bar[4 * 64], lds32(sb + OFF_MISC + 48)));
            mbar_arrive(bar_c);
            STAMPT(544, 23);
        }
    } else {
        const bool one = elect();
        auto load_xl = [&](int i) {
            mbar_expect(bar_full + 8 * i, 32768 + 10240);
            tma_load2d(sb + OFF_T + i * 10240, &tm_x, i * 64, b * TILE, bar_full + 8 * i);
            tma_load3d(sb + OFF_S + i * 32768, &tm_wl, i * 64, bar_full + 8 * i);
        };
        auto load_m = [&](int i, int slot) {
            mbar_expect(bar_full + 32 + 8 * i, 32768);
            tma_load3d(sb + OFF_S + slot * 32768, &tm_m, i * 64, bar_full + 32 + 8 * i);
        };
        auto load_v = [&](int i, int slot) {
            mbar_expect(bar_full + 64 + 8 * i, 32768);
            tma_load3d(sb + OFF_S + slot * 32768, &tm_wv, i * 64, bar_full + 64 + 8 * i);
        };
        const char* hsl = (const char*)(sc->hs + slice * NN);
        auto fill = [&](int slot) { bulk_g2s(sb + OFF_S + slot * 32768, hsl + slot * 32768, slot == 4 ? NN * 16 - 4 * 32768 : 32768, bar_fill); };
        const unsigned t0 = clock();
        if (one) {
            for (int i = 0; i < 2; i++) mbar_init(bar_full + 8 * i, 1);
            asm volatile("fence.mbarrier_init.release.cluster;" ::: "memory");
            while ((unsigned)clock() - t0 < XD0) {}
            if (rowcta) load_xl(0);
            STAMPT(512, 41);
            for (int i = 2; i < 12; i++) mbar_init(bar_full + 8 * i, 1);
            mbar_init(bar_go, 1);
            for (int i = 0; i < 4; i++) mbar_init(bar_fill + 8 * i, 1);
            for (int i = 0; i < 10; i++) mbar_init(bar_rd + 8 * i, i < 9 ? 16 : g1 - g0 - 144);
            asm volatile("fence.mbarrier_init.release.cluster;" ::: "memory");
            if ((unsigned)__cvta_generic_to_shared(smem_raw) != sb) __trap();
            mbar_expect(bar_fill, NN * 16);
        }
        __syncwarp();
        nb_arrive<3, 544>();
        nb_arrive<13, 160>();
        if (one && rowcta) {
            while ((unsigned)clock() - t0 < XD1) {}
            load_xl(1);
            STAMPT(512, 40);
        }
        __syncwarp();
        nb_sync<15, 64>();
        if (rowcta) {
            if (one) {
                if (XD2) { while ((unsigned)clock() - t0 < XD2 + 1) {} } else mbar_wait(bar_full);
                load_xl(2);
                STAMPT(512, 52);
                mbar_wait(bar_full + (XD2 ? 0 : 8)); load_xl(3);
                STAMPT(512, 53);
                asm volatile("cp.async.bulk.prefetch.L2.global [%0],%1;" ::"l"(wv + b * 64), "r"(b == NT - 1 ? 4096 : 1024) : "memory");
                asm volatile("prefetch.tensormap [%0];" ::"l"(&tm_m) : "memory");
                asm volatile("prefetch.tensormap [%0];" ::"l"(&tm_wv) : "memory");
                bar_poll(sc, 3);
                STAMPT(512, 48);
                fence_async_gmem();
            }
            WAIT_EV(5); if (one) { load_m(0, 0); load_m(1, 1); mbar_arrive(bar_go); }
            WAIT_EV(6); if (one) load_m(2, 3);
            WAIT_EV(7); if (one) load_m(3, 0);
            WAIT_EV(12); if (one) bar_arrive(&sc->bar[2 * 64]);
            STAMPT(512, 24);
            WAIT_EV(14); if (one) { fence_async_smem(); load_v(0, 4); load_v(1, 2); }
            WAIT_EV(15);
            if (one) {
                fence_async_smem();
                load_v(2, 1); load_v(3, 3);
                bar_poll(sc, 2);
                fence_async_gmem();
            }
            STAMPT(512, 25);
            WAIT_EV(2); STAMPT(512, 1); if (one) { fill(0); if (VRS > 0) fill(4); if (VRS > 1) fill(2); }
            WAIT_EV(4); if (one) fill(1);
            WAIT_EV(5); if (one) fill(3);
            if (VRS < 2) { WAIT_EV(6); if (one) fill(2); }
            if (VRS < 1) { WAIT_EV(7); if (one) fill(4); }
            WAIT_EV(12);
            STAMPT(512, 15);
            if (one) {
                fence_async_smem();
#pragma unroll
                for (int kb = 0; kb < 4; kb++)
                    asm volatile("cp.async.bulk.tensor.2d.global.shared::cta.bulk_group [%0,{%2,%3}],[%1];"
                                 ::"l"(&tm_ot), "r"(sb + OFF_T + kb * 10240), "r"(kb * 64), "r"(b * TILE) : "memory");
                asm volatile("cp.async.bulk.commit_group;" ::: "memory");
                asm volatile("cp.async.bulk.wait_group 0;" ::: "memory");
                fence_async_gmem();
            }
        } else {
            if (one) {
                bar_arrive(&sc->bar[2 * 64]);
                bar_poll(sc, 2);
                fence_async_gmem(); fence_async_smem();
                for (int i = 0; i < 5; i++) fill(i);
            }
        }
        if (one) {
            bar_arrive_relaxed(&sc->bar[1 * 64]);
            mbar_arrive(bar_t);
            STAMPT(512, 26);
            bar_poll(sc, 1);
            fence_async_gmem();
            STAMPT(512, 27);
            unsigned tn = clock();
#pragma unroll 1
            for (int r = 0; r < 9; r++) {
                mbar_wait(bar_rd + 8 * r);
                fence_async_smem();
#pragma unroll
                for (int i = 0; i < 256 / PBOX; i++) {
                    while ((int)(clock() - tn) < 0) __nanosleep(20);
                    tn = clock() + PACE;
                    tma_reduce(&tm_o256, sb + OFF_STG + r * 4096 + i * PBOX * 16, slice * 8, (g0 + 16 * r) * 16 + i * PBOX);
                }
            }
            mbar_wait(bar_rd + 72);
            STAMPT(512, 14);
            fence_async_smem();
            for (int i = 144; i < g1 - g0; i++) tma_reduce(&tm_o16, sb + OFF_STG + i * 256, slice * 8, (g0 + i) * 16);
            asm volatile("cp.async.bulk.commit_group;" ::: "memory");
            asm volatile("cp.async.bulk.wait_group.read 0;" ::: "memory");
            STAMPT(512, 13);
        }
    }
    } else {
    if (tid < 32) {
        unsigned bad = 0;
        uint4 xd[3];
#pragma unroll
        for (int k = 0; k < 3; k++) xd[k] = ldg_na((const uint4*)edst + min(b * TILE + k * 32 + lane, NN - 1u));
#pragma unroll
        for (int k = 0; k < 3; k++) { const unsigned n = min(b * TILE + k * 32 + lane, NN - 1u); bad |= (xd[k].x ^ n) | (xd[k].y ^ n) | (xd[k].z ^ n) | (xd[k].w ^ n); }
        bad = __any_sync(~0u, bad);
        if (lane == 0) sts32(sb + OFF_MISC + 20, bad);
        __syncwarp();
        nb_arrive<13, 160>();
    } else if (tid < 64) {
        const uint4* ep = (const uint4*)esrc + (min(b, NT - 1u) * TILE + lane);
        cp16(sb + OFF_EIDX + lane * 16, ep); cp16(sb + OFF_EIDX + 512 + lane * 16, ep + 32);
        if (lane < 16) cp16(sb + OFF_EIDX + 1024 + lane * 16, ep + 64);
        if (lane < 10) cp16(sb + OFF_DIS + lane * 16, dis + (min(b, NT - 1u) * 10 + lane));
        cp_commit();
        cp_wait<0>();
        nb_arrive<13, 160>();
    } else if (tid >= 192) {
        if (rowcta) {
            const unsigned bt = tid - 192;
            if (ED0) { const unsigned t0 = clock(); while ((unsigned)clock() - t0 < ED0 + 1) {} }
            const uint4 ed = ldg_na(dst4 + (b * 320 + bt)), es = ldg_na(src4 + (b * 320 + bt));
            const unsigned pad = (PADBIN + 4 * ((bt & 3) + ((b * 4) & 28))) << 16;
#pragma unroll
            for (int k = 0; k < 4; k++) if ((k & 1) == 0 || bt < 180) sts128(sb + OFF_MAIL + (k >> 1) * 9216 + (bt + (k & 1) * 320) * 16, make_uint4(pad, pad, pad, pad));
            if (bt < (512 + 2688) / 16) sts128(sb + OFF_CNT1 + bt * 16, make_uint4(0, 0, 0, 0));
            if (bt == 319) sts128(sb + OFF_MISC, make_uint4(0, 0, 0, 0));
            unsigned z;
            asm volatile("{.reg .pred p; setp.eq.u32 p,%1,0xFFFFFFFF; bar.red.popc.u32 %0,4,320,p;}" : "=r"(z) : "r"(bt) : "memory");
            const unsigned dd[4] = {ed.x + z, ed.y + z, ed.z + z, ed.w + z}, ss[4] = {es.x + z, es.y + z, es.z + z, es.w + z};
            unsigned rk[4], ow[4];
#pragma unroll
            for (int i = 0; i < 4; i++) { ow[i] = dd[i] / TILE; rk[i] = atoms_inc(sb + OFF_CNT1 + ow[i] * 4); }
#pragma unroll
            for (int i = 0; i < 4; i++) {
                const unsigned dl = dd[i] - ow[i] * TILE;
                const unsigned e = bitsel(ss[i] << 20, bitsel(dl << 21, dl << 18, 0xFF800000u), 0x00700000u) + ss[i];
                asm volatile("{.reg .pred p; setp.lt.u32 p,%2,%3; @p st.shared.u32 [%0],%1;}" ::"r"(sb + OFF_MAIL + ow[i] * 64 + rk[i] * 4 + (rk[i] >> 4) * (9216 - 64)), "r"(e), "r"(rk[i]), "n"(CELL) : "memory");
            }
            if (__builtin_expect((rk[0] | rk[1] | rk[2] | rk[3]) >= CELL, 0)) {
#pragma unroll
                for (int i = 0; i < 4; i++) if (rk[i] >= CELL) push_overflow(sc, dd[i], ss[i]);
            }
        }
        STAMPT(416, 44);
        nb_arrive<2, 352>();
    } else {
        const unsigned fw = b >> 3, hq = b & 7, q = (tid >> 5) - 2;
        const unsigned ma = sb + OFF_S + 4 * 32768 + 8192 + q * 6144;
        {
            const unsigned r = lane >> 3, da = ma + r * 128 + (((lane ^ r) & 7) << 4);
            const uint4* pa = wq + ((16 * fw + r) * 32 + q * 8 + (lane & 7));
            const uint4* pb = wk + ((32 * hq + r) * 32 + q * 8 + (lane & 7));
#pragma unroll
            for (int u = 0; u < 12; u++) cp16((da ^ ((u & 1) << 6)) + u * 512, u < 4 ? pa + u * 128 : pb + (u - 4) * 128);
            cp_commit();
        }
        const unsigned aa = ma + (lane & 15) * 128 + ((((lane >> 4) ^ lane) & 7) << 4);
        const unsigned br = 4 * ((lane & 7) >> 1) + 2 * (lane >> 4) + (lane & 1);
        const unsigned ba = ma + 2048 + br * 128 + (((((lane >> 3) & 1) ^ br) & 7) << 4);
        float c[4][4];
#pragma unroll
        for (int u = 0; u < 4; u++) c[u][0] = c[u][1] = c[u][2] = c[u][3] = 0.f;
        STAMPT(64, 38);
        cp_wait<0>();
        __syncwarp();
        STAMPT(64, 39);
#pragma unroll
        for (int k = 0; k < 4; k++) {
            const uint4 a = ldsm4(aa ^ (k << 5)), b0 = ldsm4(ba ^ (k << 5)), b1 = ldsm4((ba ^ (k << 5)) + 2048);
            mma16816(c[0], a.x, a.y, a.z, a.w, b0.x, b0.y); mma16816(c[1], a.x, a.y, a.z, a.w, b0.z, b0.w);
            mma16816(c[2], a.x, a.y, a.z, a.w, b1.x, b1.y); mma16816(c[3], a.x, a.y, a.z, a.w, b1.z, b1.w);
        }
        const unsigned ra = sb + OFF_S + 4 * 32768 + lane * 16;
#pragma unroll
        for (int i = 0; i < 4; i++)
            sts128(ra + q * 2048 + i * 512, make_uint4(__float_as_uint(c[2 * (i & 1)][2 * (i >> 1)]), __float_as_uint(c[2 * (i & 1)][2 * (i >> 1) + 1]),
                                                       __float_as_uint(c[2 * (i & 1) + 1][2 * (i >> 1)]), __float_as_uint(c[2 * (i & 1) + 1][2 * (i >> 1) + 1])));
        STAMPT(64, 42);
        nb_sync<8, 128>();
        float m[4] = {0, 0, 0, 0};
#pragma unroll
        for (int i = 0; i < 4; i++) {
            const uint4 u = lds128(ra + i * 2048 + q * 512);
            m[0] += __uint_as_float(u.x); m[1] += __uint_as_float(u.y); m[2] += __uint_as_float(u.z); m[3] += __uint_as_float(u.w);
        }
        const float k = 0.0625f * 1.4426950408889634f;
        asm volatile("st.shared.v2.u32 [%0],{%1,%2};" ::"r"(sb + OFF_MAIL + 8064 + (8 * (q >> 1) + g) * 64 + (q & 1) * 32 + t * 8),
                     "r"(pack2(m[0] * k, m[1] * k)), "r"(pack2(m[2] * k, m[3] * k)) : "memory");
        fence_async_smem();
        STAMPT(64, 43);
        nb_arrive<14, 192>();
    }
    asm volatile("setmaxnreg.inc.sync.aligned.u32 %0;" ::"n"(REG_W));
    const int w = __shfl_sync(~0u, tid >> 5, 0), wg = w >> 2;
    const int grp0 = g0 + w;
    const uint4* lp = sc->lists + (grp0 * 32 + lane);
    uint4 L0, L1;
    nb_sync<3, 544>();

    if (__builtin_expect(rowcta, 1)) {
        const unsigned descA = 0x10000u + (SB0 + OFF_S) / 16 + wg * 512;
        const unsigned greg = sb + OFF_S + w * 2048 + lane * 16;
        float d[40];
        unsigned pk[20];
        unsigned* hp = (unsigned*)(sc->hs + (2 * w * NN + b * TILE)) + lane;
        auto mma_k = [&](int Q, int slot, int st, int k0, int k1) {
            if (st < 0) wg_fence();
#pragma unroll
            for (int k = k0; k < k1; k++) {
                if (st >= 0) wg_fence();
                wg80(d, descA + slot * 2048 + k * 128, 0x10000u + (SB0 + OFF_T) / 16 + (Q & 3) * 640 + k * 2, st == -2 ? k != 0 : st == -3 || ((Q & 3) | k) != 0);
                if (st >= 0) {
#pragma unroll
                    for (int j = st + k; j < st + k + 1; j++)
                        if (j < 20) asm volatile("st.global.u32 [%0],%1;" ::"l"(hp + (j >> 1) * 32 + (j & 1) * (NN * 4)), "r"(pk[j]) : "memory");
                }
            }
            wg_commit();
        };
        auto mma_q = [&](int Q, int slot, int st) { mma_k(Q, slot, st, 0, 4); };
        auto mma_head = [&](int Q, int slot, int st) { mma_k(Q, slot, st, 0, KH); wg_wait<1>(); };
        auto mma_tail = [&](int Q, int slot, int st) { mma_k(Q, slot, st, KH, 4); };
        const uint4* xl = x + lane;
        auto eidx = [&](int i) { return lds128(sb + OFF_EIDX + (w * 5 + i) * 16); };
        auto gather = [&](const uint4& ix, int slot) {
            cp16(greg + slot * 32768, xl + ix.x * 32u); cp16(greg + slot * 32768 + 512, xl + ix.y * 32u);
            cp16(greg + slot * 32768 + 1024, xl + ix.z * 32u); cp16(greg + slot * 32768 + 1536, xl + ix.w * 32u);
            cp_commit();
        };
        const uint4 ix0 = eidx(0), ix1 = eidx(1), ix2 = eidx(2), ix3 = eidx(3), ix4 = eidx(4);
        uint4 gv[5][4];
        const unsigned gld = sb + OFF_S + w * 2048 + ((lane >> 3) & 1) * 512 + (lane >> 4) * 128 + (lane & 7) * 16;
        auto to_regs = [&](int i, int slot) {
            __syncwarp();
#pragma unroll
            for (int j = 0; j < 4; j++) gv[i][j] = ldsm4(gld + slot * 32768 + (j & 1) * 256 + (j >> 1) * 1024);
        };
        unsigned ds[10];
#pragma unroll
        for (int j = 0; j < 10; j++) ds[j] = lds32(sb + OFF_DIS + (4 * j + t) * 4);
        STAMPT(288, 2);
        mbar_wait(bar_full);
        STAMPT(288, 3);
        mma_q(0, 0, -1);
        mbar_wait(bar_full + 8);
        STAMPT(288, 50);
        mma_q(1, 1, -1);
        mbar_wait(bar_full + 16);
        STAMPT(288, 51);
        mma_head(2, 2, -1);
        EV(5);
        mma_tail(2, 2, -1);
        mbar_wait(bar_full + 24);
        STAMP(5);
        mma_q(3, 3, -1);
        mbar_wait(bar_go);
        gather(ix0, 4);
        wg_wait<0>();
        EV(6);
        STAMP(6);
#pragma unroll
        for (int j = 0; j < 20; j++) pk[j] = movm(hmul2(pack2(d[2 * j], d[2 * j + 1]), ds[j >> 1]));
#pragma unroll
        for (int j = 0; j < STPRE; j++) asm volatile("st.global.u32 [%0],%1;" ::"l"(hp + (j >> 1) * 32 + (j & 1) * (NN * 4)), "r"(pk[j]) : "memory");
        STAMP(7);
        if (G1POS < 2) nb_sync_id(8 + wg, 128);
        if (G1POS == 0) gather(ix1, 2);
        mbar_wait(bar_full + 32);
        if (G1POS == 1) { if (G0POS == 2) gather(ix0, 4); gather(ix1, 2); }
        STAMP(21);
        if (G1POS == 2) {
            mma_k(4, 0, STPRE, 0, 1);
            if (G0POS == 2) gather(ix0, 4);
            nb_sync_id(8 + wg, 128);
            gather(ix1, 2);
            mma_k(4, 0, STPRE, 1, 4);
        } else {
            mma_q(4, 0, STPRE);
        }
        STAMP(28);
        mbar_wait(bar_full + 40);
        mma_head(5, 1, STPRE + 4);
        EV(7);
        mma_tail(5, 1, STPRE + 4);
        STAMP(29);
        mbar_wait(bar_full + 48);
        STAMP(30);
        mma_head(6, 3, STPRE + 8);
        nb_sync_id(8 + wg, 128);
        gather(ix2, 1);
        mma_tail(6, 3, STPRE + 8);
        STAMP(31);
        mbar_wait(bar_full + 56);
        STAMP(32);
        mma_head(7, 0, STPRE + 12);
        nb_sync_id(8 + wg, 128);
        gather(ix3, 3);
        mma_tail(7, 0, STPRE + 12);
        EV(12);
        wg_wait<0>();
        STAMP(20);
        pack_acc(pk, d);
        nb_sync<0, 512>();
        acc_to_tile(pk, w, lane);
        gather(ix4, 0);
        cp_wait<3>();
        to_regs(0, 4);
        nb_sync<0, 512>();
        STAMP(8);
        uint4 vf[8];
        {
            const unsigned delta = t ^ (g >> 1), alsm = sb + OFF_ALPHA + w * 128;
            const bool par = g & 1;
            unsigned ta[5];
#pragma unroll
            for (int i = 0; i < 5; i++) ta[i] = tile_addr(w * 5 + i, lane);
            float v[4], u[4];
            to_regs(1, 2);
            EV(14);
            attn_scores(v, true, par, gv[0], ta[0]);
            attn_scores(v, delta == 1, par, gv[1], ta[1] ^ 32);
            cp_wait<2>();
            to_regs(2, 1);
            attn_scores(v, delta == 2, par, gv[2], ta[2] ^ 64);
            STAMP(33);
            cp_wait<1>();
            to_regs(3, 3);
            EV(15);
            STAMP(34);
            attn_scores(v, delta == 3, par, gv[3], ta[3] ^ 96);
            cp_wait<0>();
            to_regs(4, 0);
            STAMP(35);
            attn_scores(u, true, par, gv[4], ta[4]);
            attn_softmax(v, u, lane, alsm + ((lane & 4) + delta) * 16 + (lane >> 3) * 4);
            STAMP(49);
            const unsigned va = sb + OFF_S + wg * 8192 + ((lane & 7) + (lane >> 4) * 8) * 128 + (((2 * (w & 3) + ((lane >> 3) & 1)) ^ (lane & 7)) << 4);
            if (VRS > 0) mbar_wait(bar_full + 64);
            if (VRS > 1) mbar_wait(bar_full + 72);
            uint4 al = lds128(alsm);
#pragma unroll
            for (int i = 0; i < 5; i++) {
                const uint4 a = al;
                if (i < 4) al = lds128(alsm + (i + 1) * 16);
                attn_mix(gv[i], a, ta[i]);
                if (i >= 1 && i <= VRS) {
#pragma unroll
                    for (int k = 0; k < 4; k++) vf[4 * (i - 1) + k] = ldsm4t(va + (i == 1 ? 4 : 2) * 32768 + k * 2048);
                }
            }
        }
        STAMP(36);
        mbar_wait(bar_full + 80);
        fence_async_smem();
        STAMP(22);
        EV(2);
        nb_sync<0, 512>();
        mma_k(10, 1, -2, 0, 4);
        mbar_wait(bar_full + 88);
        mma_head(11, 3, -1);
        EV(4);
        mma_tail(11, 3, -1);
        auto mma_r = [&](int k0, int k1) {
            wg_fence();
#pragma unroll
            for (int k = k0; k < k1; k++) wg80r(d, vf[k], 0x10000u + (SB0 + OFF_T) / 16 + (k >> 2) * 640 + (k & 3) * 2);
            wg_commit();
        };
        if (VRS < 2) {
            mbar_wait(bar_full + 72);
            mma_head(9, 2, -1);
            EV(5);
            mma_tail(9, 2, -1);
        } else {
            mma_r(4, 5); wg_wait<1>(); EV(5); mma_r(5, 8);
        }
        if (VRS < 1) {
            mbar_wait(bar_full + 64);
            mma_k(8, 4, -3, 0, KH); wg_wait<1>();
            EV(6);
            mma_tail(8, 4, -1);
        } else if (VRS == 1) {
            mma_r(0, 1); wg_wait<1>(); EV(6); mma_r(1, 4);
        } else {
            mma_r(0, 4);
        }
        mbar_wait(bar_c);
        L1 = ldg_na(lp); L0 = ldg_na(lp + LSTR);
        wg_wait<0>();
        if (VRS < 1) EV(7);
        STAMP(9);
        pack_acc(pk, d);
        nb_sync<0, 512>();
        STAMP(10);
        if (__builtin_expect(lds32(sb + OFF_MISC + 28) & 2, 0)) {
            for (int i = 0; i < 5; i++) sts128(tile_addr(w * 5 + i, lane), attn_generic(b * TILE + w * 5 + i, x, esrc, edst, wq, wk, wv));
        } else {
            acc_to_tile(pk, w, lane);
        }
        EV(12);
    } else {
        mbar_wait(bar_c);
        L1 = ldg_na(lp); L0 = ldg_na(lp + LSTR);
    }

    const unsigned flags = lds32(sb + OFF_MISC + 28);
    const bool anyovf = flags & 1;
    const unsigned zero = flags >> 8;
    const unsigned c64 = 0x64646464u + zero;
    if (lane < 8) sts128(sb + OFF_S + NN * 16 + lane * 16, make_uint4(0, 0, 0, 0));
    const int more = anyovf ? 0x7FFFFFFF : NN << 16;
    const float zmask = (lane >= 28) ? 0.f : -1.f;
    unsigned stg = sb + OFF_STG + w * 256 + (((lane & 7) * 2 + ((lane >> 3) & 1)) ^ ((lane >> 2) & 1)) * 16;
    unsigned rdb = bar_rd, rde = bar_rd + 48;
    __syncwarp();
    mbar_wait(bar_fill);
    STAMP(11);
    CLK0(64);
#pragma unroll 1
    for (int part = 0; part < 2; part++) {
#pragma unroll 1
        do {
            unsigned ad[9], sA, sB, tA, tB, mx;
            ad[0] = row_lo(L1.x); ad[1] = row_hi(L1.x); ad[2] = row_lo(L1.y); ad[3] = row_hi(L1.y);
            ad[4] = row_lo(L1.z); ad[5] = row_hi(L1.z); ad[6] = row_lo(L1.w); ad[7] = row_hi(L1.w); ad[8] = row_lo(L0.w);
            asm volatile("prmt.b32 %0,%2,%3,0x4140;\n prmt.b32 %1,%2,%3,0x4342;" : "=r"(sA), "=r"(sB) : "r"(L0.x), "r"(c64));
            asm volatile("prmt.b32 %0,%2,%3,0x4140;\n prmt.b32 %1,%2,%3,0x4342;" : "=r"(tA), "=r"(tB) : "r"(L0.y), "r"(c64));
            asm volatile("mov.b32 %0,%1;" : "=r"(mx) : "r"(L0.w));
            const float dA = blo_v(L0.z), dB = bhi_v(L0.z);
            L1 = ldg_na(lp + 16 * 32); L0 = ldg_na(lp + 16 * 32 + LSTR);
            const bool p9 = __any_sync(~0u, (int)mx < more);
            float acc0[4] = {0, 0, 0, 0}, acc1[4] = {0, 0, 0, 0};
            uint4 v[9], a0, a1;
#pragma unroll
            for (int s = 0; s < LA; s++) v[s] = ldsm4t(sb + OFF_S + ad[s]);
            a0 = p3_sel(0, sA, sB); a1 = p3_sel(1, sA, sB);
            sched_fence(zero);
#pragma unroll
            for (int s = 0; s < 9; s++) {
                uint4 n0, n1;
                if (s < 8) n0 = p3_sel(2 * s + 2, s < 7 ? sA : tA, s < 7 ? sB : tB);
                mma16816(acc0, a0.x, a0.y, a0.z, a0.w, v[s].x, v[s].y);
                if (s + LA < 9) v[s + LA] = ldsm4t(sb + OFF_S + ad[s + LA]);
                if (s < 8) n1 = p3_sel(2 * s + 3, s < 7 ? sA : tA, s < 7 ? sB : tB);
                mma16816(acc1, a1.x, a1.y, a1.z, a1.w, v[s].z, v[s].w);
                a0 = n0; a1 = n1;
            }
            if (__builtin_expect(p9, 0)) {
                p3_step(acc0, acc1, row_hi(mx & 0x7FFFFFFFu), 16, tA, tB);
                if (__any_sync(~0u, (int)mx < 0)) {
                    const uint4 C2 = ldg_na(lp + 2 * LSTR);
                    p3_step(acc0, acc1, row_lo(C2.x), 24, tA, tB); p3_step(acc0, acc1, row_hi(C2.x), 32, tA, tB);
                    p3_step(acc0, acc1, row_lo(C2.y), 40, tA, tB); p3_step(acc0, acc1, row_hi(C2.y), 48, tA, tB);
                }
                if (anyovf) {
                    float4 e = p3_overflow(sc, grp0 + 2 * (rdb - bar_rd), sb + OFF_S);
                    float s0 = e.x + e.z, s1 = e.y + e.w;
                    for (int k = 4; k < 32; k <<= 1) {
                        float u0 = __shfl_down_sync(~0u, s0, k), u1 = __shfl_down_sync(~0u, s1, k);
                        if (lane + k < 32) { s0 += u0; s1 += u1; }
                    }
                    acc0[0] += s0; acc0[1] += s1; acc0[2] += s0 - e.x; acc0[3] += s1 - e.y;
                }
            }
            float c0 = acc0[0] + acc1[0], c1 = acc0[1] + acc1[1], c2 = acc0[2] + acc1[2], c3 = acc0[3] + acc1[3];
            float n0 = __shfl_down_sync(~0u, c0, 4), n1 = __shfl_down_sync(~0u, c1, 4);
            float o0 = c0 - c2, o1 = c1 - c3, o2 = fmaf(n0, zmask, c2), o3 = fmaf(n1, zmask, c3);
            asm volatile("stmatrix.sync.aligned.m8n8.x2.shared.b16 [%0],{%1,%2};" ::"r"(stg), "r"(pack2(o0 * dA, o1 * dA)), "r"(pack2(o2 * dB, o3 * dB)) : "memory");
            __syncwarp();
            asm volatile("{.reg .pred p; setp.eq.u32 p,%1,0; @p mbarrier.arrive.shared.b64 _,[%0];}" ::"r"(rdb), "r"(lane) : "memory");
            stg += 4096;
            rdb += 8;
            lp += 16 * 32;
        } while (rdb != rde);
        mbar_wait(bar_t);
        rde = bar_rd + 8 * ((g1 - grp0 + 15) >> 4);
    }
    STAMP(12);
    CLK1(64, 60); STAMPT(0, 61); STAMPT(352, 62); STAMPT(480, 63);
    }
}

typedef CUresult (*EncodeFn)(CUtensorMap*, CUtensorMapDataType, cuuint32_t, void*, const cuuint64_t*, const cuuint64_t*,
                             const cuuint32_t*, const cuuint32_t*, CUtensorMapInterleave, CUtensorMapSwizzle,
                             CUtensorMapL2promotion, CUtensorMapFloatOOBfill);

}

extern "C" void kernel_launch(void* const* d_in, const int* in_sizes, int n_in, void* d_out, int out_size) {
    (void)in_sizes; (void)n_in; (void)out_size;
    static EncodeFn enc = nullptr;
    static void* scratch = nullptr;
    if (!enc) {
        cudaGetSymbolAddress(&scratch, g_scratch);
        void* fn = nullptr;
        cudaDriverEntryPointQueryResult qr;
        cudaGetDriverEntryPoint("cuTensorMapEncodeTiled", &fn, cudaEnableDefault, &qr);
        enc = (EncodeFn)fn;
        cudaFuncSetAttribute(exphormer_kernel, cudaFuncAttributeMaxDynamicSharedMemorySize, SMEM_BYTES);
    }
    CUtensorMap tm_m, tm_ms, tm_mail, tm_x, tm_wl, tm_wv, tm_ot, tm_o256, tm_o16;
    auto mk = [&](CUtensorMap* tm, void* p, int rows, int bc, int br, CUtensorMapSwizzle sw, CUtensorMapL2promotion pr) {
        cuuint64_t gd[2] = {256, (cuuint64_t)rows}, gs[1] = {512};
        cuuint32_t es[2] = {1, 1}, bx[2] = {(cuuint32_t)bc, (cuuint32_t)br};
        enc(tm, CU_TENSOR_MAP_DATA_TYPE_BFLOAT16, 2, p, gd, gs, bx, es, CU_TENSOR_MAP_INTERLEAVE_NONE, sw, pr, CU_TENSOR_MAP_FLOAT_OOB_FILL_NONE);
    };
    for (int i = 0; i < 3; i++) {
        cuuint64_t gd[3] = {64, 256, 4}, gs[2] = {512, 128};
        cuuint32_t es[3] = {1, 1, 1}, bx[3] = {64, 64, 4};
        enc(i == 2 ? &tm_m : i ? &tm_wv : &tm_wl, CU_TENSOR_MAP_DATA_TYPE_BFLOAT16, 3, i == 2 ? scratch : d_in[i ? 9 : 6], gd, gs, bx, es, CU_TENSOR_MAP_INTERLEAVE_NONE,
            CU_TENSOR_MAP_SWIZZLE_128B, CU_TENSOR_MAP_L2_PROMOTION_L2_128B, CU_TENSOR_MAP_FLOAT_OOB_FILL_NONE);
    }
    {
        cuuint64_t gd[2] = {2048, NT}, gs[1] = {8192};
        cuuint32_t es[2] = {1, 1}, bx[2] = {16, NT};
        enc(&tm_mail, CU_TENSOR_MAP_DATA_TYPE_UINT32, 2, ((Scratch*)scratch)->mail, gd, gs, bx, es, CU_TENSOR_MAP_INTERLEAVE_NONE,
            CU_TENSOR_MAP_SWIZZLE_NONE, CU_TENSOR_MAP_L2_PROMOTION_NONE, CU_TENSOR_MAP_FLOAT_OOB_FILL_NONE);
    }
    mk(&tm_ms, scratch, 256, 32, 16, CU_TENSOR_MAP_SWIZZLE_NONE, CU_TENSOR_MAP_L2_PROMOTION_NONE);
    mk(&tm_x, d_in[0], NN, 64, TILE, CU_TENSOR_MAP_SWIZZLE_128B, CU_TENSOR_MAP_L2_PROMOTION_L2_128B);
    mk(&tm_ot, d_out, NN, 64, TILE, CU_TENSOR_MAP_SWIZZLE_128B, CU_TENSOR_MAP_L2_PROMOTION_NONE);
    mk(&tm_o256, d_out, NN, 8, PBOX, CU_TENSOR_MAP_SWIZZLE_NONE, CU_TENSOR_MAP_L2_PROMOTION_NONE);
    mk(&tm_o16, d_out, NN, 8, 16, CU_TENSOR_MAP_SWIZZLE_NONE, CU_TENSOR_MAP_L2_PROMOTION_NONE);
    exphormer_kernel<<<NCTA, 640, SMEM_BYTES>>>(
        (const uint4*)d_in[0], (const uint4*)d_in[2], (const uint4*)d_in[1], (const uint4*)d_in[7], (const uint4*)d_in[8], (const int*)d_in[3],
        (const int*)d_in[4], (Scratch*)scratch, (const uint4*)d_in[5], (const uint4*)d_in[9],
        tm_x, tm_wl, tm_wv, tm_m, tm_ms, tm_mail, tm_ot, tm_o256, tm_o16);
}
```

```cpp
#include <cuda_runtime.h>
#include <cuda_bf16.h>
#include <cuda.h>
#include <stdint.h>

namespace {

constexpr int NN = 10000, NE = 160000, NEE = 40000;
constexpr int TILE = 80, NT = 125, NCTA = 128, NG = 625, EPC = 1280;
constexpr int CELL = 32;
constexpr int QCAP = 192;
constexpr int OVCAP = EPC + NT * CELL;
#define XD0 700
#define XD1 1100
#define XD2 1900
#define REG_W 104
#define REG_H 64
#define KH 1
#define POLLNS 0
#define STPRE 4
#define G0POS 1
#define G1POS 1
#define LA 3
#define ED0 0
#define VRS 0
#define PACE 650
#define PBOX 256
#define PLACE_AT 1
constexpr unsigned DUMMY2 = NN | (NN << 16);

constexpr unsigned SB0 = 1024;
constexpr unsigned sb = SB0;
constexpr int OFF_S = 0;
constexpr int OFF_R = 163840;
constexpr int OFF_BAR = OFF_R;
constexpr int OFF_MISC = OFF_R + 256;
constexpr int OFF_DIS = OFF_R + 320;
constexpr int OFF_PROF = OFF_R + 512;
constexpr int OFF_EIDX = OFF_R + 1024;
constexpr int OFF_ALPHA = OFF_R + 1024;
constexpr int OFF_STG = OFF_R + 3072;
constexpr int OFF_CNT1 = OFF_R + 2560;
constexpr int OFF_CNT2 = OFF_R + 3072;
constexpr int OFF_MAIL = OFF_R + 5760;
constexpr int OFF_IMG = OFF_MAIL + 9216;
constexpr int OFF_T = OFF_R + 27648;
constexpr int SMEM_BYTES = OFF_T + 40960;
static_assert(SMEM_BYTES <= 232448 && OFF_T % 1024 == 0 && OFF_STG + 3 * 8192 == OFF_T && OFF_IMG + 10752 <= OFF_T, "smem");
#define bar_fill (sb + OFF_BAR)
#define bar_t (sb + OFF_BAR + 8)
#define bar_mail (sb + OFF_BAR + 16)
#define bar_c (sb + OFF_BAR + 24)
#define bar_rd (sb + OFF_BAR + 32)
#define bar_go (sb + OFF_BAR + 112)
#define bar_p (sb + OFF_BAR + 216)
#define bar_full (sb + OFF_BAR + 120)
constexpr int LSTR = (NG + 48) * 32;

struct __align__(256) Scratch {
    uint4 mimg[8192];
    uint4 hs[32 * NN];
    uint4 mail[2 * NT * 512];
    uint4 lists[3 * LSTR];
    uint2 ovfn[NCTA];
    unsigned bar[5 * 64];
    unsigned ovf[NCTA * OVCAP];
};
__device__ Scratch g_scratch;
#define STAMPT(th, i)
#define CLK0(th)
#define CLK1(th, i)
#define STAMP(i) STAMPT(64, i)
#define STAMP2(i) STAMPT(416, i)

extern __shared__ __align__(1024) unsigned char smem_raw[];
__device__ __forceinline__ void bar_arrive(unsigned* p) {
    asm volatile("red.release.gpu.global.add.u32 [%0],1;" ::"l"(p) : "memory");
}
__device__ __forceinline__ void bar_arrive_relaxed(unsigned* p) {
    asm volatile("red.relaxed.gpu.global.add.u32 [%0],1;" ::"l"(p) : "memory");
}
__device__ __forceinline__ void bar_poll(const Scratch* sc, int i) {
    unsigned v, target;
    int lim = 0;
    asm volatile("ld.shared.u32 %0,[%1];" : "=r"(target) : "r"(sb + OFF_MISC + 32 + 4 * i) : "memory");
    while (true) {
        asm volatile("ld.acquire.gpu.global.u32 %0,[%1];" : "=r"(v) : "l"(&sc->bar[i * 64]) : "memory");
        if ((int)(v - target) >= 0) break;
        if (++lim > (1 << 22)) __trap();
        if (POLLNS) __nanosleep(POLLNS);
    }
}
__device__ __forceinline__ unsigned bar_poll2(const unsigned* p, unsigned target) {
    unsigned long long v;
    int lim = 0;
    do {
        asm volatile("ld.acquire.gpu.global.u64 %0,[%1];" : "=l"(v) : "l"(p) : "memory");
        if (++lim > (1 << 22)) __trap();
    } while ((int)((unsigned)v - target) < 0);
    unsigned f = (unsigned)(v >> 32);
    return (f & ~3u) == target ? f & 3 : 0;
}
__device__ __noinline__ void raise_flag(unsigned* p, unsigned target, unsigned bit) {
    unsigned old = atomicCAS(p, 0, 0), seen;
    do {
        seen = old;
        old = atomicCAS(p, seen, ((seen & ~3u) == target ? seen : target) | bit);
    } while (old != seen);
}
__device__ __forceinline__ void mbar_wait(unsigned a) {
    asm volatile("{.reg .pred p; .reg .u32 n;\n"
                 "mov.u32 n,0x400000;\n"
                 "W: mbarrier.try_wait.parity.shared.b64 p,[%0],0;\n"
                 "add.u32 n,n,-1; setp.ne.and.u32 p,n,0,!p; @p bra W;}" ::"r"(a) : "memory");
}
__device__ __forceinline__ bool elect() {
    unsigned r;
    asm volatile("{.reg .pred p; elect.sync _|p,0xFFFFFFFF; selp.u32 %0,1,0,p;}" : "=r"(r));
    return r;
}
__device__ __forceinline__ uint4 ldg_na(const uint4* p) {
    uint4 v;
    asm volatile("ld.global.L1::no_allocate.v4.u32 {%0,%1,%2,%3},[%4];" : "=r"(v.x), "=r"(v.y), "=r"(v.z), "=r"(v.w) : "l"(p) : "memory");
    return v;
}
__device__ __forceinline__ uint4 lds128(unsigned a) {
    uint4 v;
    asm volatile("ld.shared.v4.u32 {%0,%1,%2,%3},[%4];" : "=r"(v.x), "=r"(v.y), "=r"(v.z), "=r"(v.w) : "r"(a) : "memory");
    return v;
}
__device__ __forceinline__ uint4 ldsm4(unsigned a) {
    uint4 v;
    asm volatile("ldmatrix.sync.aligned.m8n8.x4.shared.b16 {%0,%1,%2,%3},[%4];" : "=r"(v.x), "=r"(v.y), "=r"(v.z), "=r"(v.w) : "r"(a) : "memory");
    return v;
}
__device__ __forceinline__ void sts128(unsigned a, uint4 v) {
    asm volatile("st.shared.v4.u32 [%0],{%1,%2,%3,%4};" ::"r"(a), "r"(v.x), "r"(v.y), "r"(v.z), "r"(v.w) : "memory");
}
__device__ __forceinline__ void sts32(unsigned a, unsigned v) { asm volatile("st.shared.u32 [%0],%1;" ::"r"(a), "r"(v) : "memory"); }
__device__ __forceinline__ unsigned lds32(unsigned a) { unsigned v; asm volatile("ld.shared.u32 %0,[%1];" : "=r"(v) : "r"(a) : "memory"); return v; }
__device__ __forceinline__ unsigned atoms_add(unsigned a, unsigned k) { unsigned v; asm volatile("atom.shared.add.u32 %0,[%1],%2;" : "=r"(v) : "r"(a), "r"(k) : "memory"); return v; }
__device__ __forceinline__ unsigned bitsel(unsigned a, unsigned b, unsigned m) { unsigned r; asm("lop3.b32 %0,%1,%2,%3,0xE4;" : "=r"(r) : "r"(a), "r"(b), "r"(m)); return r; }
__device__ __forceinline__ unsigned atoms_inc(unsigned a) { unsigned v; asm volatile("atom.shared.add.u32 %0,[%1],1;" : "=r"(v) : "r"(a) : "memory"); return v; }
__device__ __forceinline__ float blo(unsigned v) { return __uint_as_float(v << 16); }
__device__ __forceinline__ float bhi(unsigned v) { return __uint_as_float(v & 0xFFFF0000u); }
__device__ __forceinline__ float blo_v(unsigned v) { float r; asm volatile("shl.b32 %0,%1,16;" : "=f"(r) : "r"(v)); return r; }
__device__ __forceinline__ float bhi_v(unsigned v) { float r; asm volatile("and.b32 %0,%1,0xFFFF0000;" : "=f"(r) : "r"(v)); return r; }
__device__ __forceinline__ unsigned pack2(float lo, float hi) { unsigned r; asm("cvt.rn.bf16x2.f32 %0,%1,%2;" : "=r"(r) : "f"(hi), "f"(lo)); return r; }

__device__ __forceinline__ void mma16816(float* d, unsigned a0, unsigned a1, unsigned a2, unsigned a3, unsigned b0, unsigned b1) {
    asm volatile("mma.sync.aligned.m16n8k16.row.col.f32.bf16.bf16.f32 {%0,%1,%2,%3},{%4,%5,%6,%7},{%8,%9},{%0,%1,%2,%3};"
                 : "+f"(d[0]), "+f"(d[1]), "+f"(d[2]), "+f"(d[3]) : "r"(a0), "r"(a1), "r"(a2), "r"(a3), "r"(b0), "r"(b1));
}
#define R10(b) "+f"(d[b + 0]), "+f"(d[b + 1]), "+f"(d[b + 2]), "+f"(d[b + 3]), "+f"(d[b + 4]), "+f"(d[b + 5]), "+f"(d[b + 6]), "+f"(d[b + 7]), "+f"(d[b + 8]), "+f"(d[b + 9])
__device__ __forceinline__ void wg80(float* d, unsigned da, unsigned db, int sc) {
    asm volatile("{.reg .pred p; .reg .b64 a, b; setp.ne.b32 p,%42,0; mov.b64 a,{%40,%43}; mov.b64 b,{%41,%43};\n"
                 "wgmma.mma_async.sync.aligned.m64n80k16.f32.bf16.bf16 "
                 "{%0,%1,%2,%3,%4,%5,%6,%7,%8,%9,%10,%11,%12,%13,%14,%15,%16,%17,%18,%19,%20,%21,%22,%23,%24,%25,%26,%27,%28,%29,%30,%31,%32,%33,%34,%35,%36,%37,%38,%39},"
                 "a,b,p,1,1,1,0;}"
                 : R10(0), R10(10), R10(20), R10(30) : "r"(da), "r"(db), "r"(sc), "r"(0x40000040));
}
__device__ __forceinline__ void wg80r(float* d, const uint4& a, unsigned db) {
    asm volatile("{.reg .b64 b; mov.b64 b,{%44,%45};\n"
                 "wgmma.mma_async.sync.aligned.m64n80k16.f32.bf16.bf16 "
                 "{%0,%1,%2,%3,%4,%5,%6,%7,%8,%9,%10,%11,%12,%13,%14,%15,%16,%17,%18,%19,%20,%21,%22,%23,%24,%25,%26,%27,%28,%29,%30,%31,%32,%33,%34,%35,%36,%37,%38,%39},"
                 "{%40,%41,%42,%43},b,1,1,1,0;}"
                 : R10(0), R10(10), R10(20), R10(30) : "r"(a.x), "r"(a.y), "r"(a.z), "r"(a.w), "r"(db), "r"(0x40000040));
}
__device__ __forceinline__ void wg_fence() { asm volatile("wgmma.fence.sync.aligned;" ::: "memory"); }
__device__ __forceinline__ void wg_commit() { asm volatile("wgmma.commit_group.sync.aligned;" ::: "memory"); }
template <int N> __device__ __forceinline__ void wg_wait() { asm volatile("wgmma.wait_group.sync.aligned %0;" ::"n"(N) : "memory"); }
__device__ __forceinline__ void bulk_g2s(unsigned dst, const void* src, unsigned bytes, unsigned bar) {
    asm volatile("cp.async.bulk.shared::cluster.global.mbarrier::complete_tx::bytes [%0],[%1],%2,[%3];" ::"r"(dst), "l"(src), "r"(bytes), "r"(bar) : "memory");
}
__device__ __forceinline__ void fence_async_smem() { asm volatile("fence.proxy.async.shared::cta;" ::: "memory"); }
__device__ __forceinline__ void fence_async_gmem() { asm volatile("fence.proxy.async.global;" ::: "memory"); }

__host__ __device__ constexpr unsigned h2c(int v) { return (0x6400u | v) | ((0x6400u | v) << 16); }
__device__ __forceinline__ unsigned row_lo(unsigned a) { unsigned r; asm volatile("dp2a.lo.u32.u32 %0,%1,0x10000010,0;" : "=r"(r) : "r"(a)); return r; }
__device__ __forceinline__ unsigned row_hi(unsigned a) { unsigned r; asm volatile("dp2a.hi.u32.u32 %0,%1,0x10000010,0;" : "=r"(r) : "r"(a)); return r; }
__device__ __forceinline__ uint4 ldsm4t(unsigned addr) {
    uint4 v;
    asm volatile("ldmatrix.sync.aligned.m8n8.x4.trans.shared.b16 {%0,%1,%2,%3},[%4];" : "=r"(v.x), "=r"(v.y), "=r"(v.z), "=r"(v.w) : "r"(addr));
    return v;
}
__device__ __forceinline__ void sched_fence(unsigned zero) { asm volatile("{.reg .pred p; setp.ne.u32 p,%0,0; @p exit;}" ::"r"(zero)); }
__device__ __forceinline__ uint4 p3_sel(int i, unsigned sA, unsigned sB) {
    uint4 a;
    asm volatile("set.le.f16x2.f16x2 %0,%4,%6;\n sub.sat.f16x2 %2,%7,%4;\n set.le.f16x2.f16x2 %1,%5,%6;\n sub.sat.f16x2 %3,%7,%5;"
                 : "=r"(a.x), "=r"(a.y), "=r"(a.z), "=r"(a.w) : "r"(sA), "r"(sB), "r"(h2c(2 * i)), "r"(h2c(2 * i + 2)));
    return a;
}
__device__ __forceinline__ void p3_step(float* acc0, float* acc1, unsigned row, int s, unsigned sA, unsigned sB) {
    const uint4 v = ldsm4t(sb + OFF_S + row), a0 = p3_sel(2 * s, sA, sB), a1 = p3_sel(2 * s + 1, sA, sB);
    mma16816(acc0, a0.x, a0.y, a0.z, a0.w, v.x, v.y);
    mma16816(acc1, a1.x, a1.y, a1.z, a1.w, v.z, v.w);
}
__device__ __noinline__ float4 p3_overflow(const Scratch* sc, int grp, unsigned sS) {
    const unsigned tag = lds32(sb + OFF_MISC + 48);
    int lane = threadIdx.x & 31, g = lane >> 2, t = lane & 3;
    float4 r = make_float4(0.f, 0.f, 0.f, 0.f);
    for (int c = 0; c < NT; c++) {
        const uint2 tn = __ldcg(&sc->ovfn[c]);
        const int n = tn.x == tag ? (int)tn.y : 0;
        for (int i0 = 0; i0 < n; i0 += 32) {
            unsigned e = (i0 + lane < n) ? __ldcg(&sc->ovf[c * OVCAP + i0 + lane]) : 0xFFFFFFFFu;
            unsigned m = __ballot_sync(~0u, (int)(e >> 18) == grp);
            while (m) {
                int j = __ffs(m) - 1;
                m &= m - 1;
                unsigned ee = __shfl_sync(~0u, e, j);
                int row = (ee >> 14) & 15;
                row ^= row >> 3;
                unsigned v = lds32(sS + (ee & 0x3FFF) * 16 + t * 4);
                if ((row >> 1) == g) {
                    if (!(row & 1)) { r.x += blo(v); r.y += bhi(v); } else { r.z += blo(v); r.w += bhi(v); }
                }
            }
        }
    }
    const float k = 1.f / 128.f;
    r.x *= k; r.y *= k; r.z *= k; r.w *= k;
    return r;
}
__device__ __forceinline__ void unpack8(float* f, uint4 v) {
    f[0] = blo(v.x); f[1] = bhi(v.x); f[2] = blo(v.y); f[3] = bhi(v.y); f[4] = blo(v.z); f[5] = bhi(v.z); f[6] = blo(v.w); f[7] = bhi(v.w);
}
__device__ __forceinline__ void vec_mat(float* o, const float* v, const uint4* __restrict__ W, int lane) {
    for (int k = 0; k < 8; k++) o[k] = 0.f;
    for (int l = 0; l < 32; l++) {
#pragma unroll
        for (int i = 0; i < 8; i++) {
            float a = __shfl_sync(~0u, v[i], l), wr[8];
            unpack8(wr, W[(l * 8 + i) * 32 + lane]);
#pragma unroll
            for (int k = 0; k < 8; k++) o[k] = fmaf(a, wr[k], o[k]);
        }
    }
}
__device__ __noinline__ uint4 attn_generic(int node, const uint4* __restrict__ x, const int* __restrict__ esrc, const int* __restrict__ edst,
                                           const uint4* __restrict__ wq, const uint4* __restrict__ wk, const uint4* __restrict__ wv) {
    int lane = threadIdx.x & 31;
    float xr[8], q[8], y[8], o[8];
    unpack8(xr, x[node * 32 + lane]);
    vec_mat(q, xr, wq, lane);
    for (int l = 0; l < 32; l++) {
#pragma unroll
        for (int i = 0; i < 8; i++) {
            float wr[8], p = 0.f;
            unpack8(wr, wk[(l * 8 + i) * 32 + lane]);
#pragma unroll
            for (int k = 0; k < 8; k++) p = fmaf(q[k], wr[k], p);
            for (int k = 16; k; k >>= 1) p += __shfl_xor_sync(~0u, p, k);
            if (lane == l) y[i] = p;
        }
    }
    for (int k = 0; k < 8; k++) o[k] = 0.f;
    float den = 0.f;
    for (int i0 = 0; i0 < NEE; i0 += 32) {
        unsigned m = __ballot_sync(~0u, edst[i0 + lane] == node);
        while (m) {
            int j = __ffs(m) - 1;
            m &= m - 1;
            float gq[8], p = 0.f;
            unpack8(gq, x[esrc[i0 + j] * 32 + lane]);
#pragma unroll
            for (int k = 0; k < 8; k++) p = fmaf(y[k], gq[k], p);
            for (int k = 16; k; k >>= 1) p += __shfl_xor_sync(~0u, p, k);
            float ex = __expf(p * 0.0625f);
            den += ex;
#pragma unroll
            for (int k = 0; k < 8; k++) o[k] = fmaf(ex, gq[k], o[k]);
        }
    }
    float inv = 1.f / (den + 1e-9f);
    for (int k = 0; k < 8; k++) o[k] *= inv;
    vec_mat(q, o, wv, lane);
    return make_uint4(pack2(q[0], q[1]), pack2(q[2], q[3]), pack2(q[4], q[5]), pack2(q[6], q[7]));
}

__device__ __forceinline__ unsigned hfma2(unsigned a, unsigned b, unsigned c) { unsigned r; asm("fma.rn.bf16x2 %0,%1,%2,%3;" : "=r"(r) : "r"(a), "r"(b), "r"(c)); return r; }
__device__ __forceinline__ unsigned hmul2(unsigned a, unsigned b) { unsigned r; asm("mul.rn.bf16x2 %0,%1,%2;" : "=r"(r) : "r"(a), "r"(b)); return r; }

__device__ __forceinline__ unsigned tile_addr(int n, unsigned chunk) { return sb + OFF_T + (chunk >> 3) * 10240 + n * 128 + (((chunk ^ n) & 7) << 4); }
__device__ __forceinline__ void attn_scores(float* v, bool mine, bool par, const uint4* gv, unsigned yaddr) {
    const uint4 y = ldsm4(yaddr);
    float c[4] = {0, 0, 0, 0}, e[4] = {0, 0, 0, 0};
    mma16816(c, gv[0].x, gv[0].y, gv[0].z, gv[0].w, y.x, y.y);
    mma16816(e, gv[2].x, gv[2].y, gv[2].z, gv[2].w, y.x, y.y);
    mma16816(c, gv[1].x, gv[1].y, gv[1].z, gv[1].w, y.z, y.w);
    mma16816(e, gv[3].x, gv[3].y, gv[3].z, gv[3].w, y.z, y.w);
    if (mine) { v[0] = par ? c[1] : c[0]; v[1] = par ? c[3] : c[2]; v[2] = par ? e[1] : e[0]; v[3] = par ? e[3] : e[2]; }
}
__device__ __forceinline__ void attn_softmax(const float* v, const float* u, unsigned lane, unsigned aladdr) {
    const bool hA = lane & 4, hB = lane & 8, hC = lane & 16;
    float a[4];
#pragma unroll
    for (int e = 0; e < 4; e++) a[e] = (hA ? u[e] : v[e]) + __shfl_xor_sync(~0u, hA ? v[e] : u[e], 4);
    float b0 = (hB ? a[1] : a[0]) + __shfl_xor_sync(~0u, hB ? a[0] : a[1], 9);
    float b1 = (hB ? a[3] : a[2]) + __shfl_xor_sync(~0u, hB ? a[2] : a[3], 9);
    float sc = (hC ? b1 : b0) + __shfl_xor_sync(~0u, hC ? b0 : b1, 18);
    float ex, inv;
    asm("ex2.approx.ftz.f32 %0,%1;" : "=f"(ex) : "f"(sc));
    float den = ex + __shfl_xor_sync(~0u, ex, 9);
    den += __shfl_xor_sync(~0u, den, 18);
    asm("rcp.approx.ftz.f32 %0,%1;" : "=f"(inv) : "f"(den + 1e-9f));
    sts32(aladdr, pack2(ex * inv, ex * inv));
    __syncwarp();
}
__device__ __forceinline__ void attn_mix(const uint4* gv, const uint4& a, unsigned oaddr) {
    const unsigned o0 = hfma2(a.w, gv[2].y, hfma2(a.z, gv[2].x, hfma2(a.y, gv[0].y, hmul2(a.x, gv[0].x))));
    const unsigned o1 = hfma2(a.w, gv[2].w, hfma2(a.z, gv[2].z, hfma2(a.y, gv[0].w, hmul2(a.x, gv[0].z))));
    const unsigned o2 = hfma2(a.w, gv[3].y, hfma2(a.z, gv[3].x, hfma2(a.y, gv[1].y, hmul2(a.x, gv[1].x))));
    const unsigned o3 = hfma2(a.w, gv[3].w, hfma2(a.z, gv[3].z, hfma2(a.y, gv[1].w, hmul2(a.x, gv[1].z))));
    asm volatile("stmatrix.sync.aligned.m8n8.x4.shared.b16 [%0],{%1,%2,%3,%4};" ::"r"(oaddr), "r"(o0), "r"(o1), "r"(o2), "r"(o3) : "memory");
}
__device__ __forceinline__ void pack_acc(unsigned* pk, const float* d) {
#pragma unroll
    for (int j = 0; j < 20; j++) pk[j] = pack2(d[2 * j], d[2 * j + 1]);
}
__device__ __forceinline__ void acc_to_tile(const unsigned* pk, int w, int lane) {
    const unsigned a = sb + OFF_T + (w >> 2) * 10240 + (lane >> 4) * 1024 + (lane & 7) * 128 + (((2 * (w & 3) + ((lane >> 3) & 1)) ^ (lane & 7)) << 4);
#pragma unroll
    for (int j = 0; j < 5; j++)
        asm volatile("stmatrix.sync.aligned.m8n8.x4.trans.shared.b16 [%0],{%1,%2,%3,%4};" ::"r"(a + j * 2048), "r"(pk[4 * j]), "r"(pk[4 * j + 1]), "r"(pk[4 * j + 2]), "r"(pk[4 * j + 3]) : "memory");
}
__device__ __forceinline__ unsigned movm(unsigned a) { unsigned d; asm volatile("movmatrix.sync.aligned.m8n8.trans.b16 %0,%1;" : "=r"(d) : "r"(a)); return d; }
__device__ __forceinline__ void tma_load2d(unsigned dst, const CUtensorMap* tm, int c0, int c1, unsigned bar) {
    asm volatile("cp.async.bulk.tensor.2d.shared::cluster.global.mbarrier::complete_tx::bytes [%0],[%1,{%3,%4}],[%2];"
                 ::"r"(dst), "l"(tm), "r"(bar), "r"(c0), "r"(c1) : "memory");
}
__device__ __forceinline__ void tma_load3d(unsigned dst, const CUtensorMap* tm, int row, unsigned bar) {
    asm volatile("cp.async.bulk.tensor.3d.shared::cluster.global.mbarrier::complete_tx::bytes [%0],[%1,{%4,%3,%4}],[%2];"
                 ::"r"(dst), "l"(tm), "r"(bar), "r"(row), "r"(0) : "memory");
}
__device__ __forceinline__ void cp16(unsigned dst, const void* src) { asm volatile("cp.async.cg.shared.global [%0],[%1],16;" ::"r"(dst), "l"(src) : "memory"); }
__device__ __forceinline__ void cp_commit() { asm volatile("cp.async.commit_group;" ::: "memory"); }
template <int N> __device__ __forceinline__ void cp_wait() { asm volatile("cp.async.wait_group %0;" ::"n"(N) : "memory"); }
__device__ __forceinline__ void nb_sync_id(int id, int n) { asm volatile("bar.sync %0,%1;" ::"r"(id), "r"(n) : "memory"); }
__device__ __forceinline__ void nb_arrive_id(int id, int n) { asm volatile("bar.arrive %0,%1;" ::"r"(id), "r"(n) : "memory"); }
template <int ID, int N> __device__ __forceinline__ void nb_sync() { asm volatile("bar.sync %0,%1;" ::"n"(ID), "n"(N) : "memory"); }
template <int ID, int N> __device__ __forceinline__ void nb_arrive() { asm volatile("bar.arrive %0,%1;" ::"n"(ID), "n"(N) : "memory"); }
__device__ __forceinline__ void mbar_init(unsigned a, int n) { asm volatile("mbarrier.init.shared.b64 [%0],%1;" ::"r"(a), "r"(n) : "memory"); }
__device__ __forceinline__ void mbar_expect(unsigned a, int n) { asm volatile("mbarrier.arrive.expect_tx.shared.b64 _,[%0],%1;" ::"r"(a), "r"(n) : "memory"); }
__device__ __forceinline__ void mbar_arrive(unsigned a) { asm volatile("mbarrier.arrive.shared.b64 _,[%0];" ::"r"(a) : "memory"); }

constexpr unsigned PADBIN = 2560;
__device__ __noinline__ void push_overflow(Scratch* sc, unsigned dst, unsigned src) {
    sc->ovf[blockIdx.x * OVCAP + atoms_inc(sb + OFF_MISC)] = (dst << 14) | src;
}
__device__ __forceinline__ void entry_overflow(Scratch* sc, unsigned e) {
    if (e < (PADBIN << 16)) push_overflow(sc, blockIdx.x * TILE + ((e >> 21) & ~3u) + ((e >> 18) & 3), e & 0xFFFF);
}
__device__ __forceinline__ unsigned rank_addr(unsigned i) { return sb + OFF_IMG + 2560 + i * 4 + (i >= 384 ? 4096 - 1536 : 0); }
__device__ __forceinline__ void place(unsigned e, unsigned r, unsigned w) {
    const unsigned p = r + (w >> 16), t2 = r * 0x801 + w;
    const unsigned tt = p < 32 ? p * 0x808 : t2, bin = p < 32 ? e >> 16 : bitsel(t2 << 2, e >> 16, 0x1070);
    asm volatile("{.reg .pred p; setp.lt.u32 p,%2,%3; @p st.shared.u16 [%0],%1;}"
                 ::"r"(sb + OFF_IMG + bitsel(tt >> 4, bin, 0x18E)), "h"((unsigned short)e), "r"(e), "n"(PADBIN << 16) : "memory");
}
__device__ __forceinline__ void place4(unsigned i) {
    uint4 e = lds128(sb + OFF_MAIL + i * 16);
    const unsigned r = lds32(rank_addr(i));
    e.w &= 0x7FFFFFFFu;
    const uint4 w = make_uint4(lds32(sb + OFF_CNT2 + (e.x >> 16)), lds32(sb + OFF_CNT2 + (e.y >> 16)), lds32(sb + OFF_CNT2 + (e.z >> 16)), lds32(sb + OFF_CNT2 + (e.w >> 16)));
    place(e.x, r & 255, w.x); place(e.y, (r >> 8) & 255, w.y); place(e.z, (r >> 16) & 255, w.z); place(e.w, r >> 24, w.w);
}
__device__ __noinline__ void place_slow(Scratch* sc, unsigned ht, unsigned broken) {
    for (unsigned i = ht; i < 576 * 4; i += 96) {
        const unsigned e = lds32(sb + OFF_MAIL + i * 4) & 0x7FFFFFFFu, w = lds32(sb + OFF_CNT2 + (e >> 16));
        const unsigned r = (lds32(rank_addr(i >> 2)) >> (8 * (i & 3))) & 255, q = (r + w) & 0xFF;
        if (r + (w >> 16) < 32) place(e, r, w);
        else if (broken >> (e >> 25) & 1) entry_overflow(sc, e);
        else if (e < (PADBIN << 16))
            asm volatile("st.shared.u16 [%0],%1;" ::"r"(sb + OFF_IMG + (q < 192 ? 8192 : 4096) + (e >> 25) * 512 + (q & 3) * 128 + (q & 28) * 4 + (q >> 5) * 2), "h"((unsigned short)e) : "memory");
    }
}
__device__ __noinline__ void tail_overflow(Scratch* sc, unsigned mask, unsigned ht) {
    for (int i = 0; i < 6 * 16; i++)
        if (mask >> (i >> 4) & 1)
            entry_overflow(sc, __ldcg((const unsigned*)(sc->mail + ((NT + blockIdx.x) * 512 + ((ht + (i >> 4) * 96) & ~3u))) + (i & 15)));
}
__device__ __forceinline__ void bulk_s2g(void* dst, unsigned src, unsigned bytes) {
    asm volatile("cp.async.bulk.global.shared::cta.bulk_group [%0],[%1],%2;" ::"l"(dst), "r"(src), "r"(bytes) : "memory");
}
__device__ __forceinline__ void tma_reduce(const CUtensorMap* tm, unsigned src, int c0, int c1) {
    asm volatile("cp.reduce.async.bulk.tensor.2d.global.shared::cta.add.tile.bulk_group [%0,{%2,%3}],[%1];" ::"l"(tm), "r"(src), "r"(c0), "r"(c1) : "memory");
}
#define EV(id) nb_arrive<id, 544>()
#define WAIT_EV(id) do { __syncwarp(); nb_sync<id, 544>(); } while (0)

__global__ void __launch_bounds__(640, 1)
exphormer_kernel(const uint4* __restrict__ x, const uint4* __restrict__ dst4, const uint4* __restrict__ src4,
                 const uint4* __restrict__ wq, const uint4* __restrict__ wk, const int* __restrict__ esrc,
                 const int* __restrict__ edst, Scratch* __restrict__ sc, const uint4* __restrict__ dis, const uint4* __restrict__ wv,
                 const __grid_constant__ CUtensorMap tm_x, const __grid_constant__ CUtensorMap tm_wl, const __grid_constant__ CUtensorMap tm_wv,
                 const __grid_constant__ CUtensorMap tm_m, const __grid_constant__ CUtensorMap tm_ms,
                 const __grid_constant__ CUtensorMap tm_mail, const __grid_constant__ CUtensorMap tm_ot, const __grid_constant__ CUtensorMap tm_o256, const __grid_constant__ CUtensorMap tm_o16) {
    const unsigned tid = threadIdx.x, lane = tid & 31, g = lane >> 2, t = lane & 3;
    const unsigned b = blockIdx.x;
    const bool rowcta = b < NT;
    const int slice = b >> 2, range = b & 3;
    const int g0 = (range * NG) >> 2, g1 = ((range + 1) * NG) >> 2;
    STAMP(0);

    if (tid >= 512) {
    asm volatile("setmaxnreg.dec.sync.aligned.u32 %0;" ::"n"(REG_H));
    if (tid >= 544) {
        const unsigned ht = tid - 544;
        if (ht < 32) {
            if (lane == 0) asm volatile("prefetch.tensormap [%0];" ::"l"(&tm_mail) : "memory");
            __syncwarp();
            nb_sync<13, 160>();
            nb_sync<2, 352>();
            if (rowcta) {
                const uint4 c = lds128(sb + OFF_CNT1 + lane * 16);
                const unsigned cc[4] = {c.x, c.y, c.z, c.w};
#pragma unroll
                for (int i = 0; i < 4; i++)
                    if (cc[i] > 16) asm volatile("red.shared.or.b32 [%0],0x80000000;" ::"r"(sb + OFF_MAIL + (lane * 4 + i) * 64 + 60) : "memory");
                fence_async_smem();
                __syncwarp();
                if (elect())
                    asm volatile("cp.async.bulk.tensor.2d.global.shared::cta.bulk_group [%0,{%2,%3}],[%1];" ::"l"(&tm_mail), "r"(sb + OFF_MAIL), "r"(b * 16), "r"(0) : "memory");
                for (int i = 0; i < 4; i++)
                    if (lds32(sb + OFF_CNT1 + lane * 16 + i * 4) > 16) bulk_s2g(sc->mail + ((NT + lane * 4 + i) * 512 + b * 4), sb + OFF_IMG + (lane * 4 + i) * 64, 64);
                asm volatile("cp.async.bulk.commit_group;" ::: "memory");
                asm volatile("cp.async.bulk.wait_group 0;" ::: "memory");
                fence_async_gmem();
                __syncwarp();
            }
            if (rowcta) nb_arrive<1, 96>();
            if (elect()) {
                bar_arrive_relaxed(&sc->bar[0]);
                STAMPT(544, 47);
                if (rowcta) {
                    bar_poll(sc, 0);
                    fence_async_gmem();
                    mbar_expect(bar_mail, 8000);
                    bulk_g2s(sb + OFF_MAIL, sc->mail + b * 512, 8000, bar_mail);
                }
            }
            __syncwarp();
        } else if (ht < 64) {
            if (lane == 0) asm volatile("prefetch.tensormap [%0];" ::"l"(&tm_ms) : "memory");
            nb_sync<14, 192>();
            if (elect()) {
                asm volatile("cp.async.bulk.tensor.2d.global.shared::cta.bulk_group [%0,{%2,%3}],[%1];" ::"l"(&tm_ms), "r"(sb + OFF_MAIL + 8064), "r"((b & 7) * 32), "r"((b >> 3) * 16) : "memory");
                asm volatile("cp.async.bulk.commit_group;" ::: "memory");
                asm volatile("cp.async.bulk.wait_group 0;" ::: "memory");
                fence_async_gmem();
                bar_arrive_relaxed(&sc->bar[3 * 64]);
                STAMPT(576, 46);
            }
            __syncwarp();
        } else {
            if (lane < 5) {
                unsigned epoch;
                asm volatile("ld.relaxed.gpu.global.u32 %0,[%1];" : "=r"(epoch) : "l"(&sc->bar[lane * 64]) : "memory");
                sts32(sb + OFF_MISC + 32 + lane * 4, (epoch & ~(NCTA - 1)) + NCTA);
            }
            __syncwarp();
            nb_arrive<14, 192>();
            nb_arrive<15, 64>();
            nb_arrive<13, 160>();
        }
        if (rowcta) {
            if (ht >= 32) {
                nb_sync<1, 96>();
                const unsigned pad = (PADBIN + 4 * lane) << 16, h2 = ht - 32;
                sts128(sb + OFF_MAIL + 8000 + h2 * 16, make_uint4(pad, pad, pad, pad));
                if (h2 < 12) sts128(sb + OFF_MAIL + 9024 + h2 * 16, make_uint4(pad, pad, pad, pad));
#pragma unroll
                for (int k = 0; k < 9; k++) {
                    const unsigned dm = k < 3 ? DUMMY2 + (lane & 7) * 0x10001u : DUMMY2;
                    if (k % 3 < 2 || h2 < 32) sts128(sb + OFF_IMG + (k / 3) * 4096 + (k % 3) * 1024 + h2 * 16, make_uint4(dm, dm, dm, dm));
                }
            }
            nb_sync<13, 96>();
            mbar_wait(bar_mail);
            STAMPT(576, 16);
            uint4 e[6], h[6];
            unsigned flagged = 0, late = 0, longg = 0;
#pragma unroll
            for (int k = 0; k < 6; k++) e[k] = lds128(sb + OFF_MAIL + (ht + k * 96) * 16);
#pragma unroll
            for (int k = 0; k < 6; k++) { flagged |= (e[k].w >> 31) << k; e[k].w &= 0x7FFFFFFFu; }
            while (flagged) {
                const unsigned f = __ffs(flagged) - 1, k = atoms_add(sb + OFF_MISC + 4, 4);
                const uint4* sp = sc->mail + ((NT + b) * 512 + ((ht + f * 96) & ~3u));
                flagged &= flagged - 1;
                if (k < 76) {
#pragma unroll
                    for (int j = 0; j < 4; j++) cp16(sb + OFF_MAIL + 8000 + (k + j) * 16, sp + j);
                } else {
                    late |= 1u << f;
                }
            }
            cp_commit();
            __syncwarp();
#pragma unroll
            for (int k = 0; k < 6; k++) {
                if (k == 5) { cp_wait<0>(); nb_sync<1, 96>(); if (ht >= 20) e[5] = lds128(sb + OFF_MAIL + (ht + 480) * 16); }
                h[k] = make_uint4(atoms_inc(sb + OFF_CNT2 + (e[k].x >> 16)), atoms_inc(sb + OFF_CNT2 + (e[k].y >> 16)),
                                  atoms_inc(sb + OFF_CNT2 + (e[k].z >> 16)), atoms_inc(sb + OFF_CNT2 + (e[k].w >> 16)));
            }
#pragma unroll
            for (int k = 0; k < 6; k++)
                sts32(rank_addr(ht + k * 96), __byte_perm(__byte_perm(min(h[k].x, 255u), min(h[k].y, 255u), 0x0040), __byte_perm(min(h[k].z, 255u), min(h[k].w, 255u), 0x0040), 0x5410));
            nb_sync<1, 96>();
            STAMPT(576, 17);
            unsigned rare;
            {
                const bool sw = lane >= 16;
                const unsigned G0 = ht >> 5, G1 = min(G0 + 3, 4u);
                uint4 c[2];
                unsigned inc[2], st[2][4], lf[2], ex[2], xs[2], word[2], s2w[2], dp[2];
#pragma unroll
                for (int j = 0; j < 2; j++) c[j] = lds128(sb + OFF_CNT2 + (j ? G1 : G0) * 512 + lane * 16);
#pragma unroll
                for (int j = 0; j < 2; j++) dp[j] = lds32(sb + OFF_DIS + ((j ? G1 : G0) * 8 + g) * 4);
#pragma unroll
                for (int j = 0; j < 2; j++) { inc[j] = c[j].x + c[j].y + c[j].z + c[j].w; const unsigned u = __shfl_up_sync(~0u, inc[j], 8); if (lane >= 8) inc[j] += u; }
#pragma unroll
                for (int j = 0; j < 2; j++) { const unsigned u = __shfl_up_sync(~0u, inc[j], 16); if (sw) inc[j] += u; }
#pragma unroll
                for (int j = 0; j < 2; j++) {
                    const unsigned s2 = c[j].x + c[j].y;
                    st[j][0] = inc[j] - s2 - c[j].z - c[j].w; st[j][1] = st[j][0] + (sw ? c[j].y : c[j].x);
                    st[j][2] = st[j][0] + s2; st[j][3] = st[j][2] + (sw ? c[j].w : c[j].z);
                    const unsigned m0 = max(st[j][0], 32u), m1 = max(st[j][1], 32u), m2 = max(st[j][2], 32u), m3 = max(st[j][3], 32u), m4 = max(inc[j], 32u);
                    const unsigned Q = __reduce_add_sync(~0u, m4 - m0);
                    lf[j] = Q <= QCAP ? (m1 - m0) | (m2 - m1) << 8 | (m3 - m2) << 16 | (m4 - m3) << 24 : 0;
                    xs[j] = __reduce_add_sync(~0u, Q <= QCAP ? (m4 - m0) << (lane & 24) : 0);
                    if (Q > 64 && (j == 0 || ht < 64)) longg |= (Q <= QCAP ? 1u : 0x100u) << (j ? G1 : G0);
                    word[j] = min(st[j][0], 32u) | min(st[j][1], 32u) << 8 | min(st[j][2], 32u) << 16 | min(st[j][3], 32u) << 24;
                    ex[j] = lf[j];
                }
#pragma unroll
                for (int d = 1; d < 8; d <<= 1)
#pragma unroll
                    for (int j = 0; j < 2; j++) { const unsigned u = __shfl_up_sync(~0u, ex[j], d); if ((lane & 7) >= d) ex[j] += u; }
#pragma unroll
                for (int j = 0; j < 2; j++) {
                    const unsigned tot = __shfl_sync(~0u, ex[j], lane | 7);
                    s2w[j] = tot * 0x01010100u + (((xs[j] * 0x01010100u) >> (lane & 24)) & 255) * 0x01010101u;
                    const unsigned q0 = s2w[j] + ex[j] - lf[j];
                    unsigned w4[4];
#pragma unroll
                    for (int i = 0; i < 4; i++)
                        w4[i] = __byte_perm((((q0 >> (8 * i)) & 255) + 192 + st[j][i] - max(st[j][i], 32u)) * 0x801 + 0x400, min(st[j][i], 32u), 0x5410);
                    if (j == 0 || ht < 64)
                        sts128(sb + OFF_CNT2 + (j ? G1 : G0) * 512 + lane * 16, make_uint4(sw ? w4[1] : w4[0], sw ? w4[0] : w4[1], sw ? w4[3] : w4[2], sw ? w4[2] : w4[3]));
                }
                if (longg && lane == 0) asm volatile("red.shared.or.b32 [%0],%1;" ::"r"(sb + OFF_MISC + 8), "r"(longg) : "memory");
                asm volatile("{.reg .pred p; setp.ne.u32 p,%1,0; bar.red.popc.u32 %0,1,96,p;}" : "=r"(rare) : "r"(longg) : "memory");
                if (ht == 64) mbar_arrive(bar_p);
#pragma unroll
                for (int j = 0; j < 2; j++) {
                    const unsigned wa = __shfl_sync(~0u, word[j], (g >> 1) * 8 + 2 * t), wb = __shfl_sync(~0u, word[j], (g >> 1) * 8 + 2 * t + 1);
                    const unsigned w2 = s2w[j];
                    const unsigned d128 = hmul2(dp[j], 0x43004300u);
                    const unsigned ha = sb + OFF_IMG + 4096 + (j ? G1 : G0) * 512 + lane * 16;
                    if (j == 0 || ht < 64) {
                        asm volatile("st.shared.v2.u32 [%0],{%1,%2};" ::"r"(ha), "r"(__byte_perm(wa, wb, (g & 1) ? 0x7362 : 0x5140)),
                                     "r"(__byte_perm(w2, w2, (g & 1) ? 0x3322 : 0x1100) + 0x1C201C20u - t * 0x08080808u) : "memory");
                        sts32(ha + 8, __byte_perm(d128, d128, lane >= 16 ? 0x1032 : 0x3210));
                    }
                }
            }
            if (__builtin_expect(!rare, 1)) {
                if (ht >= 32) place4(480 + ht);
            } else {
                place_slow(sc, ht, lds32(sb + OFF_MISC + 8) >> 8);
                nb_sync<1, 96>();
                for (longg &= 255; longg; longg &= longg - 1)
                    asm volatile("red.shared.or.b32 [%0],0x80000000;" ::"r"(sb + OFF_IMG + 4096 + (__ffs(longg) - 1) * 512 + lane * 16 + 12) : "memory");
            }
            if (__builtin_expect(late, 0)) tail_overflow(sc, late, ht);
            __syncwarp();
            STAMPT(576, 4);
            if (ht < 32) nb_sync<13, 608>(); else nb_arrive<13, 608>();
            STAMPT(544, 18);
        }
        if (ht < 32 && elect()) {
            if (rowcta) {
                fence_async_smem();
                for (int c = 0; c < 3; c++) bulk_s2g(sc->lists + (c * LSTR + b * 160), sb + OFF_IMG + c * 4096, 2560);
                asm volatile("cp.async.bulk.commit_group;" ::: "memory");
                const unsigned novf = lds32(sb + OFF_MISC), bad = lds32(sb + OFF_MISC + 20);
                if (__builtin_expect(novf | bad, 0)) {
                    sc->ovfn[b] = make_uint2(lds32(sb + OFF_MISC + 48), novf);
                    raise_flag(&sc->bar[4 * 64 + 1], lds32(sb + OFF_MISC + 48), (novf ? 1 : 0) | (bad ? 2 : 0));
                    __threadfence();
                }
                asm volatile("cp.async.bulk.wait_group 0;" ::: "memory");
                fence_async_gmem();
            }
            bar_arrive_relaxed(&sc->bar[4 * 64]);
            STAMPT(544, 19);
            sts32(sb + OFF_MISC + 28, bar_poll2(&sc->bar[4 * 64], lds32(sb + OFF_MISC + 48)));
            mbar_arrive(bar_c);
            STAMPT(544, 23);
        }
    } else {
        const bool one = elect();
        auto load_xl = [&](int i) {
            mbar_expect(bar_full + 8 * i, 32768 + 10240);
            tma_load2d(sb + OFF_T + i * 10240, &tm_x, i * 64, b * TILE, bar_full + 8 * i);
            tma_load3d(sb + OFF_S + i * 32768, &tm_wl, i * 64, bar_full + 8 * i);
        };
        auto load_m = [&](int i, int slot) {
            mbar_expect(bar_full + 32 + 8 * i, 32768);
            tma_load3d(sb + OFF_S + slot * 32768, &tm_m, i * 64, bar_full + 32 + 8 * i);
        };
        auto load_v = [&](int i, int slot) {
            mbar_expect(bar_full + 64 + 8 * i, 32768);
            tma_load3d(sb + OFF_S + slot * 32768, &tm_wv, i * 64, bar_full + 64 + 8 * i);
        };
        const char* hsl = (const char*)(sc->hs + slice * NN);
        auto fill = [&](int slot) { bulk_g2s(sb + OFF_S + slot * 32768, hsl + slot * 32768, slot == 4 ? NN * 16 - 4 * 32768 : 32768, bar_fill); };
        const unsigned t0 = clock();
        if (one) {
            for (int i = 0; i < 2; i++) mbar_init(bar_full + 8 * i, 1);
            asm volatile("fence.mbarrier_init.release.cluster;" ::: "memory");
            while ((unsigned)clock() - t0 < XD0) {}
            if (rowcta) load_xl(0);
            STAMPT(512, 41);
            for (int i = 2; i < 12; i++) mbar_init(bar_full + 8 * i, 1);
            mbar_init(bar_go, 1); mbar_init(bar_p, 1);
            for (int i = 0; i < 4; i++) mbar_init(bar_fill + 8 * i, 1);
            for (int i = 0; i < 10; i++) mbar_init(bar_rd + 8 * i, i < 9 ? 16 : g1 - g0 - 144);
            asm volatile("fence.mbarrier_init.release.cluster;" ::: "memory");
            if ((unsigned)__cvta_generic_to_shared(smem_raw) != sb) __trap();
            mbar_expect(bar_fill, NN * 16);
        }
        __syncwarp();
        nb_arrive<3, 544>();
        nb_arrive<13, 160>();
        if (one && rowcta) {
            while ((unsigned)clock() - t0 < XD1) {}
            load_xl(1);
            STAMPT(512, 40);
        }
        __syncwarp();
        nb_sync<15, 64>();
        if (rowcta) {
            if (one) {
                if (XD2) { while ((unsigned)clock() - t0 < XD2 + 1) {} } else mbar_wait(bar_full);
                load_xl(2);
                STAMPT(512, 52);
                mbar_wait(bar_full + (XD2 ? 0 : 8)); load_xl(3);
                STAMPT(512, 53);
                asm volatile("cp.async.bulk.prefetch.L2.global [%0],%1;" ::"l"(wv + b * 64), "r"(b == NT - 1 ? 4096 : 1024) : "memory");
                asm volatile("prefetch.tensormap [%0];" ::"l"(&tm_m) : "memory");
                asm volatile("prefetch.tensormap [%0];" ::"l"(&tm_wv) : "memory");
                bar_poll(sc, 3);
                STAMPT(512, 48);
                fence_async_gmem();
            }
            WAIT_EV(5); if (one) { load_m(0, 0); load_m(1, 1); mbar_arrive(bar_go); }
            WAIT_EV(6); if (one) load_m(2, 3);
            WAIT_EV(7); if (one) load_m(3, 0);
            WAIT_EV(12); if (one) bar_arrive(&sc->bar[2 * 64]);
            STAMPT(512, 24);
            WAIT_EV(14); if (one) { fence_async_smem(); load_v(0, 4); load_v(1, 2); }
            WAIT_EV(15);
            if (one) {
                fence_async_smem();
                load_v(2, 1); load_v(3, 3);
                bar_poll(sc, 2);
                fence_async_gmem();
            }
            STAMPT(512, 25);
            WAIT_EV(2); STAMPT(512, 1); if (one) { fill(0); if (VRS > 0) fill(4); if (VRS > 1) fill(2); }
            WAIT_EV(4); if (one) fill(1);
            WAIT_EV(5); if (one) fill(3);
            if (VRS < 2) { WAIT_EV(6); if (one) fill(2); }
            if (VRS < 1) { WAIT_EV(7); if (one) fill(4); }
            WAIT_EV(12);
            STAMPT(512, 15);
            if (one) {
                fence_async_smem();
#pragma unroll
                for (int kb = 0; kb < 4; kb++)
                    asm volatile("cp.async.bulk.tensor.2d.global.shared::cta.bulk_group [%0,{%2,%3}],[%1];"
                                 ::"l"(&tm_ot), "r"(sb + OFF_T + kb * 10240), "r"(kb * 64), "r"(b * TILE) : "memory");
                asm volatile("cp.async.bulk.commit_group;" ::: "memory");
                asm volatile("cp.async.bulk.wait_group 0;" ::: "memory");
                fence_async_gmem();
            }
        } else {
            if (one) {
                bar_arrive(&sc->bar[2 * 64]);
                bar_poll(sc, 2);
                fence_async_gmem(); fence_async_smem();
                for (int i = 0; i < 5; i++) fill(i);
            }
        }
        if (one) {
            bar_arrive_relaxed(&sc->bar[1 * 64]);
            mbar_arrive(bar_t);
            STAMPT(512, 26);
            bar_poll(sc, 1);
            fence_async_gmem();
            STAMPT(512, 27);
            unsigned tn = clock();
#pragma unroll 1
            for (int r = 0; r < 9; r++) {
                mbar_wait(bar_rd + 8 * r);
                fence_async_smem();
#pragma unroll
                for (int i = 0; i < 256 / PBOX; i++) {
                    while ((int)(clock() - tn) < 0) __nanosleep(20);
                    tn = clock() + PACE;
                    tma_reduce(&tm_o256, sb + OFF_STG + r * 4096 + i * PBOX * 16, slice * 8, (g0 + 16 * r) * 16 + i * PBOX);
                }
            }
            mbar_wait(bar_rd + 72);
            STAMPT(512, 14);
            fence_async_smem();
            for (int i = 144; i < g1 - g0; i++) tma_reduce(&tm_o16, sb + OFF_STG + i * 256, slice * 8, (g0 + i) * 16);
            asm volatile("cp.async.bulk.commit_group;" ::: "memory");
            asm volatile("cp.async.bulk.wait_group.read 0;" ::: "memory");
            STAMPT(512, 13);
        }
    }
    } else {
    if (tid < 32) {
        unsigned bad = 0;
        uint4 xd[3];
#pragma unroll
        for (int k = 0; k < 3; k++) xd[k] = ldg_na((const uint4*)edst + min(b * TILE + k * 32 + lane, NN - 1u));
#pragma unroll
        for (int k = 0; k < 3; k++) { const unsigned n = min(b * TILE + k * 32 + lane, NN - 1u); bad |= (xd[k].x ^ n) | (xd[k].y ^ n) | (xd[k].z ^ n) | (xd[k].w ^ n); }
        bad = __any_sync(~0u, bad);
        if (lane == 0) sts32(sb + OFF_MISC + 20, bad);
        __syncwarp();
        nb_arrive<13, 160>();
    } else if (tid < 64) {
        const uint4* ep = (const uint4*)esrc + (min(b, NT - 1u) * TILE + lane);
        cp16(sb + OFF_EIDX + lane * 16, ep); cp16(sb + OFF_EIDX + 512 + lane * 16, ep + 32);
        if (lane < 16) cp16(sb + OFF_EIDX + 1024 + lane * 16, ep + 64);
        if (lane < 10) cp16(sb + OFF_DIS + lane * 16, dis + (min(b, NT - 1u) * 10 + lane));
        cp_commit();
        cp_wait<0>();
        nb_arrive<13, 160>();
    } else if (tid >= 192) {
        if (rowcta) {
            const unsigned bt = tid - 192;
            if (ED0) { const unsigned t0 = clock(); while ((unsigned)clock() - t0 < ED0 + 1) {} }
            const uint4 ed = ldg_na(dst4 + (b * 320 + bt)), es = ldg_na(src4 + (b * 320 + bt));
            const unsigned pad = (PADBIN + 4 * ((bt & 3) + ((b * 4) & 28))) << 16;
#pragma unroll
            for (int k = 0; k < 4; k++) if ((k & 1) == 0 || bt < 180) sts128(sb + OFF_MAIL + (k >> 1) * 9216 + (bt + (k & 1) * 320) * 16, make_uint4(pad, pad, pad, pad));
            if (bt < (512 + 2688) / 16) sts128(sb + OFF_CNT1 + bt * 16, make_uint4(0, 0, 0, 0));
            if (bt == 319) sts128(sb + OFF_MISC, make_uint4(0, 0, 0, 0));
            unsigned z;
            asm volatile("{.reg .pred p; setp.eq.u32 p,%1,0xFFFFFFFF; bar.red.popc.u32 %0,4,320,p;}" : "=r"(z) : "r"(bt) : "memory");
            const unsigned dd[4] = {ed.x + z, ed.y + z, ed.z + z, ed.w + z}, ss[4] = {es.x + z, es.y + z, es.z + z, es.w + z};
            unsigned rk[4], ow[4];
#pragma unroll
            for (int i = 0; i < 4; i++) { ow[i] = dd[i] / TILE; rk[i] = atoms_inc(sb + OFF_CNT1 + ow[i] * 4); }
#pragma unroll
            for (int i = 0; i < 4; i++) {
                const unsigned dl = dd[i] - ow[i] * TILE;
                const unsigned e = bitsel(ss[i] << 20, bitsel(dl << 21, dl << 18, 0xFF800000u), 0x00700000u) + ss[i];
                asm volatile("{.reg .pred p; setp.lt.u32 p,%2,%3; @p st.shared.u32 [%0],%1;}" ::"r"(sb + OFF_MAIL + ow[i] * 64 + rk[i] * 4 + (rk[i] >> 4) * (9216 - 64)), "r"(e), "r"(rk[i]), "n"(CELL) : "memory");
            }
            if (__builtin_expect((rk[0] | rk[1] | rk[2] | rk[3]) >= CELL, 0)) {
#pragma unroll
                for (int i = 0; i < 4; i++) if (rk[i] >= CELL) push_overflow(sc, dd[i], ss[i]);
            }
        }
        STAMPT(416, 44);
        nb_arrive<2, 352>();
    } else {
        const unsigned fw = b >> 3, hq = b & 7, q = (tid >> 5) - 2;
        const unsigned ma = sb + OFF_S + 4 * 32768 + 8192 + q * 6144;
        {
            const unsigned r = lane >> 3, da = ma + r * 128 + (((lane ^ r) & 7) << 4);
            const uint4* pa = wq + ((16 * fw + r) * 32 + q * 8 + (lane & 7));
            const uint4* pb = wk + ((32 * hq + r) * 32 + q * 8 + (lane & 7));
#pragma unroll
            for (int u = 0; u < 12; u++) cp16((da ^ ((u & 1) << 6)) + u * 512, u < 4 ? pa + u * 128 : pb + (u - 4) * 128);
            cp_commit();
        }
        const unsigned aa = ma + (lane & 15) * 128 + ((((lane >> 4) ^ lane) & 7) << 4);
        const unsigned br = 4 * ((lane & 7) >> 1) + 2 * (lane >> 4) + (lane & 1);
        const unsigned ba = ma + 2048 + br * 128 + (((((lane >> 3) & 1) ^ br) & 7) << 4);
        float c[4][4];
#pragma unroll
        for (int u = 0; u < 4; u++) c[u][0] = c[u][1] = c[u][2] = c[u][3] = 0.f;
        STAMPT(64, 38);
        cp_wait<0>();
        __syncwarp();
        STAMPT(64, 39);
#pragma unroll
        for (int k = 0; k < 4; k++) {
            const uint4 a = ldsm4(aa ^ (k << 5)), b0 = ldsm4(ba ^ (k << 5)), b1 = ldsm4((ba ^ (k << 5)) + 2048);
            mma16816(c[0], a.x, a.y, a.z, a.w, b0.x, b0.y); mma16816(c[1], a.x, a.y, a.z, a.w, b0.z, b0.w);
            mma16816(c[2], a.x, a.y, a.z, a.w, b1.x, b1.y); mma16816(c[3], a.x, a.y, a.z, a.w, b1.z, b1.w);
        }
        const unsigned ra = sb + OFF_S + 4 * 32768 + lane * 16;
#pragma unroll
        for (int i = 0; i < 4; i++)
            sts128(ra + q * 2048 + i * 512, make_uint4(__float_as_uint(c[2 * (i & 1)][2 * (i >> 1)]), __float_as_uint(c[2 * (i & 1)][2 * (i >> 1) + 1]),
                                                       __float_as_uint(c[2 * (i & 1) + 1][2 * (i >> 1)]), __float_as_uint(c[2 * (i & 1) + 1][2 * (i >> 1) + 1])));
        STAMPT(64, 42);
        nb_sync<8, 128>();
        float m[4] = {0, 0, 0, 0};
#pragma unroll
        for (int i = 0; i < 4; i++) {
            const uint4 u = lds128(ra + i * 2048 + q * 512);
            m[0] += __uint_as_float(u.x); m[1] += __uint_as_float(u.y); m[2] += __uint_as_float(u.z); m[3] += __uint_as_float(u.w);
        }
        const float k = 0.0625f * 1.4426950408889634f;
        asm volatile("st.shared.v2.u32 [%0],{%1,%2};" ::"r"(sb + OFF_MAIL + 8064 + (8 * (q >> 1) + g) * 64 + (q & 1) * 32 + t * 8),
                     "r"(pack2(m[0] * k, m[1] * k)), "r"(pack2(m[2] * k, m[3] * k)) : "memory");
        fence_async_smem();
        STAMPT(64, 43);
        nb_arrive<14, 192>();
    }
    asm volatile("setmaxnreg.inc.sync.aligned.u32 %0;" ::"n"(REG_W));
    const int w = __shfl_sync(~0u, tid >> 5, 0), wg = w >> 2;
    const int grp0 = g0 + w;
    const uint4* lp = sc->lists + (grp0 * 32 + lane);
    uint4 L0, L1;
    nb_sync<3, 544>();

    if (__builtin_expect(rowcta, 1)) {
        const unsigned descA = 0x10000u + (SB0 + OFF_S) / 16 + wg * 512;
        const unsigned greg = sb + OFF_S + w * 2048 + lane * 16;
        float d[40];
        unsigned pk[20];
        unsigned* hp = (unsigned*)(sc->hs + (2 * w * NN + b * TILE)) + lane;
        auto mma_k = [&](int Q, int slot, int st, int k0, int k1) {
            if (st < 0) wg_fence();
#pragma unroll
            for (int k = k0; k < k1; k++) {
                if (st >= 0) wg_fence();
                wg80(d, descA + slot * 2048 + k * 128, 0x10000u + (SB0 + OFF_T) / 16 + (Q & 3) * 640 + k * 2, st == -2 ? k != 0 : st == -3 || ((Q & 3) | k) != 0);
                if (st >= 0) {
#pragma unroll
                    for (int j = st + k; j < st + k + 1; j++)
                        if (j < 20) asm volatile("st.global.u32 [%0],%1;" ::"l"(hp + (j >> 1) * 32 + (j & 1) * (NN * 4)), "r"(pk[j]) : "memory");
                }
            }
            wg_commit();
        };
        auto mma_q = [&](int Q, int slot, int st) { mma_k(Q, slot, st, 0, 4); };
        auto mma_head = [&](int Q, int slot, int st) { mma_k(Q, slot, st, 0, KH); wg_wait<1>(); };
        auto mma_tail = [&](int Q, int slot, int st) { mma_k(Q, slot, st, KH, 4); };
        const uint4* xl = x + lane;
        auto eidx = [&](int i) { return lds128(sb + OFF_EIDX + (w * 5 + i) * 16); };
        auto gather = [&](const uint4& ix, int slot) {
            cp16(greg + slot * 32768, xl + ix.x * 32u); cp16(greg + slot * 32768 + 512, xl + ix.y * 32u);
            cp16(greg + slot * 32768 + 1024, xl + ix.z * 32u); cp16(greg + slot * 32768 + 1536, xl + ix.w * 32u);
            cp_commit();
        };
        const uint4 ix0 = eidx(0), ix1 = eidx(1), ix2 = eidx(2), ix3 = eidx(3), ix4 = eidx(4);
        uint4 gv[5][4];
        const unsigned gld = sb + OFF_S + w * 2048 + ((lane >> 3) & 1) * 512 + (lane >> 4) * 128 + (lane & 7) * 16;
        auto to_regs = [&](int i, int slot) {
            __syncwarp();
#pragma unroll
            for (int j = 0; j < 4; j++) gv[i][j] = ldsm4(gld + slot * 32768 + (j & 1) * 256 + (j >> 1) * 1024);
        };
        unsigned ds[10];
#pragma unroll
        for (int j = 0; j < 10; j++) ds[j] = lds32(sb + OFF_DIS + (4 * j + t) * 4);
        STAMPT(288, 2);
        mbar_wait(bar_full);
        STAMPT(288, 3);
        mma_q(0, 0, -1);
        mbar_wait(bar_full + 8);
        STAMPT(288, 50);
        mma_q(1, 1, -1);
        mbar_wait(bar_full + 16);
        STAMPT(288, 51);
        mma_head(2, 2, -1);
        EV(5);
        mma_tail(2, 2, -1);
        mbar_wait(bar_full + 24);
        STAMP(5);
        mma_q(3, 3, -1);
        mbar_wait(bar_go);
        gather(ix0, 4);
        wg_wait<0>();
        EV(6);
        STAMP(6);
#pragma unroll
        for (int j = 0; j < 20; j++) pk[j] = movm(hmul2(pack2(d[2 * j], d[2 * j + 1]), ds[j >> 1]));
#pragma unroll
        for (int j = 0; j < STPRE; j++) asm volatile("st.global.u32 [%0],%1;" ::"l"(hp + (j >> 1) * 32 + (j & 1) * (NN * 4)), "r"(pk[j]) : "memory");
        STAMP(7);
        if (G1POS < 2) nb_sync_id(8 + wg, 128);
        if (G1POS == 0) gather(ix1, 2);
        mbar_wait(bar_full + 32);
        if (G1POS == 1) { if (G0POS == 2) gather(ix0, 4); gather(ix1, 2); }
        STAMP(21);
        if (G1POS == 2) {
            mma_k(4, 0, STPRE, 0, 1);
            if (G0POS == 2) gather(ix0, 4);
            nb_sync_id(8 + wg, 128);
            gather(ix1, 2);
            mma_k(4, 0, STPRE, 1, 4);
        } else {
            mma_q(4, 0, STPRE);
        }
        STAMP(28);
        mbar_wait(bar_full + 40);
        mma_head(5, 1, STPRE + 4);
        EV(7);
        mma_tail(5, 1, STPRE + 4);
        STAMP(29);
        mbar_wait(bar_full + 48);
        STAMP(30);
        mma_head(6, 3, STPRE + 8);
        nb_sync_id(8 + wg, 128);
        gather(ix2, 1);
        mma_tail(6, 3, STPRE + 8);
        STAMP(31);
        mbar_wait(bar_full + 56);
        STAMP(32);
        mma_head(7, 0, STPRE + 12);
        nb_sync_id(8 + wg, 128);
        gather(ix3, 3);
        mma_tail(7, 0, STPRE + 12);
        EV(12);
        wg_wait<0>();
        STAMP(20);
        pack_acc(pk, d);
        nb_sync<0, 512>();
        acc_to_tile(pk, w, lane);
        gather(ix4, 0);
        cp_wait<3>();
        to_regs(0, 4);
        nb_sync<0, 512>();
        STAMP(8);
        uint4 vf[8];
        {
            const unsigned delta = t ^ (g >> 1), alsm = sb + OFF_ALPHA + w * 128;
            const bool par = g & 1;
            unsigned ta[5];
#pragma unroll
            for (int i = 0; i < 5; i++) ta[i] = tile_addr(w * 5 + i, lane);
            float v[4], u[4];
            to_regs(1, 2);
            EV(14);
            attn_scores(v, true, par, gv[0], ta[0]);
            attn_scores(v, delta == 1, par, gv[1], ta[1] ^ 32);
            cp_wait<2>();
            to_regs(2, 1);
            attn_scores(v, delta == 2, par, gv[2], ta[2] ^ 64);
            STAMP(33);
            cp_wait<1>();
            to_regs(3, 3);
            EV(15);
            STAMP(34);
            attn_scores(v, delta == 3, par, gv[3], ta[3] ^ 96);
            cp_wait<0>();
            to_regs(4, 0);
            STAMP(35);
            attn_scores(u, true, par, gv[4], ta[4]);
            attn_softmax(v, u, lane, alsm + ((lane & 4) + delta) * 16 + (lane >> 3) * 4);
            STAMP(49);
            const unsigned va = sb + OFF_S + wg * 8192 + ((lane & 7) + (lane >> 4) * 8) * 128 + (((2 * (w & 3) + ((lane >> 3) & 1)) ^ (lane & 7)) << 4);
            if (VRS > 0) mbar_wait(bar_full + 64);
            if (VRS > 1) mbar_wait(bar_full + 72);
            uint4 al = lds128(alsm);
#pragma unroll
            for (int i = 0; i < 5; i++) {
                const uint4 a = al;
                if (i < 4) al = lds128(alsm + (i + 1) * 16);
                attn_mix(gv[i], a, ta[i]);
                if (i == PLACE_AT) {
                    mbar_wait(bar_p);
                    if (__builtin_expect(lds32(sb + OFF_MISC + 8) == 0, 1)) place4(tid);
                    nb_arrive<13, 608>();
                }
                if (i >= 1 && i <= VRS) {
#pragma unroll
                    for (int k = 0; k < 4; k++) vf[4 * (i - 1) + k] = ldsm4t(va + (i == 1 ? 4 : 2) * 32768 + k * 2048);
                }
            }
        }
        STAMP(36);
        mbar_wait(bar_full + 80);
        fence_async_smem();
        STAMP(22);
        EV(2);
        nb_sync<0, 512>();
        mma_k(10, 1, -2, 0, 4);
        mbar_wait(bar_full + 88);
        mma_head(11, 3, -1);
        EV(4);
        mma_tail(11, 3, -1);
        auto mma_r = [&](int k0, int k1) {
            wg_fence();
#pragma unroll
            for (int k = k0; k < k1; k++) wg80r(d, vf[k], 0x10000u + (SB0 + OFF_T) / 16 + (k >> 2) * 640 + (k & 3) * 2);
            wg_commit();
        };
        if (VRS < 2) {
            mbar_wait(bar_full + 72);
            mma_head(9, 2, -1);
            EV(5);
            mma_tail(9, 2, -1);
        } else {
            mma_r(4, 5); wg_wait<1>(); EV(5); mma_r(5, 8);
        }
        if (VRS < 1) {
            mbar_wait(bar_full + 64);
            mma_k(8, 4, -3, 0, KH); wg_wait<1>();
            EV(6);
            mma_tail(8, 4, -1);
        } else if (VRS == 1) {
            mma_r(0, 1); wg_wait<1>(); EV(6); mma_r(1, 4);
        } else {
            mma_r(0, 4);
        }
        mbar_wait(bar_c);
        L1 = ldg_na(lp); L0 = ldg_na(lp + LSTR);
        wg_wait<0>();
        if (VRS < 1) EV(7);
        STAMP(9);
        pack_acc(pk, d);
        nb_sync<0, 512>();
        STAMP(10);
        if (__builtin_expect(lds32(sb + OFF_MISC + 28) & 2, 0)) {
            for (int i = 0; i < 5; i++) sts128(tile_addr(w * 5 + i, lane), attn_generic(b * TILE + w * 5 + i, x, esrc, edst, wq, wk, wv));
        } else {
            acc_to_tile(pk, w, lane);
        }
        EV(12);
    } else {
        mbar_wait(bar_c);
        L1 = ldg_na(lp); L0 = ldg_na(lp + LSTR);
    }

    const unsigned flags = lds32(sb + OFF_MISC + 28);
    const bool anyovf = flags & 1;
    const unsigned zero = flags >> 8;
    const unsigned c64 = 0x64646464u + zero;
    if (lane < 8) sts128(sb + OFF_S + NN * 16 + lane * 16, make_uint4(0, 0, 0, 0));
    const int more = anyovf ? 0x7FFFFFFF : NN << 16;
    const float zmask = (lane >= 28) ? 0.f : -1.f;
    unsigned stg = sb + OFF_STG + w * 256 + (((lane & 7) * 2 + ((lane >> 3) & 1)) ^ ((lane >> 2) & 1)) * 16;
    unsigned rdb = bar_rd, rde = bar_rd + 48;
    __syncwarp();
    mbar_wait(bar_fill);
    STAMP(11);
    CLK0(64);
#pragma unroll 1
    for (int part = 0; part < 2; part++) {
#pragma unroll 1
        do {
            unsigned ad[9], sA, sB, tA, tB, mx;
            ad[0] = row_lo(L1.x); ad[1] = row_hi(L1.x); ad[2] = row_lo(L1.y); ad[3] = row_hi(L1.y);
            ad[4] = row_lo(L1.z); ad[5] = row_hi(L1.z); ad[6] = row_lo(L1.w); ad[7] = row_hi(L1.w); ad[8] = row_lo(L0.w);
            asm volatile("prmt.b32 %0,%2,%3,0x4140;\n prmt.b32 %1,%2,%3,0x4342;" : "=r"(sA), "=r"(sB) : "r"(L0.x), "r"(c64));
            asm volatile("prmt.b32 %0,%2,%3,0x4140;\n prmt.b32 %1,%2,%3,0x4342;" : "=r"(tA), "=r"(tB) : "r"(L0.y), "r"(c64));
            asm volatile("mov.b32 %0,%1;" : "=r"(mx) : "r"(L0.w));
            const float dA = blo_v(L0.z), dB = bhi_v(L0.z);
            L1 = ldg_na(lp + 16 * 32); L0 = ldg_na(lp + 16 * 32 + LSTR);
            const bool p9 = __any_sync(~0u, (int)mx < more);
            float acc0[4] = {0, 0, 0, 0}, acc1[4] = {0, 0, 0, 0};
            uint4 v[9], a0, a1;
#pragma unroll
            for (int s = 0; s < LA; s++) v[s] = ldsm4t(sb + OFF_S + ad[s]);
            a0 = p3_sel(0, sA, sB); a1 = p3_sel(1, sA, sB);
            sched_fence(zero);
#pragma unroll
            for (int s = 0; s < 9; s++) {
                uint4 n0, n1;
                if (s < 8) n0 = p3_sel(2 * s + 2, s < 7 ? sA : tA, s < 7 ? sB : tB);
                mma16816(acc0, a0.x, a0.y, a0.z, a0.w, v[s].x, v[s].y);
                if (s + LA < 9) v[s + LA] = ldsm4t(sb + OFF_S + ad[s + LA]);
                if (s < 8) n1 = p3_sel(2 * s + 3, s < 7 ? sA : tA, s < 7 ? sB : tB);
                mma16816(acc1, a1.x, a1.y, a1.z, a1.w, v[s].z, v[s].w);
                a0 = n0; a1 = n1;
            }
            if (__builtin_expect(p9, 0)) {
                p3_step(acc0, acc1, row_hi(mx & 0x7FFFFFFFu), 16, tA, tB);
                if (__any_sync(~0u, (int)mx < 0)) {
                    const uint4 C2 = ldg_na(lp + 2 * LSTR);
                    p3_step(acc0, acc1, row_lo(C2.x), 24, tA, tB); p3_step(acc0, acc1, row_hi(C2.x), 32, tA, tB);
                    p3_step(acc0, acc1, row_lo(C2.y), 40, tA, tB); p3_step(acc0, acc1, row_hi(C2.y), 48, tA, tB);
                }
                if (anyovf) {
                    float4 e = p3_overflow(sc, grp0 + 2 * (rdb - bar_rd), sb + OFF_S);
                    float s0 = e.x + e.z, s1 = e.y + e.w;
                    for (int k = 4; k < 32; k <<= 1) {
                        float u0 = __shfl_down_sync(~0u, s0, k), u1 = __shfl_down_sync(~0u, s1, k);
                        if (lane + k < 32) { s0 += u0; s1 += u1; }
                    }
                    acc0[0] += s0; acc0[1] += s1; acc0[2] += s0 - e.x; acc0[3] += s1 - e.y;
                }
            }
            float c0 = acc0[0] + acc1[0], c1 = acc0[1] + acc1[1], c2 = acc0[2] + acc1[2], c3 = acc0[3] + acc1[3];
            float n0 = __shfl_down_sync(~0u, c0, 4), n1 = __shfl_down_sync(~0u, c1, 4);
            float o0 = c0 - c2, o1 = c1 - c3, o2 = fmaf(n0, zmask, c2), o3 = fmaf(n1, zmask, c3);
            asm volatile("stmatrix.sync.aligned.m8n8.x2.shared.b16 [%0],{%1,%2};" ::"r"(stg), "r"(pack2(o0 * dA, o1 * dA)), "r"(pack2(o2 * dB, o3 * dB)) : "memory");
            __syncwarp();
            asm volatile("{.reg .pred p; setp.eq.u32 p,%1,0; @p mbarrier.arrive.shared.b64 _,[%0];}" ::"r"(rdb), "r"(lane) : "memory");
            stg += 4096;
            rdb += 8;
            lp += 16 * 32;
        } while (rdb != rde);
        mbar_wait(bar_t);
        rde = bar_rd + 8 * ((g1 - grp0 + 15) >> 4);
    }
    STAMP(12);
    CLK1(64, 60); STAMPT(0, 61); STAMPT(352, 62); STAMPT(480, 63);
    }
}

typedef CUresult (*EncodeFn)(CUtensorMap*, CUtensorMapDataType, cuuint32_t, void*, const cuuint64_t*, const cuuint64_t*,
                             const cuuint32_t*, const cuuint32_t*, CUtensorMapInterleave, CUtensorMapSwizzle,
                             CUtensorMapL2promotion, CUtensorMapFloatOOBfill);

}

extern "C" void kernel_launch(void* const* d_in, const int* in_sizes, int n_in, void* d_out, int out_size) {
    (void)in_sizes; (void)n_in; (void)out_size;
    static EncodeFn enc = nullptr;
    static void* scratch = nullptr;
    if (!enc) {
        cudaGetSymbolAddress(&scratch, g_scratch);
        void* fn = nullptr;
        cudaDriverEntryPointQueryResult qr;
        cudaGetDriverEntryPoint("cuTensorMapEncodeTiled", &fn, cudaEnableDefault, &qr);
        enc = (EncodeFn)fn;
        cudaFuncSetAttribute(exphormer_kernel, cudaFuncAttributeMaxDynamicSharedMemorySize, SMEM_BYTES);
    }
    CUtensorMap tm_m, tm_ms, tm_mail, tm_x, tm_wl, tm_wv, tm_ot, tm_o256, tm_o16;
    auto mk = [&](CUtensorMap* tm, void* p, int rows, int bc, int br, CUtensorMapSwizzle sw, CUtensorMapL2promotion pr) {
        cuuint64_t gd[2] = {256, (cuuint64_t)rows}, gs[1] = {512};
        cuuint32_t es[2] = {1, 1}, bx[2] = {(cuuint32_t)bc, (cuuint32_t)br};
        enc(tm, CU_TENSOR_MAP_DATA_TYPE_BFLOAT16, 2, p, gd, gs, bx, es, CU_TENSOR_MAP_INTERLEAVE_NONE, sw, pr, CU_TENSOR_MAP_FLOAT_OOB_FILL_NONE);
    };
    for (int i = 0; i < 3; i++) {
        cuuint64_t gd[3] = {64, 256, 4}, gs[2] = {512, 128};
        cuuint32_t es[3] = {1, 1, 1}, bx[3] = {64, 64, 4};
        enc(i == 2 ? &tm_m : i ? &tm_wv : &tm_wl, CU_TENSOR_MAP_DATA_TYPE_BFLOAT16, 3, i == 2 ? scratch : d_in[i ? 9 : 6], gd, gs, bx, es, CU_TENSOR_MAP_INTERLEAVE_NONE,
            CU_TENSOR_MAP_SWIZZLE_128B, CU_TENSOR_MAP_L2_PROMOTION_L2_128B, CU_TENSOR_MAP_FLOAT_OOB_FILL_NONE);
    }
    {
        cuuint64_t gd[2] = {2048, NT}, gs[1] = {8192};
        cuuint32_t es[2] = {1, 1}, bx[2] = {16, NT};
        enc(&tm_mail, CU_TENSOR_MAP_DATA_TYPE_UINT32, 2, ((Scratch*)scratch)->mail, gd, gs, bx, es, CU_TENSOR_MAP_INTERLEAVE_NONE,
            CU_TENSOR_MAP_SWIZZLE_NONE, CU_TENSOR_MAP_L2_PROMOTION_NONE, CU_TENSOR_MAP_FLOAT_OOB_FILL_NONE);
    }
    mk(&tm_ms, scratch, 256, 32, 16, CU_TENSOR_MAP_SWIZZLE_NONE, CU_TENSOR_MAP_L2_PROMOTION_NONE);
    mk(&tm_x, d_in[0], NN, 64, TILE, CU_TENSOR_MAP_SWIZZLE_128B, CU_TENSOR_MAP_L2_PROMOTION_L2_128B);
    mk(&tm_ot, d_out, NN, 64, TILE, CU_TENSOR_MAP_SWIZZLE_128B, CU_TENSOR_MAP_L2_PROMOTION_NONE);
    mk(&tm_o256, d_out, NN, 8, PBOX, CU_TENSOR_MAP_SWIZZLE_NONE, CU_TENSOR_MAP_L2_PROMOTION_NONE);
    mk(&tm_o16, d_out, NN, 8, 16, CU_TENSOR_MAP_SWIZZLE_NONE, CU_TENSOR_MAP_L2_PROMOTION_NONE);
    exphormer_kernel<<<NCTA, 640, SMEM_BYTES>>>(
        (const uint4*)d_in[0], (const uint4*)d_in[2], (const uint4*)d_in[1], (const uint4*)d_in[7], (const uint4*)d_in[8], (const int*)d_in[3],
        (const int*)d_in[4], (Scratch*)scratch, (const uint4*)d_in[5], (const uint4*)d_in[9],
        tm_x, tm_wl, tm_wv, tm_m, tm_ms, tm_mail, tm_ot, tm_o256, tm_o16);
}
```

```cpp
#include <cuda_runtime.h>
#include <cuda_bf16.h>
#include <cuda.h>
#include <stdint.h>

namespace {

constexpr int NN = 10000, NE = 160000, NEE = 40000;
constexpr int TILE = 80, NT = 125, NCTA = 128, NG = 625, EPC = 1280;
constexpr int CELL = 32;
constexpr int QCAP = 192;
constexpr int OVCAP = EPC + NT * CELL;
#define XD0 700
#define XD1 1100
#define XD2 1900
#define REG_W 104
#define REG_H 64
#define KH 1
#define POLLNS 0
#define STPRE 4
#define G0POS 1
#define G1POS 1
#define LA 3
#define ED0 0
#define VRS 0
#define PACE 720
#define PSLEEP 0
#define PLACE_AT 1
#define MAP 4
#define SKIPLAST 1
#define VK 4
constexpr unsigned DUMMY2 = NN | (NN << 16);

constexpr unsigned SB0 = 1024;
constexpr unsigned sb = SB0;
constexpr int OFF_S = 0;
constexpr int OFF_R = 163840;
constexpr int OFF_BAR = OFF_R;
constexpr int OFF_MISC = OFF_R + 256;
constexpr int OFF_DIS = OFF_R + 320;
constexpr int OFF_PROF = OFF_R + 512;
constexpr int OFF_EIDX = OFF_R + 1024;
constexpr int OFF_ALPHA = OFF_R + 1024;
constexpr int OFF_STG = OFF_R + 3072;
constexpr int OFF_CNT1 = OFF_R + 2560;
constexpr int OFF_CNT2 = OFF_R + 3072;
constexpr int OFF_MAIL = OFF_R + 5760;
constexpr int OFF_IMG = OFF_MAIL + 9216;
constexpr int OFF_T = OFF_R + 27648;
constexpr int SMEM_BYTES = OFF_T + 40960;
static_assert(SMEM_BYTES <= 232448 && OFF_T % 1024 == 0 && OFF_STG + 3 * 8192 == OFF_T && OFF_IMG + 10752 <= OFF_T, "smem");
#define bar_fill (sb + OFF_BAR)
#define bar_t (sb + OFF_BAR + 8)
#define bar_mail (sb + OFF_BAR + 16)
#define bar_c (sb + OFF_BAR + 24)
#define bar_rd (sb + OFF_BAR + 32)
#define bar_go (sb + OFF_BAR + 112)
#define bar_p (sb + OFF_BAR + 216)
#define bar_full (sb + OFF_BAR + 120)
constexpr int LSTR = (NG + 48) * 32;

struct __align__(256) Scratch {
    uint4 mimg[8192];
    uint4 hs[32 * NN];
    uint4 mail[2 * NT * 512];
    uint4 lists[3 * LSTR];
    uint2 ovfn[NCTA];
    unsigned bar[5 * 64];
    unsigned ovf[NCTA * OVCAP];
};
__device__ Scratch g_scratch;
#define STAMPT(th, i)
#define CLK0(th)
#define CLK1(th, i)
#define STAMP(i) STAMPT(64, i)
#define STAMP2(i) STAMPT(416, i)

extern __shared__ __align__(1024) unsigned char smem_raw[];
__device__ __forceinline__ void bar_arrive(unsigned* p) {
    asm volatile("red.release.gpu.global.add.u32 [%0],1;" ::"l"(p) : "memory");
}
__device__ __forceinline__ void bar_arrive_relaxed(unsigned* p) {
    asm volatile("red.relaxed.gpu.global.add.u32 [%0],1;" ::"l"(p) : "memory");
}
__device__ __forceinline__ void bar_poll(const Scratch* sc, int i) {
    unsigned v, target;
    int lim = 0;
    asm volatile("ld.shared.u32 %0,[%1];" : "=r"(target) : "r"(sb + OFF_MISC + 32 + 4 * i) : "memory");
    while (true) {
        asm volatile("ld.acquire.gpu.global.u32 %0,[%1];" : "=r"(v) : "l"(&sc->bar[i * 64]) : "memory");
        if ((int)(v - target) >= 0) break;
        if (++lim > (1 << 22)) __trap();
        if (POLLNS) __nanosleep(POLLNS);
    }
}
__device__ __forceinline__ unsigned bar_poll2(const unsigned* p, unsigned target) {
    unsigned long long v;
    int lim = 0;
    do {
        asm volatile("ld.acquire.gpu.global.u64 %0,[%1];" : "=l"(v) : "l"(p) : "memory");
        if (++lim > (1 << 22)) __trap();
    } while ((int)((unsigned)v - target) < 0);
    unsigned f = (unsigned)(v >> 32);
    return (f & ~3u) == target ? f & 3 : 0;
}
__device__ __noinline__ void raise_flag(unsigned* p, unsigned target, unsigned bit) {
    unsigned old = atomicCAS(p, 0, 0), seen;
    do {
        seen = old;
        old = atomicCAS(p, seen, ((seen & ~3u) == target ? seen : target) | bit);
    } while (old != seen);
}
__device__ __forceinline__ void mbar_wait(unsigned a) {
    asm volatile("{.reg .pred p; .reg .u32 n;\n"
                 "mov.u32 n,0x400000;\n"
                 "W: mbarrier.try_wait.parity.shared.b64 p,[%0],0;\n"
                 "add.u32 n,n,-1; setp.ne.and.u32 p,n,0,!p; @p bra W;}" ::"r"(a) : "memory");
}
__device__ __forceinline__ bool elect() {
    unsigned r;
    asm volatile("{.reg .pred p; elect.sync _|p,0xFFFFFFFF; selp.u32 %0,1,0,p;}" : "=r"(r));
    return r;
}
__device__ __forceinline__ uint4 ldg_na(const uint4* p) {
    uint4 v;
    asm volatile("ld.global.L1::no_allocate.v4.u32 {%0,%1,%2,%3},[%4];" : "=r"(v.x), "=r"(v.y), "=r"(v.z), "=r"(v.w) : "l"(p) : "memory");
    return v;
}
__device__ __forceinline__ uint4 lds128(unsigned a) {
    uint4 v;
    asm volatile("ld.shared.v4.u32 {%0,%1,%2,%3},[%4];" : "=r"(v.x), "=r"(v.y), "=r"(v.z), "=r"(v.w) : "r"(a) : "memory");
    return v;
}
__device__ __forceinline__ uint4 ldsm4(unsigned a) {
    uint4 v;
    asm volatile("ldmatrix.sync.aligned.m8n8.x4.shared.b16 {%0,%1,%2,%3},[%4];" : "=r"(v.x), "=r"(v.y), "=r"(v.z), "=r"(v.w) : "r"(a) : "memory");
    return v;
}
__device__ __forceinline__ void sts128(unsigned a, uint4 v) {
    asm volatile("st.shared.v4.u32 [%0],{%1,%2,%3,%4};" ::"r"(a), "r"(v.x), "r"(v.y), "r"(v.z), "r"(v.w) : "memory");
}
__device__ __forceinline__ void sts32(unsigned a, unsigned v) { asm volatile("st.shared.u32 [%0],%1;" ::"r"(a), "r"(v) : "memory"); }
__device__ __forceinline__ unsigned lds32(unsigned a) { unsigned v; asm volatile("ld.shared.u32 %0,[%1];" : "=r"(v) : "r"(a) : "memory"); return v; }
__device__ __forceinline__ unsigned atoms_add(unsigned a, unsigned k) { unsigned v; asm volatile("atom.shared.add.u32 %0,[%1],%2;" : "=r"(v) : "r"(a), "r"(k) : "memory"); return v; }
__device__ __forceinline__ unsigned bitsel(unsigned a, unsigned b, unsigned m) { unsigned r; asm("lop3.b32 %0,%1,%2,%3,0xE4;" : "=r"(r) : "r"(a), "r"(b), "r"(m)); return r; }
__device__ __forceinline__ unsigned atoms_inc(unsigned a) { unsigned v; asm volatile("atom.shared.add.u32 %0,[%1],1;" : "=r"(v) : "r"(a) : "memory"); return v; }
__device__ __forceinline__ float blo(unsigned v) { return __uint_as_float(v << 16); }
__device__ __forceinline__ float bhi(unsigned v) { return __uint_as_float(v & 0xFFFF0000u); }
__device__ __forceinline__ float blo_v(unsigned v) { float r; asm volatile("shl.b32 %0,%1,16;" : "=f"(r) : "r"(v)); return r; }
__device__ __forceinline__ float bhi_v(unsigned v) { float r; asm volatile("and.b32 %0,%1,0xFFFF0000;" : "=f"(r) : "r"(v)); return r; }
__device__ __forceinline__ unsigned pack2(float lo, float hi) { unsigned r; asm("cvt.rn.bf16x2.f32 %0,%1,%2;" : "=r"(r) : "f"(hi), "f"(lo)); return r; }

__device__ __forceinline__ void mma16816(float* d, unsigned a0, unsigned a1, unsigned a2, unsigned a3, unsigned b0, unsigned b1) {
    asm volatile("mma.sync.aligned.m16n8k16.row.col.f32.bf16.bf16.f32 {%0,%1,%2,%3},{%4,%5,%6,%7},{%8,%9},{%0,%1,%2,%3};"
                 : "+f"(d[0]), "+f"(d[1]), "+f"(d[2]), "+f"(d[3]) : "r"(a0), "r"(a1), "r"(a2), "r"(a3), "r"(b0), "r"(b1));
}
#define R10(b) "+f"(d[b + 0]), "+f"(d[b + 1]), "+f"(d[b + 2]), "+f"(d[b + 3]), "+f"(d[b + 4]), "+f"(d[b + 5]), "+f"(d[b + 6]), "+f"(d[b + 7]), "+f"(d[b + 8]), "+f"(d[b + 9])
__device__ __forceinline__ void wg80(float* d, unsigned da, unsigned db, int sc) {
    asm volatile("{.reg .pred p; .reg .b64 a, b; setp.ne.b32 p,%42,0; mov.b64 a,{%40,%43}; mov.b64 b,{%41,%43};\n"
                 "wgmma.mma_async.sync.aligned.m64n80k16.f32.bf16.bf16 "
                 "{%0,%1,%2,%3,%4,%5,%6,%7,%8,%9,%10,%11,%12,%13,%14,%15,%16,%17,%18,%19,%20,%21,%22,%23,%24,%25,%26,%27,%28,%29,%30,%31,%32,%33,%34,%35,%36,%37,%38,%39},"
                 "a,b,p,1,1,1,0;}"
                 : R10(0), R10(10), R10(20), R10(30) : "r"(da), "r"(db), "r"(sc), "r"(0x40000040));
}
__device__ __forceinline__ void wg80r(float* d, const uint4& a, unsigned db) {
    asm volatile("{.reg .b64 b; mov.b64 b,{%44,%45};\n"
                 "wgmma.mma_async.sync.aligned.m64n80k16.f32.bf16.bf16 "
                 "{%0,%1,%2,%3,%4,%5,%6,%7,%8,%9,%10,%11,%12,%13,%14,%15,%16,%17,%18,%19,%20,%21,%22,%23,%24,%25,%26,%27,%28,%29,%30,%31,%32,%33,%34,%35,%36,%37,%38,%39},"
                 "{%40,%41,%42,%43},b,1,1,1,0;}"
                 : R10(0), R10(10), R10(20), R10(30) : "r"(a.x), "r"(a.y), "r"(a.z), "r"(a.w), "r"(db), "r"(0x40000040));
}
__device__ __forceinline__ void wg_fence() { asm volatile("wgmma.fence.sync.aligned;" ::: "memory"); }
__device__ __forceinline__ void wg_commit() { asm volatile("wgmma.commit_group.sync.aligned;" ::: "memory"); }
template <int N> __device__ __forceinline__ void wg_wait() { asm volatile("wgmma.wait_group.sync.aligned %0;" ::"n"(N) : "memory"); }
__device__ __forceinline__ void bulk_g2s(unsigned dst, const void* src, unsigned bytes, unsigned bar) {
    asm volatile("cp.async.bulk.shared::cluster.global.mbarrier::complete_tx::bytes [%0],[%1],%2,[%3];" ::"r"(dst), "l"(src), "r"(bytes), "r"(bar) : "memory");
}
__device__ __forceinline__ void fence_async_smem() { asm volatile("fence.proxy.async.shared::cta;" ::: "memory"); }
__device__ __forceinline__ void fence_async_gmem() { asm volatile("fence.proxy.async.global;" ::: "memory"); }

__host__ __device__ constexpr unsigned h2c(int v) { return (0x6400u | v) | ((0x6400u | v) << 16); }
__device__ __forceinline__ unsigned row_lo(unsigned a) { unsigned r; asm volatile("dp2a.lo.u32.u32 %0,%1,0x10000010,0;" : "=r"(r) : "r"(a)); return r; }
__device__ __forceinline__ unsigned row_hi(unsigned a) { unsigned r; asm volatile("dp2a.hi.u32.u32 %0,%1,0x10000010,0;" : "=r"(r) : "r"(a)); return r; }
__device__ __forceinline__ uint4 ldsm4t(unsigned addr) {
    uint4 v;
    asm volatile("ldmatrix.sync.aligned.m8n8.x4.trans.shared.b16 {%0,%1,%2,%3},[%4];" : "=r"(v.x), "=r"(v.y), "=r"(v.z), "=r"(v.w) : "r"(addr));
    return v;
}
__device__ __forceinline__ void sched_fence(unsigned zero) { asm volatile("{.reg .pred p; setp.ne.u32 p,%0,0; @p exit;}" ::"r"(zero)); }
__device__ __forceinline__ uint4 p3_sel(int i, unsigned sA, unsigned sB) {
    uint4 a;
    asm volatile("set.le.f16x2.f16x2 %0,%4,%6;\n sub.sat.f16x2 %2,%7,%4;\n set.le.f16x2.f16x2 %1,%5,%6;\n sub.sat.f16x2 %3,%7,%5;"
                 : "=r"(a.x), "=r"(a.y), "=r"(a.z), "=r"(a.w) : "r"(sA), "r"(sB), "r"(h2c(2 * i)), "r"(h2c(2 * i + 2)));
    return a;
}
__device__ __forceinline__ void p3_step(float* acc0, float* acc1, unsigned row, int s, unsigned sA, unsigned sB) {
    const uint4 v = ldsm4t(sb + OFF_S + row), a0 = p3_sel(2 * s, sA, sB), a1 = p3_sel(2 * s + 1, sA, sB);
    mma16816(acc0, a0.x, a0.y, a0.z, a0.w, v.x, v.y);
    mma16816(acc1, a1.x, a1.y, a1.z, a1.w, v.z, v.w);
}
__device__ __noinline__ float4 p3_overflow(const Scratch* sc, int grp, unsigned sS) {
    const unsigned tag = lds32(sb + OFF_MISC + 48);
    int lane = threadIdx.x & 31, g = lane >> 2, t = lane & 3;
    float4 r = make_float4(0.f, 0.f, 0.f, 0.f);
    for (int c = 0; c < NT; c++) {
        const uint2 tn = __ldcg(&sc->ovfn[c]);
        const int n = tn.x == tag ? (int)tn.y : 0;
        for (int i0 = 0; i0 < n; i0 += 32) {
            unsigned e = (i0 + lane < n) ? __ldcg(&sc->ovf[c * OVCAP + i0 + lane]) : 0xFFFFFFFFu;
            unsigned m = __ballot_sync(~0u, (int)(e >> 18) == grp);
            while (m) {
                int j = __ffs(m) - 1;
                m &= m - 1;
                unsigned ee = __shfl_sync(~0u, e, j);
                int row = (ee >> 14) & 15;
                row ^= row >> 3;
                unsigned v = lds32(sS + (ee & 0x3FFF) * 16 + t * 4);
                if ((row >> 1) == g) {
                    if (!(row & 1)) { r.x += blo(v); r.y += bhi(v); } else { r.z += blo(v); r.w += bhi(v); }
                }
            }
        }
    }
    const float k = 1.f / 128.f;
    r.x *= k; r.y *= k; r.z *= k; r.w *= k;
    return r;
}
__device__ __forceinline__ void unpack8(float* f, uint4 v) {
    f[0] = blo(v.x); f[1] = bhi(v.x); f[2] = blo(v.y); f[3] = bhi(v.y); f[4] = blo(v.z); f[5] = bhi(v.z); f[6] = blo(v.w); f[7] = bhi(v.w);
}
__device__ __forceinline__ void vec_mat(float* o, const float* v, const uint4* __restrict__ W, int lane) {
    for (int k = 0; k < 8; k++) o[k] = 0.f;
    for (int l = 0; l < 32; l++) {
#pragma unroll
        for (int i = 0; i < 8; i++) {
            float a = __shfl_sync(~0u, v[i], l), wr[8];
            unpack8(wr, W[(l * 8 + i) * 32 + lane]);
#pragma unroll
            for (int k = 0; k < 8; k++) o[k] = fmaf(a, wr[k], o[k]);
        }
    }
}
__device__ __noinline__ uint4 attn_generic(int node, const uint4* __restrict__ x, const int* __restrict__ esrc, const int* __restrict__ edst,
                                           const uint4* __restrict__ wq, const uint4* __restrict__ wk, const uint4* __restrict__ wv) {
    int lane = threadIdx.x & 31;
    float xr[8], q[8], y[8], o[8];
    unpack8(xr, x[node * 32 + lane]);
    vec_mat(q, xr, wq, lane);
    for (int l = 0; l < 32; l++) {
#pragma unroll
        for (int i = 0; i < 8; i++) {
            float wr[8], p = 0.f;
            unpack8(wr, wk[(l * 8 + i) * 32 + lane]);
#pragma unroll
            for (int k = 0; k < 8; k++) p = fmaf(q[k], wr[k], p);
            for (int k = 16; k; k >>= 1) p += __shfl_xor_sync(~0u, p, k);
            if (lane == l) y[i] = p;
        }
    }
    for (int k = 0; k < 8; k++) o[k] = 0.f;
    float den = 0.f;
    for (int i0 = 0; i0 < NEE; i0 += 32) {
        unsigned m = __ballot_sync(~0u, edst[i0 + lane] == node);
        while (m) {
            int j = __ffs(m) - 1;
            m &= m - 1;
            float gq[8], p = 0.f;
            unpack8(gq, x[esrc[i0 + j] * 32 + lane]);
#pragma unroll
            for (int k = 0; k < 8; k++) p = fmaf(y[k], gq[k], p);
            for (int k = 16; k; k >>= 1) p += __shfl_xor_sync(~0u, p, k);
            float ex = __expf(p * 0.0625f);
            den += ex;
#pragma unroll
            for (int k = 0; k < 8; k++) o[k] = fmaf(ex, gq[k], o[k]);
        }
    }
    float inv = 1.f / (den + 1e-9f);
    for (int k = 0; k < 8; k++) o[k] *= inv;
    vec_mat(q, o, wv, lane);
    return make_uint4(pack2(q[0], q[1]), pack2(q[2], q[3]), pack2(q[4], q[5]), pack2(q[6], q[7]));
}

__device__ __forceinline__ unsigned hfma2(unsigned a, unsigned b, unsigned c) { unsigned r; asm("fma.rn.bf16x2 %0,%1,%2,%3;" : "=r"(r) : "r"(a), "r"(b), "r"(c)); return r; }
__device__ __forceinline__ unsigned hmul2(unsigned a, unsigned b) { unsigned r; asm("mul.rn.bf16x2 %0,%1,%2;" : "=r"(r) : "r"(a), "r"(b)); return r; }

__device__ __forceinline__ unsigned tile_addr(int n, unsigned chunk) { return sb + OFF_T + (chunk >> 3) * 10240 + n * 128 + (((chunk ^ n) & 7) << 4); }
__device__ __forceinline__ void attn_scores(float* v, bool mine, bool par, const uint4* gv, unsigned yaddr) {
    const uint4 y = ldsm4(yaddr);
    float c[4] = {0, 0, 0, 0}, e[4] = {0, 0, 0, 0};
    mma16816(c, gv[0].x, gv[0].y, gv[0].z, gv[0].w, y.x, y.y);
    mma16816(e, gv[2].x, gv[2].y, gv[2].z, gv[2].w, y.x, y.y);
    mma16816(c, gv[1].x, gv[1].y, gv[1].z, gv[1].w, y.z, y.w);
    mma16816(e, gv[3].x, gv[3].y, gv[3].z, gv[3].w, y.z, y.w);
    if (mine) { v[0] = par ? c[1] : c[0]; v[1] = par ? c[3] : c[2]; v[2] = par ? e[1] : e[0]; v[3] = par ? e[3] : e[2]; }
}
__device__ __forceinline__ void attn_softmax(const float* v, const float* u, unsigned lane, unsigned aladdr) {
    const bool hA = lane & 4, hB = lane & 8, hC = lane & 16;
    float a[4];
#pragma unroll
    for (int e = 0; e < 4; e++) a[e] = (hA ? u[e] : v[e]) + __shfl_xor_sync(~0u, hA ? v[e] : u[e], 4);
    float b0 = (hB ? a[1] : a[0]) + __shfl_xor_sync(~0u, hB ? a[0] : a[1], 9);
    float b1 = (hB ? a[3] : a[2]) + __shfl_xor_sync(~0u, hB ? a[2] : a[3], 9);
    float sc = (hC ? b1 : b0) + __shfl_xor_sync(~0u, hC ? b0 : b1, 18);
    float ex, inv;
    asm("ex2.approx.ftz.f32 %0,%1;" : "=f"(ex) : "f"(sc));
    float den = ex + __shfl_xor_sync(~0u, ex, 9);
    den += __shfl_xor_sync(~0u, den, 18);
    asm("rcp.approx.ftz.f32 %0,%1;" : "=f"(inv) : "f"(den + 1e-9f));
    sts32(aladdr, pack2(ex * inv, ex * inv));
    __syncwarp();
}
__device__ __forceinline__ void attn_mix(const uint4* gv, const uint4& a, unsigned oaddr) {
    const unsigned o0 = hfma2(a.w, gv[2].y, hfma2(a.z, gv[2].x, hfma2(a.y, gv[0].y, hmul2(a.x, gv[0].x))));
    const unsigned o1 = hfma2(a.w, gv[2].w, hfma2(a.z, gv[2].z, hfma2(a.y, gv[0].w, hmul2(a.x, gv[0].z))));
    const unsigned o2 = hfma2(a.w, gv[3].y, hfma2(a.z, gv[3].x, hfma2(a.y, gv[1].y, hmul2(a.x, gv[1].x))));
    const unsigned o3 = hfma2(a.w, gv[3].w, hfma2(a.z, gv[3].z, hfma2(a.y, gv[1].w, hmul2(a.x, gv[1].z))));
    asm volatile("stmatrix.sync.aligned.m8n8.x4.shared.b16 [%0],{%1,%2,%3,%4};" ::"r"(oaddr), "r"(o0), "r"(o1), "r"(o2), "r"(o3) : "memory");
}
__device__ __forceinline__ void pack_acc(unsigned* pk, const float* d) {
#pragma unroll
    for (int j = 0; j < 20; j++) pk[j] = pack2(d[2 * j], d[2 * j + 1]);
}
__device__ __forceinline__ void acc_to_tile(const unsigned* pk, int w, int lane) {
    const unsigned a = sb + OFF_T + (w >> 2) * 10240 + (lane >> 4) * 1024 + (lane & 7) * 128 + (((2 * (w & 3) + ((lane >> 3) & 1)) ^ (lane & 7)) << 4);
#pragma unroll
    for (int j = 0; j < 5; j++)
        asm volatile("stmatrix.sync.aligned.m8n8.x4.trans.shared.b16 [%0],{%1,%2,%3,%4};" ::"r"(a + j * 2048), "r"(pk[4 * j]), "r"(pk[4 * j + 1]), "r"(pk[4 * j + 2]), "r"(pk[4 * j + 3]) : "memory");
}
__device__ __forceinline__ unsigned movm(unsigned a) { unsigned d; asm volatile("movmatrix.sync.aligned.m8n8.trans.b16 %0,%1;" : "=r"(d) : "r"(a)); return d; }
__device__ __forceinline__ void tma_load2d(unsigned dst, const CUtensorMap* tm, int c0, int c1, unsigned bar) {
    asm volatile("cp.async.bulk.tensor.2d.shared::cluster.global.mbarrier::complete_tx::bytes [%0],[%1,{%3,%4}],[%2];"
                 ::"r"(dst), "l"(tm), "r"(bar), "r"(c0), "r"(c1) : "memory");
}
__device__ __forceinline__ void tma_load3d(unsigned dst, const CUtensorMap* tm, int row, unsigned bar) {
    asm volatile("cp.async.bulk.tensor.3d.shared::cluster.global.mbarrier::complete_tx::bytes [%0],[%1,{%4,%3,%4}],[%2];"
                 ::"r"(dst), "l"(tm), "r"(bar), "r"(row), "r"(0) : "memory");
}
__device__ __forceinline__ void cp16(unsigned dst, const void* src) { asm volatile("cp.async.cg.shared.global [%0],[%1],16;" ::"r"(dst), "l"(src) : "memory"); }
__device__ __forceinline__ void cp_commit() { asm volatile("cp.async.commit_group;" ::: "memory"); }
template <int N> __device__ __forceinline__ void cp_wait() { asm volatile("cp.async.wait_group %0;" ::"n"(N) : "memory"); }
__device__ __forceinline__ void nb_sync_id(int id, int n) { asm volatile("bar.sync %0,%1;" ::"r"(id), "r"(n) : "memory"); }
__device__ __forceinline__ void nb_arrive_id(int id, int n) { asm volatile("bar.arrive %0,%1;" ::"r"(id), "r"(n) : "memory"); }
template <int ID, int N> __device__ __forceinline__ void nb_sync() { asm volatile("bar.sync %0,%1;" ::"n"(ID), "n"(N) : "memory"); }
template <int ID, int N> __device__ __forceinline__ void nb_arrive() { asm volatile("bar.arrive %0,%1;" ::"n"(ID), "n"(N) : "memory"); }
__device__ __forceinline__ void mbar_init(unsigned a, int n) { asm volatile("mbarrier.init.shared.b64 [%0],%1;" ::"r"(a), "r"(n) : "memory"); }
__device__ __forceinline__ void mbar_expect(unsigned a, int n) { asm volatile("mbarrier.arrive.expect_tx.shared.b64 _,[%0],%1;" ::"r"(a), "r"(n) : "memory"); }
__device__ __forceinline__ void mbar_arrive(unsigned a) { asm volatile("mbarrier.arrive.shared.b64 _,[%0];" ::"r"(a) : "memory"); }

constexpr unsigned PADBIN = 2560;
__device__ __noinline__ void push_overflow(Scratch* sc, unsigned dst, unsigned src) {
    sc->ovf[blockIdx.x * OVCAP + atoms_inc(sb + OFF_MISC)] = (dst << 14) | src;
}
__device__ __forceinline__ void entry_overflow(Scratch* sc, unsigned e) {
    if (e < (PADBIN << 16)) push_overflow(sc, blockIdx.x * TILE + ((e >> 21) & ~3u) + ((e >> 18) & 3), e & 0xFFFF);
}
__device__ __forceinline__ unsigned rank_addr(unsigned i) { return sb + OFF_IMG + 2560 + i * 4 + (i >= 384 ? 4096 - 1536 : 0); }
__device__ __forceinline__ void place(unsigned e, unsigned r, unsigned w) {
    const unsigned p = r + (w >> 16), t2 = r * 0x801 + w;
    const unsigned tt = p < 32 ? p * 0x808 : t2, bin = p < 32 ? e >> 16 : bitsel(t2 << 2, e >> 16, 0x1070);
    asm volatile("{.reg .pred p; setp.lt.u32 p,%2,%3; @p st.shared.u16 [%0],%1;}"
                 ::"r"(sb + OFF_IMG + bitsel(tt >> 4, bin, 0x18E)), "h"((unsigned short)e), "r"(e), "n"(PADBIN << 16) : "memory");
}
__device__ __forceinline__ void place4(unsigned i) {
    uint4 e = lds128(sb + OFF_MAIL + i * 16);
    const unsigned r = lds32(rank_addr(i));
    e.w &= 0x7FFFFFFFu;
    const uint4 w = make_uint4(lds32(sb + OFF_CNT2 + (e.x >> 16)), lds32(sb + OFF_CNT2 + (e.y >> 16)), lds32(sb + OFF_CNT2 + (e.z >> 16)), lds32(sb + OFF_CNT2 + (e.w >> 16)));
    place(e.x, r & 255, w.x); place(e.y, (r >> 8) & 255, w.y); place(e.z, (r >> 16) & 255, w.z); place(e.w, r >> 24, w.w);
}
__device__ __noinline__ void place_slow(Scratch* sc, unsigned ht, unsigned broken) {
    for (unsigned i = ht; i < 576 * 4; i += 96) {
        const unsigned e = lds32(sb + OFF_MAIL + i * 4) & 0x7FFFFFFFu, w = lds32(sb + OFF_CNT2 + (e >> 16));
        const unsigned r = (lds32(rank_addr(i >> 2)) >> (8 * (i & 3))) & 255, q = (r + w) & 0xFF;
        if (r + (w >> 16) < 32) place(e, r, w);
        else if (broken >> (e >> 25) & 1) entry_overflow(sc, e);
        else if (e < (PADBIN << 16))
            asm volatile("st.shared.u16 [%0],%1;" ::"r"(sb + OFF_IMG + (q < 192 ? 8192 : 4096) + (e >> 25) * 512 + (q & 3) * 128 + (q & 28) * 4 + (q >> 5) * 2), "h"((unsigned short)e) : "memory");
    }
}
__device__ __noinline__ void tail_overflow(Scratch* sc, unsigned mask, unsigned ht) {
    for (int i = 0; i < 6 * 16; i++)
        if (mask >> (i >> 4) & 1)
            entry_overflow(sc, __ldcg((const unsigned*)(sc->mail + ((NT + blockIdx.x) * 512 + ((ht + (i >> 4) * 96) & ~3u))) + (i & 15)));
}
__device__ __forceinline__ void bulk_s2g(void* dst, unsigned src, unsigned bytes) {
    asm volatile("cp.async.bulk.global.shared::cta.bulk_group [%0],[%1],%2;" ::"l"(dst), "r"(src), "r"(bytes) : "memory");
}
__device__ __forceinline__ void tma_reduce(const CUtensorMap* tm, unsigned src, int c0, int c1) {
    asm volatile("cp.reduce.async.bulk.tensor.2d.global.shared::cta.add.tile.bulk_group [%0,{%2,%3}],[%1];" ::"l"(tm), "r"(src), "r"(c0), "r"(c1) : "memory");
}
#define EV(id) nb_arrive<id, 544>()
#define WAIT_EV(id) do { __syncwarp(); nb_sync<id, 544>(); } while (0)

__global__ void __launch_bounds__(640, 1)
exphormer_kernel(const uint4* __restrict__ x, const uint4* __restrict__ dst4, const uint4* __restrict__ src4,
                 const uint4* __restrict__ wq, const uint4* __restrict__ wk, const int* __restrict__ esrc,
                 const int* __restrict__ edst, Scratch* __restrict__ sc, const uint4* __restrict__ dis, const uint4* __restrict__ wv,
                 const __grid_constant__ CUtensorMap tm_x, const __grid_constant__ CUtensorMap tm_wl, const __grid_constant__ CUtensorMap tm_wv,
                 const __grid_constant__ CUtensorMap tm_m, const __grid_constant__ CUtensorMap tm_ms,
                 const __grid_constant__ CUtensorMap tm_mail, const __grid_constant__ CUtensorMap tm_ot, const __grid_constant__ CUtensorMap tm_o256, const __grid_constant__ CUtensorMap tm_o192) {
    const unsigned tid = threadIdx.x, lane = tid & 31, g = lane >> 2, t = lane & 3;
    const unsigned b = blockIdx.x;
    const bool rowcta = b < NT;
    const int slice = (b >> 4) * 4 + (b & 3), range = (b >> 2) & 3;
    const int g0 = (range * NG) >> 2, g1 = ((range + 1) * NG) >> 2;
    STAMP(0);

    if (tid >= 512) {
    asm volatile("setmaxnreg.dec.sync.aligned.u32 %0;" ::"n"(REG_H));
    if (tid >= 544) {
        const unsigned ht = tid - 544;
        if (ht < 32) {
            if (lane == 0) asm volatile("prefetch.tensormap [%0];" ::"l"(&tm_mail) : "memory");
            __syncwarp();
            nb_sync<13, 160>();
            nb_sync<2, 352>();
            if (rowcta) {
                const uint4 c = lds128(sb + OFF_CNT1 + lane * 16);
                const unsigned cc[4] = {c.x, c.y, c.z, c.w};
#pragma unroll
                for (int i = 0; i < 4; i++)
                    if (cc[i] > 16) asm volatile("red.shared.or.b32 [%0],0x80000000;" ::"r"(sb + OFF_MAIL + (lane * 4 + i) * 64 + 60) : "memory");
                fence_async_smem();
                __syncwarp();
                if (elect())
                    asm volatile("cp.async.bulk.tensor.2d.global.shared::cta.bulk_group [%0,{%2,%3}],[%1];" ::"l"(&tm_mail), "r"(sb + OFF_MAIL), "r"(b * 16), "r"(0) : "memory");
                for (int i = 0; i < 4; i++)
                    if (lds32(sb + OFF_CNT1 + lane * 16 + i * 4) > 16) bulk_s2g(sc->mail + ((NT + lane * 4 + i) * 512 + b * 4), sb + OFF_IMG + (lane * 4 + i) * 64, 64);
                asm volatile("cp.async.bulk.commit_group;" ::: "memory");
                asm volatile("cp.async.bulk.wait_group 0;" ::: "memory");
                fence_async_gmem();
                __syncwarp();
            }
            if (rowcta) nb_arrive<1, 96>();
            if (elect()) {
                bar_arrive_relaxed(&sc->bar[0]);
                STAMPT(544, 47);
                if (rowcta) {
                    bar_poll(sc, 0);
                    fence_async_gmem();
                    mbar_expect(bar_mail, 8000);
                    bulk_g2s(sb + OFF_MAIL, sc->mail + b * 512, 8000, bar_mail);
                }
            }
            __syncwarp();
        } else if (ht < 64) {
            if (lane == 0) asm volatile("prefetch.tensormap [%0];" ::"l"(&tm_ms) : "memory");
            nb_sync<14, 192>();
            if (elect()) {
                asm volatile("cp.async.bulk.tensor.2d.global.shared::cta.bulk_group [%0,{%2,%3}],[%1];" ::"l"(&tm_ms), "r"(sb + OFF_MAIL + 8064), "r"((b & 7) * 32), "r"((b >> 3) * 16) : "memory");
                asm volatile("cp.async.bulk.commit_group;" ::: "memory");
                asm volatile("cp.async.bulk.wait_group 0;" ::: "memory");
                fence_async_gmem();
                bar_arrive_relaxed(&sc->bar[3 * 64]);
                STAMPT(576, 46);
            }
            __syncwarp();
        } else {
            if (lane < 5) {
                unsigned epoch;
                asm volatile("ld.relaxed.gpu.global.u32 %0,[%1];" : "=r"(epoch) : "l"(&sc->bar[lane * 64]) : "memory");
                sts32(sb + OFF_MISC + 32 + lane * 4, (epoch & ~(NCTA - 1)) + NCTA);
            }
            __syncwarp();
            nb_arrive<14, 192>();
            nb_arrive<15, 64>();
            nb_arrive<13, 160>();
        }
        if (rowcta) {
            if (ht >= 32) {
                nb_sync<1, 96>();
                const unsigned pad = (PADBIN + 4 * lane) << 16, h2 = ht - 32;
                sts128(sb + OFF_MAIL + 8000 + h2 * 16, make_uint4(pad, pad, pad, pad));
                if (h2 < 12) sts128(sb + OFF_MAIL + 9024 + h2 * 16, make_uint4(pad, pad, pad, pad));
#pragma unroll
                for (int k = 0; k < 9; k++) {
                    const unsigned dm = k < 3 ? DUMMY2 + (lane & 7) * 0x10001u : DUMMY2;
                    if (k % 3 < 2 || h2 < 32) sts128(sb + OFF_IMG + (k / 3) * 4096 + (k % 3) * 1024 + h2 * 16, make_uint4(dm, dm, dm, dm));
                }
            }
            nb_sync<13, 96>();
            mbar_wait(bar_mail);
            STAMPT(576, 16);
            uint4 e[6], h[6];
            unsigned flagged = 0, late = 0, longg = 0;
#pragma unroll
            for (int k = 0; k < 6; k++) e[k] = lds128(sb + OFF_MAIL + (ht + k * 96) * 16);
#pragma unroll
            for (int k = 0; k < 6; k++) { flagged |= (e[k].w >> 31) << k; e[k].w &= 0x7FFFFFFFu; }
            while (flagged) {
                const unsigned f = __ffs(flagged) - 1, k = atoms_add(sb + OFF_MISC + 4, 4);
                const uint4* sp = sc->mail + ((NT + b) * 512 + ((ht + f * 96) & ~3u));
                flagged &= flagged - 1;
                if (k < 76) {
#pragma unroll
                    for (int j = 0; j < 4; j++) cp16(sb + OFF_MAIL + 8000 + (k + j) * 16, sp + j);
                } else {
                    late |= 1u << f;
                }
            }
            cp_commit();
            __syncwarp();
#pragma unroll
            for (int k = 0; k < 6; k++) {
                if (k == 5) { cp_wait<0>(); nb_sync<1, 96>(); if (ht >= 20) e[5] = lds128(sb + OFF_MAIL + (ht + 480) * 16); }
                h[k] = make_uint4(atoms_inc(sb + OFF_CNT2 + (e[k].x >> 16)), atoms_inc(sb + OFF_CNT2 + (e[k].y >> 16)),
                                  atoms_inc(sb + OFF_CNT2 + (e[k].z >> 16)), atoms_inc(sb + OFF_CNT2 + (e[k].w >> 16)));
            }
#pragma unroll
            for (int k = 0; k < 6; k++)
                sts32(rank_addr(ht + k * 96), __byte_perm(__byte_perm(min(h[k].x, 255u), min(h[k].y, 255u), 0x0040), __byte_perm(min(h[k].z, 255u), min(h[k].w, 255u), 0x0040), 0x5410));
            nb_sync<1, 96>();
            STAMPT(576, 17);
            unsigned rare;
            {
                const bool sw = lane >= 16;
                const unsigned G0 = ht >> 5, G1 = min(G0 + 3, 4u);
                uint4 c[2];
                unsigned inc[2], st[2][4], lf[2], ex[2], xs[2], word[2], s2w[2], dp[2];
#pragma unroll
                for (int j = 0; j < 2; j++) c[j] = lds128(sb + OFF_CNT2 + (j ? G1 : G0) * 512 + lane * 16);
#pragma unroll
                for (int j = 0; j < 2; j++) dp[j] = lds32(sb + OFF_DIS + ((j ? G1 : G0) * 8 + g) * 4);
#pragma unroll
                for (int j = 0; j < 2; j++) { inc[j] = c[j].x + c[j].y + c[j].z + c[j].w; const unsigned u = __shfl_up_sync(~0u, inc[j], 8); if (lane >= 8) inc[j] += u; }
#pragma unroll
                for (int j = 0; j < 2; j++) { const unsigned u = __shfl_up_sync(~0u, inc[j], 16); if (sw) inc[j] += u; }
#pragma unroll
                for (int j = 0; j < 2; j++) {
                    const unsigned s2 = c[j].x + c[j].y;
                    st[j][0] = inc[j] - s2 - c[j].z - c[j].w; st[j][1] = st[j][0] + (sw ? c[j].y : c[j].x);
                    st[j][2] = st[j][0] + s2; st[j][3] = st[j][2] + (sw ? c[j].w : c[j].z);
                    const unsigned m0 = max(st[j][0], 32u), m1 = max(st[j][1], 32u), m2 = max(st[j][2], 32u), m3 = max(st[j][3], 32u), m4 = max(inc[j], 32u);
                    const unsigned Q = __reduce_add_sync(~0u, m4 - m0);
                    lf[j] = Q <= QCAP ? (m1 - m0) | (m2 - m1) << 8 | (m3 - m2) << 16 | (m4 - m3) << 24 : 0;
                    xs[j] = __reduce_add_sync(~0u, Q <= QCAP ? (m4 - m0) << (lane & 24) : 0);
                    if (Q > 64 && (j == 0 || ht < 64)) longg |= (Q <= QCAP ? 1u : 0x100u) << (j ? G1 : G0);
                    word[j] = min(st[j][0], 32u) | min(st[j][1], 32u) << 8 | min(st[j][2], 32u) << 16 | min(st[j][3], 32u) << 24;
                    ex[j] = lf[j];
                }
#pragma unroll
                for (int d = 1; d < 8; d <<= 1)
#pragma unroll
                    for (int j = 0; j < 2; j++) { const unsigned u = __shfl_up_sync(~0u, ex[j], d); if ((lane & 7) >= d) ex[j] += u; }
#pragma unroll
                for (int j = 0; j < 2; j++) {
                    const unsigned tot = __shfl_sync(~0u, ex[j], lane | 7);
                    s2w[j] = tot * 0x01010100u + (((xs[j] * 0x01010100u) >> (lane & 24)) & 255) * 0x01010101u;
                    const unsigned q0 = s2w[j] + ex[j] - lf[j];
                    unsigned w4[4];
#pragma unroll
                    for (int i = 0; i < 4; i++)
                        w4[i] = __byte_perm((((q0 >> (8 * i)) & 255) + 192 + st[j][i] - max(st[j][i], 32u)) * 0x801 + 0x400, min(st[j][i], 32u), 0x5410);
                    if (j == 0 || ht < 64)
                        sts128(sb + OFF_CNT2 + (j ? G1 : G0) * 512 + lane * 16, make_uint4(sw ? w4[1] : w4[0], sw ? w4[0] : w4[1], sw ? w4[3] : w4[2], sw ? w4[2] : w4[3]));
                }
                if (longg && lane == 0) asm volatile("red.shared.or.b32 [%0],%1;" ::"r"(sb + OFF_MISC + 8), "r"(longg) : "memory");
                asm volatile("{.reg .pred p; setp.ne.u32 p,%1,0; bar.red.popc.u32 %0,1,96,p;}" : "=r"(rare) : "r"(longg) : "memory");
                if (ht == 64) mbar_arrive(bar_p);
#pragma unroll
                for (int j = 0; j < 2; j++) {
                    const unsigned wa = __shfl_sync(~0u, word[j], (g >> 1) * 8 + 2 * t), wb = __shfl_sync(~0u, word[j], (g >> 1) * 8 + 2 * t + 1);
                    const unsigned w2 = s2w[j];
                    const unsigned d128 = hmul2(dp[j], 0x43004300u);
                    const unsigned ha = sb + OFF_IMG + 4096 + (j ? G1 : G0) * 512 + lane * 16;
                    if (j == 0 || ht < 64) {
                        asm volatile("st.shared.v2.u32 [%0],{%1,%2};" ::"r"(ha), "r"(__byte_perm(wa, wb, (g & 1) ? 0x7362 : 0x5140)),
                                     "r"(__byte_perm(w2, w2, (g & 1) ? 0x3322 : 0x1100) + 0x1C201C20u - t * 0x08080808u) : "memory");
                        sts32(ha + 8, __byte_perm(d128, d128, lane >= 16 ? 0x1032 : 0x3210));
                    }
                }
            }
            if (__builtin_expect(!rare, 1)) {
                if (ht >= 32) place4(480 + ht);
            } else {
                place_slow(sc, ht, lds32(sb + OFF_MISC + 8) >> 8);
                nb_sync<1, 96>();
                for (longg &= 255; longg; longg &= longg - 1)
                    asm volatile("red.shared.or.b32 [%0],0x80000000;" ::"r"(sb + OFF_IMG + 4096 + (__ffs(longg) - 1) * 512 + lane * 16 + 12) : "memory");
            }
            if (__builtin_expect(late, 0)) tail_overflow(sc, late, ht);
            __syncwarp();
            STAMPT(576, 4);
            if (ht < 32) nb_sync<13, 608>(); else nb_arrive<13, 608>();
            STAMPT(544, 18);
        }
        if (ht < 32 && elect()) {
            if (rowcta) {
                fence_async_smem();
                for (int c = 0; c < 3; c++) bulk_s2g(sc->lists + (c * LSTR + b * 160), sb + OFF_IMG + c * 4096, 2560);
                asm volatile("cp.async.bulk.commit_group;" ::: "memory");
                const unsigned novf = lds32(sb + OFF_MISC), bad = lds32(sb + OFF_MISC + 20);
                if (__builtin_expect(novf | bad, 0)) {
                    sc->ovfn[b] = make_uint2(lds32(sb + OFF_MISC + 48), novf);
                    raise_flag(&sc->bar[4 * 64 + 1], lds32(sb + OFF_MISC + 48), (novf ? 1 : 0) | (bad ? 2 : 0));
                    __threadfence();
                }
                asm volatile("cp.async.bulk.wait_group 0;" ::: "memory");
                fence_async_gmem();
            }
            bar_arrive_relaxed(&sc->bar[4 * 64]);
            STAMPT(544, 19);
            sts32(sb + OFF_MISC + 28, bar_poll2(&sc->bar[4 * 64], lds32(sb + OFF_MISC + 48)));
            mbar_arrive(bar_c);
            STAMPT(544, 23);
        }
    } else {
        const bool one = elect();
        auto load_xl = [&](int i) {
            mbar_expect(bar_full + 8 * i, 32768 + 10240);
            tma_load2d(sb + OFF_T + i * 10240, &tm_x, i * 64, b * TILE, bar_full + 8 * i);
            tma_load3d(sb + OFF_S + i * 32768, &tm_wl, i * 64, bar_full + 8 * i);
        };
        auto load_m = [&](int i, int slot) {
            mbar_expect(bar_full + 32 + 8 * i, 32768);
            tma_load3d(sb + OFF_S + slot * 32768, &tm_m, i * 64, bar_full + 32 + 8 * i);
        };
        auto load_v = [&](int i, int slot) {
            mbar_expect(bar_full + 64 + 8 * i, 32768);
            tma_load3d(sb + OFF_S + slot * 32768, &tm_wv, i * 64, bar_full + 64 + 8 * i);
        };
        const char* hsl = (const char*)(sc->hs + slice * NN);
        auto fill = [&](int slot) { bulk_g2s(sb + OFF_S + slot * 32768, hsl + slot * 32768, slot == 4 ? NN * 16 - 4 * 32768 : 32768, bar_fill); };
        const unsigned t0 = clock();
        if (one) {
            for (int i = 0; i < 2; i++) mbar_init(bar_full + 8 * i, 1);
            asm volatile("fence.mbarrier_init.release.cluster;" ::: "memory");
            while ((unsigned)clock() - t0 < XD0) {}
            if (rowcta) load_xl(0);
            STAMPT(512, 41);
            for (int i = 2; i < 12; i++) mbar_init(bar_full + 8 * i, 1);
            mbar_init(bar_go, 1); mbar_init(bar_p, 1);
            for (int i = 0; i < 4; i++) mbar_init(bar_fill + 8 * i, 1);
            for (int i = 0; i < 10; i++) mbar_init(bar_rd + 8 * i, i < 9 ? 16 : g1 - g0 - 144);
            asm volatile("fence.mbarrier_init.release.cluster;" ::: "memory");
            if ((unsigned)__cvta_generic_to_shared(smem_raw) != sb) __trap();
            mbar_expect(bar_fill, NN * 16);
        }
        __syncwarp();
        nb_arrive<3, 544>();
        nb_arrive<13, 160>();
        if (one && rowcta) {
            while ((unsigned)clock() - t0 < XD1) {}
            load_xl(1);
            STAMPT(512, 40);
        }
        __syncwarp();
        nb_sync<15, 64>();
        if (rowcta) {
            if (one) {
                if (XD2) { while ((unsigned)clock() - t0 < XD2 + 1) {} } else mbar_wait(bar_full);
                load_xl(2);
                STAMPT(512, 52);
                mbar_wait(bar_full + (XD2 ? 0 : 8)); load_xl(3);
                STAMPT(512, 53);
                asm volatile("cp.async.bulk.prefetch.L2.global [%0],%1;" ::"l"(wv + b * 64), "r"(b == NT - 1 ? 4096 : 1024) : "memory");
                asm volatile("prefetch.tensormap [%0];" ::"l"(&tm_m) : "memory");
                asm volatile("prefetch.tensormap [%0];" ::"l"(&tm_wv) : "memory");
                bar_poll(sc, 3);
                STAMPT(512, 48);
                fence_async_gmem();
            }
            WAIT_EV(5); if (one) { load_m(0, 0); load_m(1, 1); mbar_arrive(bar_go); }
            WAIT_EV(6); if (one) load_m(2, 3);
            WAIT_EV(7); if (one) load_m(3, 0);
            WAIT_EV(12); if (one) bar_arrive(&sc->bar[2 * 64]);
            STAMPT(512, 24);
            WAIT_EV(14); if (one) { fence_async_smem(); load_v(0, 4); load_v(1, 2); }
            WAIT_EV(15);
            if (one) {
                fence_async_smem();
                load_v(2, 1); load_v(3, 3);
                bar_poll(sc, 2);
                fence_async_gmem();
            }
            STAMPT(512, 25);
            WAIT_EV(2); STAMPT(512, 1); if (one) { fill(0); if (VRS == 1) fill(4); }
            WAIT_EV(4); if (one) { fill(2); if (VRS == 3) { fence_async_smem(); fill(4); } }
            WAIT_EV(5); if (one) fill(1);
            WAIT_EV(6); if (one) fill(3);
            if (VRS < 1) { WAIT_EV(7); if (one) fill(4); }
            WAIT_EV(12);
            STAMPT(512, 15);
            if (one) {
                fence_async_smem();
#pragma unroll
                for (int kb = 0; kb < 4; kb++)
                    asm volatile("cp.async.bulk.tensor.2d.global.shared::cta.bulk_group [%0,{%2,%3}],[%1];"
                                 ::"l"(&tm_ot), "r"(sb + OFF_T + kb * 10240), "r"(kb * 64), "r"(b * TILE) : "memory");
                asm volatile("cp.async.bulk.commit_group;" ::: "memory");
                asm volatile("cp.async.bulk.wait_group 0;" ::: "memory");
                fence_async_gmem();
            }
        } else {
            if (one) {
                bar_arrive(&sc->bar[2 * 64]);
                bar_poll(sc, 2);
                fence_async_gmem(); fence_async_smem();
                for (int i = 0; i < 5; i++) fill(i);
            }
        }
        if (one) {
            bar_arrive_relaxed(&sc->bar[1 * 64]);
            mbar_arrive(bar_t);
            STAMPT(512, 26);
            bar_poll(sc, 1);
            fence_async_gmem();
            STAMPT(512, 27);
            unsigned tn = clock();
#pragma unroll 1
            for (int r = 0; r < 9; r++) {
                mbar_wait(bar_rd + 8 * r);
                fence_async_smem();
                while ((int)(clock() - tn) < 0) { if (PSLEEP) __nanosleep(PSLEEP); }
                tn = clock() + PACE;
                tma_reduce(&tm_o256, sb + OFF_STG + r * 4096, slice * 8, (g0 + 16 * r) * 16);
            }
            mbar_wait(bar_rd + 72);
            STAMPT(512, 14);
            fence_async_smem();
            tma_reduce(range == 3 ? &tm_o256 : &tm_o192, sb + OFF_STG + 9 * 4096, slice * 8, (g0 + 144) * 16);
            asm volatile("cp.async.bulk.commit_group;" ::: "memory");
            asm volatile("cp.async.bulk.wait_group.read 0;" ::: "memory");
            STAMPT(512, 13);
        }
    }
    } else {
    if (tid < 32) {
        unsigned bad = 0;
        uint4 xd[3];
#pragma unroll
        for (int k = 0; k < 3; k++) xd[k] = ldg_na((const uint4*)edst + min(b * TILE + k * 32 + lane, NN - 1u));
#pragma unroll
        for (int k = 0; k < 3; k++) { const unsigned n = min(b * TILE + k * 32 + lane, NN - 1u); bad |= (xd[k].x ^ n) | (xd[k].y ^ n) | (xd[k].z ^ n) | (xd[k].w ^ n); }
        bad = __any_sync(~0u, bad);
        if (lane == 0) sts32(sb + OFF_MISC + 20, bad);
        __syncwarp();
        nb_arrive<13, 160>();
    } else if (tid < 64) {
        const uint4* ep = (const uint4*)esrc + (min(b, NT - 1u) * TILE + lane);
        cp16(sb + OFF_EIDX + lane * 16, ep); cp16(sb + OFF_EIDX + 512 + lane * 16, ep + 32);
        if (lane < 16) cp16(sb + OFF_EIDX + 1024 + lane * 16, ep + 64);
        if (lane < 10) cp16(sb + OFF_DIS + lane * 16, dis + (min(b, NT - 1u) * 10 + lane));
        cp_commit();
        cp_wait<0>();
        nb_arrive<13, 160>();
    } else if (tid >= 192) {
        if (rowcta) {
            const unsigned bt = tid - 192;
            if (ED0) { const unsigned t0 = clock(); while ((unsigned)clock() - t0 < ED0 + 1) {} }
            const uint4 ed = ldg_na(dst4 + (b * 320 + bt)), es = ldg_na(src4 + (b * 320 + bt));
            const unsigned pad = (PADBIN + 4 * ((bt & 3) + ((b * 4) & 28))) << 16;
#pragma unroll
            for (int k = 0; k < 4; k++) if ((k & 1) == 0 || bt < 180) sts128(sb + OFF_MAIL + (k >> 1) * 9216 + (bt + (k & 1) * 320) * 16, make_uint4(pad, pad, pad, pad));
            if (bt < (512 + 2688) / 16) sts128(sb + OFF_CNT1 + bt * 16, make_uint4(0, 0, 0, 0));
            if (bt == 319) sts128(sb + OFF_MISC, make_uint4(0, 0, 0, 0));
            unsigned z;
            asm volatile("{.reg .pred p; setp.eq.u32 p,%1,0xFFFFFFFF; bar.red.popc.u32 %0,4,320,p;}" : "=r"(z) : "r"(bt) : "memory");
            const unsigned dd[4] = {ed.x + z, ed.y + z, ed.z + z, ed.w + z}, ss[4] = {es.x + z, es.y + z, es.z + z, es.w + z};
            unsigned rk[4], ow[4];
#pragma unroll
            for (int i = 0; i < 4; i++) { ow[i] = dd[i] / TILE; rk[i] = atoms_inc(sb + OFF_CNT1 + ow[i] * 4); }
#pragma unroll
            for (int i = 0; i < 4; i++) {
                const unsigned dl = dd[i] - ow[i] * TILE;
                const unsigned e = bitsel(ss[i] << 20, bitsel(dl << 21, dl << 18, 0xFF800000u), 0x00700000u) + ss[i];
                asm volatile("{.reg .pred p; setp.lt.u32 p,%2,%3; @p st.shared.u32 [%0],%1;}" ::"r"(sb + OFF_MAIL + ow[i] * 64 + rk[i] * 4 + (rk[i] >> 4) * (9216 - 64)), "r"(e), "r"(rk[i]), "n"(CELL) : "memory");
            }
            if (__builtin_expect((rk[0] | rk[1] | rk[2] | rk[3]) >= CELL, 0)) {
#pragma unroll
                for (int i = 0; i < 4; i++) if (rk[i] >= CELL) push_overflow(sc, dd[i], ss[i]);
            }
        }
        STAMPT(416, 44);
        nb_arrive<2, 352>();
    } else {
        const unsigned fw = b >> 3, hq = b & 7, q = (tid >> 5) - 2;
        const unsigned ma = sb + OFF_S + 4 * 32768 + 8192 + q * 6144;
        {
            const unsigned r = lane >> 3, da = ma + r * 128 + (((lane ^ r) & 7) << 4);
            const uint4* pa = wq + ((16 * fw + r) * 32 + q * 8 + (lane & 7));
            const uint4* pb = wk + ((32 * hq + r) * 32 + q * 8 + (lane & 7));
#pragma unroll
            for (int u = 0; u < 12; u++) cp16((da ^ ((u & 1) << 6)) + u * 512, u < 4 ? pa + u * 128 : pb + (u - 4) * 128);
            cp_commit();
        }
        const unsigned aa = ma + (lane & 15) * 128 + ((((lane >> 4) ^ lane) & 7) << 4);
        const unsigned br = 4 * ((lane & 7) >> 1) + 2 * (lane >> 4) + (lane & 1);
        const unsigned ba = ma + 2048 + br * 128 + (((((lane >> 3) & 1) ^ br) & 7) << 4);
        float c[4][4];
#pragma unroll
        for (int u = 0; u < 4; u++) c[u][0] = c[u][1] = c[u][2] = c[u][3] = 0.f;
        STAMPT(64, 38);
        cp_wait<0>();
        __syncwarp();
        STAMPT(64, 39);
#pragma unroll
        for (int k = 0; k < 4; k++) {
            const uint4 a = ldsm4(aa ^ (k << 5)), b0 = ldsm4(ba ^ (k << 5)), b1 = ldsm4((ba ^ (k << 5)) + 2048);
            mma16816(c[0], a.x, a.y, a.z, a.w, b0.x, b0.y); mma16816(c[1], a.x, a.y, a.z, a.w, b0.z, b0.w);
            mma16816(c[2], a.x, a.y, a.z, a.w, b1.x, b1.y); mma16816(c[3], a.x, a.y, a.z, a.w, b1.z, b1.w);
        }
        const unsigned ra = sb + OFF_S + 4 * 32768 + lane * 16;
#pragma unroll
        for (int i = 0; i < 4; i++)
            sts128(ra + q * 2048 + i * 512, make_uint4(__float_as_uint(c[2 * (i & 1)][2 * (i >> 1)]), __float_as_uint(c[2 * (i & 1)][2 * (i >> 1) + 1]),
                                                       __float_as_uint(c[2 * (i & 1) + 1][2 * (i >> 1)]), __float_as_uint(c[2 * (i & 1) + 1][2 * (i >> 1) + 1])));
        STAMPT(64, 42);
        nb_sync<8, 128>();
        float m[4] = {0, 0, 0, 0};
#pragma unroll
        for (int i = 0; i < 4; i++) {
            const uint4 u = lds128(ra + i * 2048 + q * 512);
            m[0] += __uint_as_float(u.x); m[1] += __uint_as_float(u.y); m[2] += __uint_as_float(u.z); m[3] += __uint_as_float(u.w);
        }
        const float k = 0.0625f * 1.4426950408889634f;
        asm volatile("st.shared.v2.u32 [%0],{%1,%2};" ::"r"(sb + OFF_MAIL + 8064 + (8 * (q >> 1) + g) * 64 + (q & 1) * 32 + t * 8),
                     "r"(pack2(m[0] * k, m[1] * k)), "r"(pack2(m[2] * k, m[3] * k)) : "memory");
        fence_async_smem();
        STAMPT(64, 43);
        nb_arrive<14, 192>();
    }
    asm volatile("setmaxnreg.inc.sync.aligned.u32 %0;" ::"n"(REG_W));
    const int w = __shfl_sync(~0u, tid >> 5, 0), wg = w >> 2;
    const int grp0 = g0 + w;
    const uint4* lp = sc->lists + (grp0 * 32 + lane);
    uint4 L0, L1;
    nb_sync<3, 544>();

    if (__builtin_expect(rowcta, 1)) {
        const unsigned descA = 0x10000u + (SB0 + OFF_S) / 16 + wg * 512;
        const unsigned greg = sb + OFF_S + w * 2048 + lane * 16;
        float d[40];
        unsigned pk[20];
        unsigned* hp = (unsigned*)(sc->hs + (2 * w * NN + b * TILE)) + lane;
        auto mma_k = [&](int Q, int slot, int st, int k0, int k1) {
            if (st < 0) wg_fence();
#pragma unroll
            for (int k = k0; k < k1; k++) {
                if (st >= 0) wg_fence();
                wg80(d, descA + slot * 2048 + k * 128, 0x10000u + (SB0 + OFF_T) / 16 + (Q & 3) * 640 + k * 2, st == -2 ? k != 0 : st == -3 || ((Q & 3) | k) != 0);
                if (st >= 0) {
#pragma unroll
                    for (int j = st + k; j < st + k + 1; j++)
                        if (j < 20) asm volatile("st.global.u32 [%0],%1;" ::"l"(hp + (j >> 1) * 32 + (j & 1) * (NN * 4)), "r"(pk[j]) : "memory");
                }
            }
            wg_commit();
        };
        auto mma_q = [&](int Q, int slot, int st) { mma_k(Q, slot, st, 0, 4); };
        auto mma_head = [&](int Q, int slot, int st) { mma_k(Q, slot, st, 0, KH); wg_wait<1>(); };
        auto mma_tail = [&](int Q, int slot, int st) { mma_k(Q, slot, st, KH, 4); };
        const uint4* xl = x + lane;
        auto eidx = [&](int i) { return lds128(sb + OFF_EIDX + (w * 5 + i) * 16); };
        auto gather = [&](const uint4& ix, int slot) {
            cp16(greg + slot * 32768, xl + ix.x * 32u); cp16(greg + slot * 32768 + 512, xl + ix.y * 32u);
            cp16(greg + slot * 32768 + 1024, xl + ix.z * 32u); cp16(greg + slot * 32768 + 1536, xl + ix.w * 32u);
            cp_commit();
        };
        const uint4 ix0 = eidx(0), ix1 = eidx(1), ix2 = eidx(2), ix3 = eidx(3), ix4 = eidx(4);
        uint4 gv[5][4];
        const unsigned gld = sb + OFF_S + w * 2048 + ((lane >> 3) & 1) * 512 + (lane >> 4) * 128 + (lane & 7) * 16;
        auto to_regs = [&](int i, int slot) {
            __syncwarp();
#pragma unroll
            for (int j = 0; j < 4; j++) gv[i][j] = ldsm4(gld + slot * 32768 + (j & 1) * 256 + (j >> 1) * 1024);
        };
        unsigned ds[10];
#pragma unroll
        for (int j = 0; j < 10; j++) ds[j] = lds32(sb + OFF_DIS + (4 * j + t) * 4);
        STAMPT(288, 2);
        mbar_wait(bar_full);
        STAMPT(288, 3);
        mma_q(0, 0, -1);
        mbar_wait(bar_full + 8);
        STAMPT(288, 50);
        mma_q(1, 1, -1);
        mbar_wait(bar_full + 16);
        STAMPT(288, 51);
        mma_head(2, 2, -1);
        EV(5);
        mma_tail(2, 2, -1);
        mbar_wait(bar_full + 24);
        STAMP(5);
        mma_q(3, 3, -1);
        mbar_wait(bar_go);
        gather(ix0, 4);
        wg_wait<0>();
        EV(6);
        STAMP(6);
#pragma unroll
        for (int j = 0; j < 20; j++) pk[j] = movm(hmul2(pack2(d[2 * j], d[2 * j + 1]), ds[j >> 1]));
#pragma unroll
        for (int j = 0; j < STPRE; j++) asm volatile("st.global.u32 [%0],%1;" ::"l"(hp + (j >> 1) * 32 + (j & 1) * (NN * 4)), "r"(pk[j]) : "memory");
        STAMP(7);
        if (G1POS < 2) nb_sync_id(8 + wg, 128);
        if (G1POS == 0) gather(ix1, 2);
        mbar_wait(bar_full + 32);
        if (G1POS == 1) { if (G0POS == 2) gather(ix0, 4); gather(ix1, 2); }
        STAMP(21);
        if (G1POS == 2) {
            mma_k(4, 0, STPRE, 0, 1);
            if (G0POS == 2) gather(ix0, 4);
            nb_sync_id(8 + wg, 128);
            gather(ix1, 2);
            mma_k(4, 0, STPRE, 1, 4);
        } else {
            mma_q(4, 0, STPRE);
        }
        STAMP(28);
        mbar_wait(bar_full + 40);
        mma_head(5, 1, STPRE + 4);
        EV(7);
        mma_tail(5, 1, STPRE + 4);
        STAMP(29);
        mbar_wait(bar_full + 48);
        STAMP(30);
        mma_head(6, 3, STPRE + 8);
        nb_sync_id(8 + wg, 128);
        gather(ix2, 1);
        mma_tail(6, 3, STPRE + 8);
        STAMP(31);
        mbar_wait(bar_full + 56);
        STAMP(32);
        mma_head(7, 0, STPRE + 12);
        nb_sync_id(8 + wg, 128);
        gather(ix3, 3);
        mma_tail(7, 0, STPRE + 12);
        EV(12);
        wg_wait<0>();
        STAMP(20);
        pack_acc(pk, d);
        nb_sync<0, 512>();
        acc_to_tile(pk, w, lane);
        gather(ix4, 0);
        cp_wait<3>();
        to_regs(0, 4);
        nb_sync<0, 512>();
        STAMP(8);
        uint4 vf[4];
        auto load_vf = [&]() {
            const unsigned va = sb + OFF_S + 4 * 32768 + wg * 8192 + ((lane & 7) + (lane >> 4) * 8) * 128 + (((2 * (w & 3) + ((lane >> 3) & 1)) ^ (lane & 7)) << 4);
#pragma unroll
            for (int k = 0; k < 4; k++) vf[k] = ldsm4t(va + k * 2048);
        };
        {
            const unsigned delta = t ^ (g >> 1), alsm = sb + OFF_ALPHA + w * 128;
            const bool par = g & 1;
            unsigned ta[5];
#pragma unroll
            for (int i = 0; i < 5; i++) ta[i] = tile_addr(w * 5 + i, lane);
            float v[4], u[4];
            to_regs(1, 2);
            EV(14);
            attn_scores(v, true, par, gv[0], ta[0]);
            attn_scores(v, delta == 1, par, gv[1], ta[1] ^ 32);
            cp_wait<2>();
            to_regs(2, 1);
            attn_scores(v, delta == 2, par, gv[2], ta[2] ^ 64);
            STAMP(33);
            cp_wait<1>();
            to_regs(3, 3);
            EV(15);
            STAMP(34);
            attn_scores(v, delta == 3, par, gv[3], ta[3] ^ 96);
            cp_wait<0>();
            to_regs(4, 0);
            STAMP(35);
            attn_scores(u, true, par, gv[4], ta[4]);
            attn_softmax(v, u, lane, alsm + ((lane & 4) + delta) * 16 + (lane >> 3) * 4);
            STAMP(49);
            if (VRS == 1) mbar_wait(bar_full + 64);
            uint4 al = lds128(alsm);
#pragma unroll
            for (int i = 0; i < 5; i++) {
                const uint4 a = al;
                if (i < 4) al = lds128(alsm + (i + 1) * 16);
                attn_mix(gv[i], a, ta[i]);
                if (i == PLACE_AT) {
                    mbar_wait(bar_p);
                    if (__builtin_expect(lds32(sb + OFF_MISC + 8) == 0, 1)) place4(tid);
                    nb_arrive<13, 608>();
                }
                if (i == 1 && VRS == 1) load_vf();
            }
        }
        STAMP(36);
        mbar_wait(bar_full + 64); mbar_wait(bar_full + 72); mbar_wait(bar_full + 80);
        fence_async_smem();
        STAMP(22);
        EV(2);
        nb_sync<0, 512>();
        mma_k(9, 2, -2, 0, VK);
        if (VRS == 3) load_vf();
        if (VK < 4) mma_k(9, 2, -1, VK, 4);
        mma_head(10, 1, -1);
        EV(4);
        mma_tail(10, 1, -1);
        mbar_wait(bar_full + 88);
        mma_head(11, 3, -1);
        EV(5);
        mma_tail(11, 3, -1);
        if (VRS == 0) {
            mma_k(8, 4, -3, 0, KH); wg_wait<1>();
            EV(6);
            mma_tail(8, 4, -1);
        } else {
            wg_fence();
            wg80r(d, vf[0], 0x10000u + (SB0 + OFF_T) / 16);
            wg_commit();
            wg_wait<1>();
            EV(6);
            wg_fence();
#pragma unroll
            for (int k = 1; k < 4; k++) wg80r(d, vf[k], 0x10000u + (SB0 + OFF_T) / 16 + k * 2);
            wg_commit();
        }
        mbar_wait(bar_c);
        L1 = ldg_na(lp); L0 = ldg_na(lp + LSTR);
        wg_wait<0>();
        if (VRS < 1) EV(7);
        STAMP(9);
        pack_acc(pk, d);
        nb_sync<0, 512>();
        STAMP(10);
        if (__builtin_expect(lds32(sb + OFF_MISC + 28) & 2, 0)) {
            for (int i = 0; i < 5; i++) sts128(tile_addr(w * 5 + i, lane), attn_generic(b * TILE + w * 5 + i, x, esrc, edst, wq, wk, wv));
        } else {
            acc_to_tile(pk, w, lane);
        }
        EV(12);
    } else {
        mbar_wait(bar_c);
        L1 = ldg_na(lp); L0 = ldg_na(lp + LSTR);
    }

    const unsigned flags = lds32(sb + OFF_MISC + 28);
    const bool anyovf = flags & 1;
    const unsigned zero = flags >> 8;
    const unsigned c64 = 0x64646464u + zero;
    if (lane < 8) sts128(sb + OFF_S + NN * 16 + lane * 16, make_uint4(0, 0, 0, 0));
    const int more = anyovf ? 0x7FFFFFFF : NN << 16;
    const float zmask = (lane >= 28) ? 0.f : -1.f;
    unsigned stg = sb + OFF_STG + w * 256 + (((lane & 7) * 2 + ((lane >> 3) & 1)) ^ ((lane >> 2) & 1)) * 16;
    unsigned rdb = bar_rd, rde = bar_rd + 48;
    const unsigned rdl = bar_rd + 8 * ((g1 - grp0 - 1) >> 4);
    __syncwarp();
    mbar_wait(bar_fill);
    STAMP(11);
    CLK0(64);
#pragma unroll 1
    for (int part = 0; part < 2; part++) {
#pragma unroll 1
        do {
            unsigned ad[9], sA, sB, tA, tB, mx;
            ad[0] = row_lo(L1.x); ad[1] = row_hi(L1.x); ad[2] = row_lo(L1.y); ad[3] = row_hi(L1.y);
            ad[4] = row_lo(L1.z); ad[5] = row_hi(L1.z); ad[6] = row_lo(L1.w); ad[7] = row_hi(L1.w); ad[8] = row_lo(L0.w);
            asm volatile("prmt.b32 %0,%2,%3,0x4140;\n prmt.b32 %1,%2,%3,0x4342;" : "=r"(sA), "=r"(sB) : "r"(L0.x), "r"(c64));
            asm volatile("prmt.b32 %0,%2,%3,0x4140;\n prmt.b32 %1,%2,%3,0x4342;" : "=r"(tA), "=r"(tB) : "r"(L0.y), "r"(c64));
            asm volatile("mov.b32 %0,%1;" : "=r"(mx) : "r"(L0.w));
            const float dA = blo_v(L0.z), dB = bhi_v(L0.z);
            asm volatile("{.reg .pred p; setp.ne.u32 p,%9,%10;\n @p ld.global.L1::no_allocate.v4.u32 {%0,%1,%2,%3},[%8+%11];\n @p ld.global.L1::no_allocate.v4.u32 {%4,%5,%6,%7},[%8+%12];}"
                         : "=r"(L1.x), "=r"(L1.y), "=r"(L1.z), "=r"(L1.w), "=r"(L0.x), "=r"(L0.y), "=r"(L0.z), "=r"(L0.w)
                         : "l"(lp), "r"(rdb), "r"(rdl), "n"(16 * 32 * 16), "n"((16 * 32 + LSTR) * 16) : "memory");
            const bool p9 = __any_sync(~0u, (int)mx < more);
            float acc0[4] = {0, 0, 0, 0}, acc1[4] = {0, 0, 0, 0};
            uint4 v[9], a0, a1;
#pragma unroll
            for (int s = 0; s < LA; s++) v[s] = ldsm4t(sb + OFF_S + ad[s]);
            a0 = p3_sel(0, sA, sB); a1 = p3_sel(1, sA, sB);
            sched_fence(zero);
#pragma unroll
            for (int s = 0; s < 9; s++) {
                uint4 n0, n1;
                if (s < 8) n0 = p3_sel(2 * s + 2, s < 7 ? sA : tA, s < 7 ? sB : tB);
                mma16816(acc0, a0.x, a0.y, a0.z, a0.w, v[s].x, v[s].y);
                if (s + LA < 9) v[s + LA] = ldsm4t(sb + OFF_S + ad[s + LA]);
                if (s < 8) n1 = p3_sel(2 * s + 3, s < 7 ? sA : tA, s < 7 ? sB : tB);
                mma16816(acc1, a1.x, a1.y, a1.z, a1.w, v[s].z, v[s].w);
                a0 = n0; a1 = n1;
            }
            if (__builtin_expect(p9, 0)) {
                p3_step(acc0, acc1, row_hi(mx & 0x7FFFFFFFu), 16, tA, tB);
                if (__any_sync(~0u, (int)mx < 0)) {
                    const uint4 C2 = ldg_na(lp + 2 * LSTR);
                    p3_step(acc0, acc1, row_lo(C2.x), 24, tA, tB); p3_step(acc0, acc1, row_hi(C2.x), 32, tA, tB);
                    p3_step(acc0, acc1, row_lo(C2.y), 40, tA, tB); p3_step(acc0, acc1, row_hi(C2.y), 48, tA, tB);
                }
                if (anyovf) {
                    float4 e = p3_overflow(sc, grp0 + 2 * (rdb - bar_rd), sb + OFF_S);
                    float s0 = e.x + e.z, s1 = e.y + e.w;
                    for (int k = 4; k < 32; k <<= 1) {
                        float u0 = __shfl_down_sync(~0u, s0, k), u1 = __shfl_down_sync(~0u, s1, k);
                        if (lane + k < 32) { s0 += u0; s1 += u1; }
                    }
                    acc0[0] += s0; acc0[1] += s1; acc0[2] += s0 - e.x; acc0[3] += s1 - e.y;
                }
            }
            float c0 = acc0[0] + acc1[0], c1 = acc0[1] + acc1[1], c2 = acc0[2] + acc1[2], c3 = acc0[3] + acc1[3];
            float n0 = __shfl_down_sync(~0u, c0, 4), n1 = __shfl_down_sync(~0u, c1, 4);
            float o0 = c0 - c2, o1 = c1 - c3, o2 = fmaf(n0, zmask, c2), o3 = fmaf(n1, zmask, c3);
            asm volatile("stmatrix.sync.aligned.m8n8.x2.shared.b16 [%0],{%1,%2};" ::"r"(stg), "r"(pack2(o0 * dA, o1 * dA)), "r"(pack2(o2 * dB, o3 * dB)) : "memory");
            __syncwarp();
            asm volatile("{.reg .pred p; setp.eq.u32 p,%1,0; @p mbarrier.arrive.shared.b64 _,[%0];}" ::"r"(rdb), "r"(lane) : "memory");
            stg += 4096;
            rdb += 8;
            lp += 16 * 32;
        } while (rdb != rde);
        mbar_wait(bar_t);
        rde = rdl + 8;
    }
    STAMP(12);
    CLK1(64, 60); STAMPT(0, 61); STAMPT(352, 62); STAMPT(480, 63);
    }
}

typedef CUresult (*EncodeFn)(CUtensorMap*, CUtensorMapDataType, cuuint32_t, void*, const cuuint64_t*, const cuuint64_t*,
                             const cuuint32_t*, const cuuint32_t*, CUtensorMapInterleave, CUtensorMapSwizzle,
                             CUtensorMapL2promotion, CUtensorMapFloatOOBfill);

}

extern "C" void kernel_launch(void* const* d_in, const int* in_sizes, int n_in, void* d_out, int out_size) {
    (void)in_sizes; (void)n_in; (void)out_size;
    static EncodeFn enc = nullptr;
    static void* scratch = nullptr;
    if (!enc) {
        cudaGetSymbolAddress(&scratch, g_scratch);
        void* fn = nullptr;
        cudaDriverEntryPointQueryResult qr;
        cudaGetDriverEntryPoint("cuTensorMapEncodeTiled", &fn, cudaEnableDefault, &qr);
        enc = (EncodeFn)fn;
        cudaFuncSetAttribute(exphormer_kernel, cudaFuncAttributeMaxDynamicSharedMemorySize, SMEM_BYTES);
    }
    CUtensorMap tm_m, tm_ms, tm_mail, tm_x, tm_wl, tm_wv, tm_ot, tm_o256, tm_o192;
    auto mk = [&](CUtensorMap* tm, void* p, int rows, int bc, int br, CUtensorMapSwizzle sw, CUtensorMapL2promotion pr) {
        cuuint64_t gd[2] = {256, (cuuint64_t)rows}, gs[1] = {512};
        cuuint32_t es[2] = {1, 1}, bx[2] = {(cuuint32_t)bc, (cuuint32_t)br};
        enc(tm, CU_TENSOR_MAP_DATA_TYPE_BFLOAT16, 2, p, gd, gs, bx, es, CU_TENSOR_MAP_INTERLEAVE_NONE, sw, pr, CU_TENSOR_MAP_FLOAT_OOB_FILL_NONE);
    };
    for (int i = 0; i < 3; i++) {
        cuuint64_t gd[3] = {64, 256, 4}, gs[2] = {512, 128};
        cuuint32_t es[3] = {1, 1, 1}, bx[3] = {64, 64, 4};
        enc(i == 2 ? &tm_m : i ? &tm_wv : &tm_wl, CU_TENSOR_MAP_DATA_TYPE_BFLOAT16, 3, i == 2 ? scratch : d_in[i ? 9 : 6], gd, gs, bx, es, CU_TENSOR_MAP_INTERLEAVE_NONE,
            CU_TENSOR_MAP_SWIZZLE_128B, CU_TENSOR_MAP_L2_PROMOTION_L2_128B, CU_TENSOR_MAP_FLOAT_OOB_FILL_NONE);
    }
    {
        cuuint64_t gd[2] = {2048, NT}, gs[1] = {8192};
        cuuint32_t es[2] = {1, 1}, bx[2] = {16, NT};
        enc(&tm_mail, CU_TENSOR_MAP_DATA_TYPE_UINT32, 2, ((Scratch*)scratch)->mail, gd, gs, bx, es, CU_TENSOR_MAP_INTERLEAVE_NONE,
            CU_TENSOR_MAP_SWIZZLE_NONE, CU_TENSOR_MAP_L2_PROMOTION_NONE, CU_TENSOR_MAP_FLOAT_OOB_FILL_NONE);
    }
    mk(&tm_ms, scratch, 256, 32, 16, CU_TENSOR_MAP_SWIZZLE_NONE, CU_TENSOR_MAP_L2_PROMOTION_NONE);
    mk(&tm_x, d_in[0], NN, 64, TILE, CU_TENSOR_MAP_SWIZZLE_128B, CU_TENSOR_MAP_L2_PROMOTION_L2_128B);
    mk(&tm_ot, d_out, NN, 64, TILE, CU_TENSOR_MAP_SWIZZLE_128B, CU_TENSOR_MAP_L2_PROMOTION_NONE);
    mk(&tm_o256, d_out, NN, 8, 256, CU_TENSOR_MAP_SWIZZLE_NONE, CU_TENSOR_MAP_L2_PROMOTION_NONE);
    mk(&tm_o192, d_out, NN, 8, 192, CU_TENSOR_MAP_SWIZZLE_NONE, CU_TENSOR_MAP_L2_PROMOTION_NONE);
    exphormer_kernel<<<NCTA, 640, SMEM_BYTES>>>(
        (const uint4*)d_in[0], (const uint4*)d_in[2], (const uint4*)d_in[1], (const uint4*)d_in[7], (const uint4*)d_in[8], (const int*)d_in[3],
        (const int*)d_in[4], (Scratch*)scratch, (const uint4*)d_in[5], (const uint4*)d_in[9],
        tm_x, tm_wl, tm_wv, tm_m, tm_ms, tm_mail, tm_ot, tm_o256, tm_o192);
}
```

```cpp
#include <cuda_runtime.h>
#include <cuda_bf16.h>
#include <cuda.h>
#include <stdint.h>

namespace {

constexpr int NN = 10000, NE = 160000, NEE = 40000;
constexpr int TILE = 80, NT = 125, NCTA = 128, NG = 625, EPC = 1280;
constexpr int CELL = 32;
constexpr int QCAP = 192;
constexpr int OVCAP = EPC + NT * CELL;
#define XD0 700
#define XD1 1100
#define XD2 1900
#define REG_W 104
#define REG_H 64
#define KH 1
#define POLLNS 0
#define STPRE 4
#define G0POS 1
#define G1POS 1
#define LA 3
#define ED0 0
#define VRS 0
#define PACE 720
#define PSLEEP 0
#define PLACE_AT 4
#define MAP 4
#define SKIPLAST 1
#define VK 4
#define GT 1
#define STAG 2
#define PLACE2 1
#define STAGAT 3
constexpr unsigned DUMMY2 = NN | (NN << 16);

constexpr unsigned SB0 = 1024;
constexpr unsigned sb = SB0;
constexpr int OFF_S = 0;
constexpr int OFF_R = 163840;
constexpr int OFF_BAR = OFF_R;
constexpr int OFF_MISC = OFF_R + 256;
constexpr int OFF_DIS = OFF_R + 320;
constexpr int OFF_PROF = OFF_R + 512;
constexpr int OFF_EIDX = OFF_R + 1024;
constexpr int OFF_ALPHA = OFF_R + 1024;
constexpr int OFF_STG = OFF_R + 3072;
constexpr int OFF_CNT1 = OFF_R + 2560;
constexpr int OFF_CNT2 = OFF_R + 3072;
constexpr int OFF_MAIL = OFF_R + 5760;
constexpr int OFF_IMG = OFF_MAIL + 9216;
constexpr int OFF_T = OFF_R + 27648;
constexpr int SMEM_BYTES = OFF_T + 40960;
static_assert(SMEM_BYTES <= 232448 && OFF_T % 1024 == 0 && OFF_STG + 3 * 8192 == OFF_T && OFF_IMG + 10752 <= OFF_T, "smem");
#define bar_fill (sb + OFF_BAR)
#define bar_t (sb + OFF_BAR + 8)
#define bar_mail (sb + OFF_BAR + 16)
#define bar_c (sb + OFF_BAR + 24)
#define bar_rd (sb + OFF_BAR + 32)
#define bar_go (sb + OFF_BAR + 112)
#define bar_g (sb + OFF_BAR + 224 - 8)
#define bar_p (sb + OFF_MISC + 56)
#define bar_full (sb + OFF_BAR + 120)
constexpr int LSTR = (NG + 48) * 32;

struct __align__(256) Scratch {
    uint4 mimg[8192];
    uint4 hs[32 * NN];
    uint4 mail[2 * NT * 512];
    uint4 lists[3 * LSTR];
    uint2 ovfn[NCTA];
    unsigned bar[5 * 64];
    unsigned ovf[NCTA * OVCAP];
};
__device__ Scratch g_scratch;
#define STAMPT(th, i)
#define CLK0(th)
#define CLK1(th, i)
#define STAMP(i) STAMPT(64, i)
#define STAMP2(i) STAMPT(416, i)

extern __shared__ __align__(1024) unsigned char smem_raw[];
__device__ __forceinline__ void bar_arrive(unsigned* p) {
    asm volatile("red.release.gpu.global.add.u32 [%0],1;" ::"l"(p) : "memory");
}
__device__ __forceinline__ void bar_arrive_relaxed(unsigned* p) {
    asm volatile("red.relaxed.gpu.global.add.u32 [%0],1;" ::"l"(p) : "memory");
}
__device__ __forceinline__ void bar_poll(const Scratch* sc, int i) {
    unsigned v, target;
    int lim = 0;
    asm volatile("ld.shared.u32 %0,[%1];" : "=r"(target) : "r"(sb + OFF_MISC + 32 + 4 * i) : "memory");
    while (true) {
        asm volatile("ld.acquire.gpu.global.u32 %0,[%1];" : "=r"(v) : "l"(&sc->bar[i * 64]) : "memory");
        if ((int)(v - target) >= 0) break;
        if (++lim > (1 << 22)) __trap();
        if (POLLNS) __nanosleep(POLLNS);
    }
}
__device__ __forceinline__ unsigned bar_poll2(const unsigned* p, unsigned target) {
    unsigned long long v;
    int lim = 0;
    do {
        asm volatile("ld.acquire.gpu.global.u64 %0,[%1];" : "=l"(v) : "l"(p) : "memory");
        if (++lim > (1 << 22)) __trap();
    } while ((int)((unsigned)v - target) < 0);
    unsigned f = (unsigned)(v >> 32);
    return (f & ~3u) == target ? f & 3 : 0;
}
__device__ __noinline__ void raise_flag(unsigned* p, unsigned target, unsigned bit) {
    unsigned old = atomicCAS(p, 0, 0), seen;
    do {
        seen = old;
        old = atomicCAS(p, seen, ((seen & ~3u) == target ? seen : target) | bit);
    } while (old != seen);
}
__device__ __forceinline__ void mbar_wait(unsigned a) {
    asm volatile("{.reg .pred p; .reg .u32 n;\n"
                 "mov.u32 n,0x400000;\n"
                 "W: mbarrier.try_wait.parity.shared.b64 p,[%0],0;\n"
                 "add.u32 n,n,-1; setp.ne.and.u32 p,n,0,!p; @p bra W;}" ::"r"(a) : "memory");
}
__device__ __forceinline__ bool elect() {
    unsigned r;
    asm volatile("{.reg .pred p; elect.sync _|p,0xFFFFFFFF; selp.u32 %0,1,0,p;}" : "=r"(r));
    return r;
}
__device__ __forceinline__ uint4 ldg_na(const uint4* p) {
    uint4 v;
    asm volatile("ld.global.L1::no_allocate.v4.u32 {%0,%1,%2,%3},[%4];" : "=r"(v.x), "=r"(v.y), "=r"(v.z), "=r"(v.w) : "l"(p) : "memory");
    return v;
}
__device__ __forceinline__ uint4 lds128(unsigned a) {
    uint4 v;
    asm volatile("ld.shared.v4.u32 {%0,%1,%2,%3},[%4];" : "=r"(v.x), "=r"(v.y), "=r"(v.z), "=r"(v.w) : "r"(a) : "memory");
    return v;
}
__device__ __forceinline__ uint4 ldsm4(unsigned a) {
    uint4 v;
    asm volatile("ldmatrix.sync.aligned.m8n8.x4.shared.b16 {%0,%1,%2,%3},[%4];" : "=r"(v.x), "=r"(v.y), "=r"(v.z), "=r"(v.w) : "r"(a) : "memory");
    return v;
}
__device__ __forceinline__ void sts128(unsigned a, uint4 v) {
    asm volatile("st.shared.v4.u32 [%0],{%1,%2,%3,%4};" ::"r"(a), "r"(v.x), "r"(v.y), "r"(v.z), "r"(v.w) : "memory");
}
__device__ __forceinline__ void sts32(unsigned a, unsigned v) { asm volatile("st.shared.u32 [%0],%1;" ::"r"(a), "r"(v) : "memory"); }
__device__ __forceinline__ unsigned lds32(unsigned a) { unsigned v; asm volatile("ld.shared.u32 %0,[%1];" : "=r"(v) : "r"(a) : "memory"); return v; }
__device__ __forceinline__ unsigned atoms_add(unsigned a, unsigned k) { unsigned v; asm volatile("atom.shared.add.u32 %0,[%1],%2;" : "=r"(v) : "r"(a), "r"(k) : "memory"); return v; }
__device__ __forceinline__ unsigned bitsel(unsigned a, unsigned b, unsigned m) { unsigned r; asm("lop3.b32 %0,%1,%2,%3,0xE4;" : "=r"(r) : "r"(a), "r"(b), "r"(m)); return r; }
__device__ __forceinline__ unsigned atoms_inc(unsigned a) { unsigned v; asm volatile("atom.shared.add.u32 %0,[%1],1;" : "=r"(v) : "r"(a) : "memory"); return v; }
__device__ __forceinline__ float blo(unsigned v) { return __uint_as_float(v << 16); }
__device__ __forceinline__ float bhi(unsigned v) { return __uint_as_float(v & 0xFFFF0000u); }
__device__ __forceinline__ float blo_v(unsigned v) { float r; asm volatile("shl.b32 %0,%1,16;" : "=f"(r) : "r"(v)); return r; }
__device__ __forceinline__ float bhi_v(unsigned v) { float r; asm volatile("and.b32 %0,%1,0xFFFF0000;" : "=f"(r) : "r"(v)); return r; }
__device__ __forceinline__ unsigned pack2(float lo, float hi) { unsigned r; asm("cvt.rn.bf16x2.f32 %0,%1,%2;" : "=r"(r) : "f"(hi), "f"(lo)); return r; }

__device__ __forceinline__ void mma16816(float* d, unsigned a0, unsigned a1, unsigned a2, unsigned a3, unsigned b0, unsigned b1) {
    asm volatile("mma.sync.aligned.m16n8k16.row.col.f32.bf16.bf16.f32 {%0,%1,%2,%3},{%4,%5,%6,%7},{%8,%9},{%0,%1,%2,%3};"
                 : "+f"(d[0]), "+f"(d[1]), "+f"(d[2]), "+f"(d[3]) : "r"(a0), "r"(a1), "r"(a2), "r"(a3), "r"(b0), "r"(b1));
}
#define R10(b) "+f"(d[b + 0]), "+f"(d[b + 1]), "+f"(d[b + 2]), "+f"(d[b + 3]), "+f"(d[b + 4]), "+f"(d[b + 5]), "+f"(d[b + 6]), "+f"(d[b + 7]), "+f"(d[b + 8]), "+f"(d[b + 9])
__device__ __forceinline__ void wg80(float* d, unsigned da, unsigned db, int sc) {
    asm volatile("{.reg .pred p; .reg .b64 a, b; setp.ne.b32 p,%42,0; mov.b64 a,{%40,%43}; mov.b64 b,{%41,%43};\n"
                 "wgmma.mma_async.sync.aligned.m64n80k16.f32.bf16.bf16 "
                 "{%0,%1,%2,%3,%4,%5,%6,%7,%8,%9,%10,%11,%12,%13,%14,%15,%16,%17,%18,%19,%20,%21,%22,%23,%24,%25,%26,%27,%28,%29,%30,%31,%32,%33,%34,%35,%36,%37,%38,%39},"
                 "a,b,p,1,1,1,0;}"
                 : R10(0), R10(10), R10(20), R10(30) : "r"(da), "r"(db), "r"(sc), "r"(0x40000040));
}
__device__ __forceinline__ void wg80r(float* d, const uint4& a, unsigned db) {
    asm volatile("{.reg .b64 b; mov.b64 b,{%44,%45};\n"
                 "wgmma.mma_async.sync.aligned.m64n80k16.f32.bf16.bf16 "
                 "{%0,%1,%2,%3,%4,%5,%6,%7,%8,%9,%10,%11,%12,%13,%14,%15,%16,%17,%18,%19,%20,%21,%22,%23,%24,%25,%26,%27,%28,%29,%30,%31,%32,%33,%34,%35,%36,%37,%38,%39},"
                 "{%40,%41,%42,%43},b,1,1,1,0;}"
                 : R10(0), R10(10), R10(20), R10(30) : "r"(a.x), "r"(a.y), "r"(a.z), "r"(a.w), "r"(db), "r"(0x40000040));
}
__device__ __forceinline__ void wg_fence() { asm volatile("wgmma.fence.sync.aligned;" ::: "memory"); }
__device__ __forceinline__ void wg_commit() { asm volatile("wgmma.commit_group.sync.aligned;" ::: "memory"); }
template <int N> __device__ __forceinline__ void wg_wait() { asm volatile("wgmma.wait_group.sync.aligned %0;" ::"n"(N) : "memory"); }
__device__ __forceinline__ void bulk_g2s(unsigned dst, const void* src, unsigned bytes, unsigned bar) {
    asm volatile("cp.async.bulk.shared::cluster.global.mbarrier::complete_tx::bytes [%0],[%1],%2,[%3];" ::"r"(dst), "l"(src), "r"(bytes), "r"(bar) : "memory");
}
__device__ __forceinline__ void fence_async_smem() { asm volatile("fence.proxy.async.shared::cta;" ::: "memory"); }
__device__ __forceinline__ void fence_async_gmem() { asm volatile("fence.proxy.async.global;" ::: "memory"); }

__host__ __device__ constexpr unsigned h2c(int v) { return (0x6400u | v) | ((0x6400u | v) << 16); }
__device__ __forceinline__ unsigned row_lo(unsigned a) { unsigned r; asm volatile("dp2a.lo.u32.u32 %0,%1,0x10000010,0;" : "=r"(r) : "r"(a)); return r; }
__device__ __forceinline__ unsigned row_hi(unsigned a) { unsigned r; asm volatile("dp2a.hi.u32.u32 %0,%1,0x10000010,0;" : "=r"(r) : "r"(a)); return r; }
__device__ __forceinline__ uint4 ldsm4t(unsigned addr) {
    uint4 v;
    asm volatile("ldmatrix.sync.aligned.m8n8.x4.trans.shared.b16 {%0,%1,%2,%3},[%4];" : "=r"(v.x), "=r"(v.y), "=r"(v.z), "=r"(v.w) : "r"(addr));
    return v;
}
__device__ __forceinline__ void sched_fence(unsigned zero) { asm volatile("{.reg .pred p; setp.ne.u32 p,%0,0; @p exit;}" ::"r"(zero)); }
__device__ __forceinline__ uint4 p3_sel(int i, unsigned sA, unsigned sB) {
    uint4 a;
    asm volatile("set.le.f16x2.f16x2 %0,%4,%6;\n sub.sat.f16x2 %2,%7,%4;\n set.le.f16x2.f16x2 %1,%5,%6;\n sub.sat.f16x2 %3,%7,%5;"
                 : "=r"(a.x), "=r"(a.y), "=r"(a.z), "=r"(a.w) : "r"(sA), "r"(sB), "r"(h2c(2 * i)), "r"(h2c(2 * i + 2)));
    return a;
}
__device__ __forceinline__ void p3_step(float* acc0, float* acc1, unsigned row, int s, unsigned sA, unsigned sB) {
    const uint4 v = ldsm4t(sb + OFF_S + row), a0 = p3_sel(2 * s, sA, sB), a1 = p3_sel(2 * s + 1, sA, sB);
    mma16816(acc0, a0.x, a0.y, a0.z, a0.w, v.x, v.y);
    mma16816(acc1, a1.x, a1.y, a1.z, a1.w, v.z, v.w);
}
__device__ __noinline__ float4 p3_overflow(const Scratch* sc, int grp, unsigned sS) {
    const unsigned tag = lds32(sb + OFF_MISC + 48);
    int lane = threadIdx.x & 31, g = lane >> 2, t = lane & 3;
    float4 r = make_float4(0.f, 0.f, 0.f, 0.f);
    for (int c = 0; c < NT; c++) {
        const uint2 tn = __ldcg(&sc->ovfn[c]);
        const int n = tn.x == tag ? (int)tn.y : 0;
        for (int i0 = 0; i0 < n; i0 += 32) {
            unsigned e = (i0 + lane < n) ? __ldcg(&sc->ovf[c * OVCAP + i0 + lane]) : 0xFFFFFFFFu;
            unsigned m = __ballot_sync(~0u, (int)(e >> 18) == grp);
            while (m) {
                int j = __ffs(m) - 1;
                m &= m - 1;
                unsigned ee = __shfl_sync(~0u, e, j);
                int row = (ee >> 14) & 15;
                row ^= row >> 3;
                unsigned v = lds32(sS + (ee & 0x3FFF) * 16 + t * 4);
                if ((row >> 1) == g) {
                    if (!(row & 1)) { r.x += blo(v); r.y += bhi(v); } else { r.z += blo(v); r.w += bhi(v); }
                }
            }
        }
    }
    const float k = 1.f / 128.f;
    r.x *= k; r.y *= k; r.z *= k; r.w *= k;
    return r;
}
__device__ __forceinline__ void unpack8(float* f, uint4 v) {
    f[0] = blo(v.x); f[1] = bhi(v.x); f[2] = blo(v.y); f[3] = bhi(v.y); f[4] = blo(v.z); f[5] = bhi(v.z); f[6] = blo(v.w); f[7] = bhi(v.w);
}
__device__ __forceinline__ void vec_mat(float* o, const float* v, const uint4* __restrict__ W, int lane) {
    for (int k = 0; k < 8; k++) o[k] = 0.f;
    for (int l = 0; l < 32; l++) {
#pragma unroll
        for (int i = 0; i < 8; i++) {
            float a = __shfl_sync(~0u, v[i], l), wr[8];
            unpack8(wr, W[(l * 8 + i) * 32 + lane]);
#pragma unroll
            for (int k = 0; k < 8; k++) o[k] = fmaf(a, wr[k], o[k]);
        }
    }
}
__device__ __noinline__ uint4 attn_generic(int node, const uint4* __restrict__ x, const int* __restrict__ esrc, const int* __restrict__ edst,
                                           const uint4* __restrict__ wq, const uint4* __restrict__ wk, const uint4* __restrict__ wv) {
    int lane = threadIdx.x & 31;
    float xr[8], q[8], y[8], o[8];
    unpack8(xr, x[node * 32 + lane]);
    vec_mat(q, xr, wq, lane);
    for (int l = 0; l < 32; l++) {
#pragma unroll
        for (int i = 0; i < 8; i++) {
            float wr[8], p = 0.f;
            unpack8(wr, wk[(l * 8 + i) * 32 + lane]);
#pragma unroll
            for (int k = 0; k < 8; k++) p = fmaf(q[k], wr[k], p);
            for (int k = 16; k; k >>= 1) p += __shfl_xor_sync(~0u, p, k);
            if (lane == l) y[i] = p;
        }
    }
    for (int k = 0; k < 8; k++) o[k] = 0.f;
    float den = 0.f;
    for (int i0 = 0; i0 < NEE; i0 += 32) {
        unsigned m = __ballot_sync(~0u, edst[i0 + lane] == node);
        while (m) {
            int j = __ffs(m) - 1;
            m &= m - 1;
            float gq[8], p = 0.f;
            unpack8(gq, x[esrc[i0 + j] * 32 + lane]);
#pragma unroll
            for (int k = 0; k < 8; k++) p = fmaf(y[k], gq[k], p);
            for (int k = 16; k; k >>= 1) p += __shfl_xor_sync(~0u, p, k);
            float ex = __expf(p * 0.0625f);
            den += ex;
#pragma unroll
            for (int k = 0; k < 8; k++) o[k] = fmaf(ex, gq[k], o[k]);
        }
    }
    float inv = 1.f / (den + 1e-9f);
    for (int k = 0; k < 8; k++) o[k] *= inv;
    vec_mat(q, o, wv, lane);
    return make_uint4(pack2(q[0], q[1]), pack2(q[2], q[3]), pack2(q[4], q[5]), pack2(q[6], q[7]));
}

__device__ __forceinline__ unsigned hfma2(unsigned a, unsigned b, unsigned c) { unsigned r; asm("fma.rn.bf16x2 %0,%1,%2,%3;" : "=r"(r) : "r"(a), "r"(b), "r"(c)); return r; }
__device__ __forceinline__ unsigned hmul2(unsigned a, unsigned b) { unsigned r; asm("mul.rn.bf16x2 %0,%1,%2;" : "=r"(r) : "r"(a), "r"(b)); return r; }

__device__ __forceinline__ unsigned tile_addr(int n, unsigned chunk) { return sb + OFF_T + (chunk >> 3) * 10240 + n * 128 + (((chunk ^ n) & 7) << 4); }
__device__ __forceinline__ void attn_scores(float* v, bool mine, bool par, const uint4* gv, unsigned yaddr) {
    const uint4 y = ldsm4(yaddr);
    float c[4] = {0, 0, 0, 0}, e[4] = {0, 0, 0, 0};
    mma16816(c, gv[0].x, gv[0].y, gv[0].z, gv[0].w, y.x, y.y);
    mma16816(e, gv[2].x, gv[2].y, gv[2].z, gv[2].w, y.x, y.y);
    mma16816(c, gv[1].x, gv[1].y, gv[1].z, gv[1].w, y.z, y.w);
    mma16816(e, gv[3].x, gv[3].y, gv[3].z, gv[3].w, y.z, y.w);
    if (mine) { v[0] = par ? c[1] : c[0]; v[1] = par ? c[3] : c[2]; v[2] = par ? e[1] : e[0]; v[3] = par ? e[3] : e[2]; }
}
__device__ __forceinline__ void attn_softmax(const float* v, const float* u, unsigned lane, unsigned aladdr) {
    const bool hA = lane & 4, hB = lane & 8, hC = lane & 16;
    float a[4];
#pragma unroll
    for (int e = 0; e < 4; e++) a[e] = (hA ? u[e] : v[e]) + __shfl_xor_sync(~0u, hA ? v[e] : u[e], 4);
    float b0 = (hB ? a[1] : a[0]) + __shfl_xor_sync(~0u, hB ? a[0] : a[1], 9);
    float b1 = (hB ? a[3] : a[2]) + __shfl_xor_sync(~0u, hB ? a[2] : a[3], 9);
    float sc = (hC ? b1 : b0) + __shfl_xor_sync(~0u, hC ? b0 : b1, 18);
    float ex, inv;
    asm("ex2.approx.ftz.f32 %0,%1;" : "=f"(ex) : "f"(sc));
    float den = ex + __shfl_xor_sync(~0u, ex, 9);
    den += __shfl_xor_sync(~0u, den, 18);
    asm("rcp.approx.ftz.f32 %0,%1;" : "=f"(inv) : "f"(den + 1e-9f));
    sts32(aladdr, pack2(ex * inv, ex * inv));
    __syncwarp();
}
__device__ __forceinline__ void attn_mix(const uint4* gv, const uint4& a, unsigned oaddr) {
    const unsigned o0 = hfma2(a.w, gv[2].y, hfma2(a.z, gv[2].x, hfma2(a.y, gv[0].y, hmul2(a.x, gv[0].x))));
    const unsigned o1 = hfma2(a.w, gv[2].w, hfma2(a.z, gv[2].z, hfma2(a.y, gv[0].w, hmul2(a.x, gv[0].z))));
    const unsigned o2 = hfma2(a.w, gv[3].y, hfma2(a.z, gv[3].x, hfma2(a.y, gv[1].y, hmul2(a.x, gv[1].x))));
    const unsigned o3 = hfma2(a.w, gv[3].w, hfma2(a.z, gv[3].z, hfma2(a.y, gv[1].w, hmul2(a.x, gv[1].z))));
    asm volatile("stmatrix.sync.aligned.m8n8.x4.shared.b16 [%0],{%1,%2,%3,%4};" ::"r"(oaddr), "r"(o0), "r"(o1), "r"(o2), "r"(o3) : "memory");
}
__device__ __forceinline__ void pack_acc(unsigned* pk, const float* d) {
#pragma unroll
    for (int j = 0; j < 20; j++) pk[j] = pack2(d[2 * j], d[2 * j + 1]);
}
__device__ __forceinline__ void acc_to_tile(const unsigned* pk, int w, int lane) {
    const unsigned a = sb + OFF_T + (w >> 2) * 10240 + (lane >> 4) * 1024 + (lane & 7) * 128 + (((2 * (w & 3) + ((lane >> 3) & 1)) ^ (lane & 7)) << 4);
#pragma unroll
    for (int j = 0; j < 5; j++)
        asm volatile("stmatrix.sync.aligned.m8n8.x4.trans.shared.b16 [%0],{%1,%2,%3,%4};" ::"r"(a + j * 2048), "r"(pk[4 * j]), "r"(pk[4 * j + 1]), "r"(pk[4 * j + 2]), "r"(pk[4 * j + 3]) : "memory");
}
__device__ __forceinline__ unsigned movm(unsigned a) { unsigned d; asm volatile("movmatrix.sync.aligned.m8n8.trans.b16 %0,%1;" : "=r"(d) : "r"(a)); return d; }
__device__ __forceinline__ void tma_load2d(unsigned dst, const CUtensorMap* tm, int c0, int c1, unsigned bar) {
    asm volatile("cp.async.bulk.tensor.2d.shared::cluster.global.mbarrier::complete_tx::bytes [%0],[%1,{%3,%4}],[%2];"
                 ::"r"(dst), "l"(tm), "r"(bar), "r"(c0), "r"(c1) : "memory");
}
__device__ __forceinline__ void tma_load3d(unsigned dst, const CUtensorMap* tm, int row, unsigned bar) {
    asm volatile("cp.async.bulk.tensor.3d.shared::cluster.global.mbarrier::complete_tx::bytes [%0],[%1,{%4,%3,%4}],[%2];"
                 ::"r"(dst), "l"(tm), "r"(bar), "r"(row), "r"(0) : "memory");
}
__device__ __forceinline__ void cp16(unsigned dst, const void* src) { asm volatile("cp.async.cg.shared.global [%0],[%1],16;" ::"r"(dst), "l"(src) : "memory"); }
__device__ __forceinline__ void cp_commit() { asm volatile("cp.async.commit_group;" ::: "memory"); }
template <int N> __device__ __forceinline__ void cp_wait() { asm volatile("cp.async.wait_group %0;" ::"n"(N) : "memory"); }
__device__ __forceinline__ void nb_sync_id(int id, int n) { asm volatile("bar.sync %0,%1;" ::"r"(id), "r"(n) : "memory"); }
__device__ __forceinline__ void nb_arrive_id(int id, int n) { asm volatile("bar.arrive %0,%1;" ::"r"(id), "r"(n) : "memory"); }
template <int ID, int N> __device__ __forceinline__ void nb_sync() { asm volatile("bar.sync %0,%1;" ::"n"(ID), "n"(N) : "memory"); }
template <int ID, int N> __device__ __forceinline__ void nb_arrive() { asm volatile("bar.arrive %0,%1;" ::"n"(ID), "n"(N) : "memory"); }
__device__ __forceinline__ void mbar_init(unsigned a, int n) { asm volatile("mbarrier.init.shared.b64 [%0],%1;" ::"r"(a), "r"(n) : "memory"); }
__device__ __forceinline__ void mbar_expect(unsigned a, int n) { asm volatile("mbarrier.arrive.expect_tx.shared.b64 _,[%0],%1;" ::"r"(a), "r"(n) : "memory"); }
__device__ __forceinline__ void mbar_arrive(unsigned a) { asm volatile("mbarrier.arrive.shared.b64 _,[%0];" ::"r"(a) : "memory"); }

constexpr unsigned PADBIN = 2560;
__device__ __noinline__ void push_overflow(Scratch* sc, unsigned dst, unsigned src) {
    sc->ovf[blockIdx.x * OVCAP + atoms_inc(sb + OFF_MISC)] = (dst << 14) | src;
}
__device__ __forceinline__ void entry_overflow(Scratch* sc, unsigned e) {
    if (e < (PADBIN << 16)) push_overflow(sc, blockIdx.x * TILE + ((e >> 21) & ~3u) + ((e >> 18) & 3), e & 0xFFFF);
}
__device__ __forceinline__ unsigned rank_addr(unsigned i) { return sb + OFF_IMG + 2560 + i * 4 + (i >= 384 ? 4096 - 1536 : 0); }
__device__ __forceinline__ void place(unsigned e, unsigned r, unsigned w) {
    const unsigned p = r + (w >> 16), t2 = r * 0x801 + w;
    const unsigned tt = p < 32 ? p * 0x808 : t2, bin = p < 32 ? e >> 16 : bitsel(t2 << 2, e >> 16, 0x1070);
    asm volatile("{.reg .pred p; setp.lt.u32 p,%2,%3; @p st.shared.u16 [%0],%1;}"
                 ::"r"(sb + OFF_IMG + bitsel(tt >> 4, bin, 0x18E)), "h"((unsigned short)e), "r"(e), "n"(PADBIN << 16) : "memory");
}
__device__ __forceinline__ void place4(unsigned i) {
    uint4 e = lds128(sb + OFF_MAIL + i * 16);
    const unsigned r = lds32(rank_addr(i));
    e.w &= 0x7FFFFFFFu;
    const uint4 w = make_uint4(lds32(sb + OFF_CNT2 + (e.x >> 16)), lds32(sb + OFF_CNT2 + (e.y >> 16)), lds32(sb + OFF_CNT2 + (e.z >> 16)), lds32(sb + OFF_CNT2 + (e.w >> 16)));
    place(e.x, r & 255, w.x); place(e.y, (r >> 8) & 255, w.y); place(e.z, (r >> 16) & 255, w.z); place(e.w, r >> 24, w.w);
}
__device__ __noinline__ void place_slow(Scratch* sc, unsigned ht, unsigned broken) {
    for (unsigned i = ht; i < 576 * 4; i += 96) {
        const unsigned e = lds32(sb + OFF_MAIL + i * 4) & 0x7FFFFFFFu, w = lds32(sb + OFF_CNT2 + (e >> 16));
        const unsigned r = (lds32(rank_addr(i >> 2)) >> (8 * (i & 3))) & 255, q = (r + w) & 0xFF;
        if (r + (w >> 16) < 32) place(e, r, w);
        else if (broken >> (e >> 25) & 1) entry_overflow(sc, e);
        else if (e < (PADBIN << 16))
            asm volatile("st.shared.u16 [%0],%1;" ::"r"(sb + OFF_IMG + (q < 192 ? 8192 : 4096) + (e >> 25) * 512 + (q & 3) * 128 + (q & 28) * 4 + (q >> 5) * 2), "h"((unsigned short)e) : "memory");
    }
}
__device__ __noinline__ void tail_overflow(Scratch* sc, unsigned mask, unsigned ht) {
    for (int i = 0; i < 6 * 16; i++)
        if (mask >> (i >> 4) & 1)
            entry_overflow(sc, __ldcg((const unsigned*)(sc->mail + ((NT + blockIdx.x) * 512 + ((ht + (i >> 4) * 96) & ~3u))) + (i & 15)));
}
__device__ __forceinline__ void bulk_s2g(void* dst, unsigned src, unsigned bytes) {
    asm volatile("cp.async.bulk.global.shared::cta.bulk_group [%0],[%1],%2;" ::"l"(dst), "r"(src), "r"(bytes) : "memory");
}
__device__ __forceinline__ void tma_reduce(const CUtensorMap* tm, unsigned src, int c0, int c1) {
    asm volatile("cp.reduce.async.bulk.tensor.2d.global.shared::cta.add.tile.bulk_group [%0,{%2,%3}],[%1];" ::"l"(tm), "r"(src), "r"(c0), "r"(c1) : "memory");
}
#define EV(id) nb_arrive<id, 544>()
#define WAIT_EV(id) do { __syncwarp(); nb_sync<id, 544>(); } while (0)

__global__ void __launch_bounds__(640, 1)
exphormer_kernel(const uint4* __restrict__ x, const uint4* __restrict__ dst4, const uint4* __restrict__ src4,
                 const uint4* __restrict__ wq, const uint4* __restrict__ wk, const int* __restrict__ esrc,
                 const int* __restrict__ edst, Scratch* __restrict__ sc, const uint4* __restrict__ dis, const uint4* __restrict__ wv,
                 const __grid_constant__ CUtensorMap tm_x, const __grid_constant__ CUtensorMap tm_wl, const __grid_constant__ CUtensorMap tm_wv,
                 const __grid_constant__ CUtensorMap tm_m, const __grid_constant__ CUtensorMap tm_ms,
                 const __grid_constant__ CUtensorMap tm_mail, const __grid_constant__ CUtensorMap tm_ot, const __grid_constant__ CUtensorMap tm_o256, const __grid_constant__ CUtensorMap tm_o192) {
    const unsigned tid = threadIdx.x, lane = tid & 31, g = lane >> 2, t = lane & 3;
    const unsigned b = blockIdx.x;
    const bool rowcta = b < NT;
    const int slice = (b >> 4) * 4 + (b & 3), range = (b >> 2) & 3;
    const int g0 = (range * NG) >> 2, g1 = ((range + 1) * NG) >> 2;
    STAMP(0);

    if (tid >= 512) {
    asm volatile("setmaxnreg.dec.sync.aligned.u32 %0;" ::"n"(REG_H));
    if (tid >= 544) {
        const unsigned ht = tid - 544;
        if (ht < 32) {
            if (lane == 0) asm volatile("prefetch.tensormap [%0];" ::"l"(&tm_mail) : "memory");
            __syncwarp();
            nb_sync<13, 160>();
            nb_sync<2, 352>();
            if (rowcta) {
                const uint4 c = lds128(sb + OFF_CNT1 + lane * 16);
                const unsigned cc[4] = {c.x, c.y, c.z, c.w};
#pragma unroll
                for (int i = 0; i < 4; i++)
                    if (cc[i] > 16) asm volatile("red.shared.or.b32 [%0],0x80000000;" ::"r"(sb + OFF_MAIL + (lane * 4 + i) * 64 + 60) : "memory");
                fence_async_smem();
                __syncwarp();
                if (elect())
                    asm volatile("cp.async.bulk.tensor.2d.global.shared::cta.bulk_group [%0,{%2,%3}],[%1];" ::"l"(&tm_mail), "r"(sb + OFF_MAIL), "r"(b * 16), "r"(0) : "memory");
                for (int i = 0; i < 4; i++)
                    if (lds32(sb + OFF_CNT1 + lane * 16 + i * 4) > 16) bulk_s2g(sc->mail + ((NT + lane * 4 + i) * 512 + b * 4), sb + OFF_IMG + (lane * 4 + i) * 64, 64);
                asm volatile("cp.async.bulk.commit_group;" ::: "memory");
                asm volatile("cp.async.bulk.wait_group 0;" ::: "memory");
                fence_async_gmem();
                __syncwarp();
            }
            if (rowcta) nb_arrive<1, 96>();
            if (elect()) {
                bar_arrive_relaxed(&sc->bar[0]);
                STAMPT(544, 47);
                if (rowcta) {
                    bar_poll(sc, 0);
                    fence_async_gmem();
                    mbar_expect(bar_mail, 8000);
                    bulk_g2s(sb + OFF_MAIL, sc->mail + b * 512, 8000, bar_mail);
                }
            }
            __syncwarp();
        } else if (ht < 64) {
            if (lane == 0) asm volatile("prefetch.tensormap [%0];" ::"l"(&tm_ms) : "memory");
            nb_sync<14, 192>();
            if (elect()) {
                asm volatile("cp.async.bulk.tensor.2d.global.shared::cta.bulk_group [%0,{%2,%3}],[%1];" ::"l"(&tm_ms), "r"(sb + OFF_MAIL + 8064), "r"((b & 7) * 32), "r"((b >> 3) * 16) : "memory");
                asm volatile("cp.async.bulk.commit_group;" ::: "memory");
                asm volatile("cp.async.bulk.wait_group 0;" ::: "memory");
                fence_async_gmem();
                bar_arrive_relaxed(&sc->bar[3 * 64]);
                STAMPT(576, 46);
            }
            __syncwarp();
        } else {
            if (lane < 5) {
                unsigned epoch;
                asm volatile("ld.relaxed.gpu.global.u32 %0,[%1];" : "=r"(epoch) : "l"(&sc->bar[lane * 64]) : "memory");
                sts32(sb + OFF_MISC + 32 + lane * 4, (epoch & ~(NCTA - 1)) + NCTA);
            }
            __syncwarp();
            nb_arrive<14, 192>();
            nb_arrive<15, 64>();
            nb_arrive<13, 160>();
        }
        if (rowcta) {
            if (ht >= 32) {
                nb_sync<1, 96>();
                const unsigned pad = (PADBIN + 4 * lane) << 16, h2 = ht - 32;
                sts128(sb + OFF_MAIL + 8000 + h2 * 16, make_uint4(pad, pad, pad, pad));
                if (h2 < 12) sts128(sb + OFF_MAIL + 9024 + h2 * 16, make_uint4(pad, pad, pad, pad));
#pragma unroll
                for (int k = 0; k < 9; k++) {
                    const unsigned dm = k < 3 ? DUMMY2 + (lane & 7) * 0x10001u : DUMMY2;
                    if (k % 3 < 2 || h2 < 32) sts128(sb + OFF_IMG + (k / 3) * 4096 + (k % 3) * 1024 + h2 * 16, make_uint4(dm, dm, dm, dm));
                }
            }
            nb_sync<13, 96>();
            mbar_wait(bar_mail);
            STAMPT(576, 16);
            uint4 e[6], h[6];
            unsigned flagged = 0, late = 0, longg = 0;
#pragma unroll
            for (int k = 0; k < 6; k++) e[k] = lds128(sb + OFF_MAIL + (ht + k * 96) * 16);
#pragma unroll
            for (int k = 0; k < 6; k++) { flagged |= (e[k].w >> 31) << k; e[k].w &= 0x7FFFFFFFu; }
            while (flagged) {
                const unsigned f = __ffs(flagged) - 1, k = atoms_add(sb + OFF_MISC + 4, 4);
                const uint4* sp = sc->mail + ((NT + b) * 512 + ((ht + f * 96) & ~3u));
                flagged &= flagged - 1;
                if (k < 76) {
#pragma unroll
                    for (int j = 0; j < 4; j++) cp16(sb + OFF_MAIL + 8000 + (k + j) * 16, sp + j);
                } else {
                    late |= 1u << f;
                }
            }
            cp_commit();
            __syncwarp();
#pragma unroll
            for (int k = 0; k < 6; k++) {
                if (k == 5) { cp_wait<0>(); nb_sync<1, 96>(); if (ht >= 20) e[5] = lds128(sb + OFF_MAIL + (ht + 480) * 16); }
                h[k] = make_uint4(atoms_inc(sb + OFF_CNT2 + (e[k].x >> 16)), atoms_inc(sb + OFF_CNT2 + (e[k].y >> 16)),
                                  atoms_inc(sb + OFF_CNT2 + (e[k].z >> 16)), atoms_inc(sb + OFF_CNT2 + (e[k].w >> 16)));
            }
#pragma unroll
            for (int k = 0; k < 6; k++)
                sts32(rank_addr(ht + k * 96), __byte_perm(__byte_perm(min(h[k].x, 255u), min(h[k].y, 255u), 0x0040), __byte_perm(min(h[k].z, 255u), min(h[k].w, 255u), 0x0040), 0x5410));
            nb_sync<1, 96>();
            STAMPT(576, 17);
            unsigned rare;
            {
                const bool sw = lane >= 16;
                const unsigned G0 = ht >> 5, G1 = min(G0 + 3, 4u);
                uint4 c[2];
                unsigned inc[2], st[2][4], lf[2], ex[2], xs[2], word[2], s2w[2], dp[2];
#pragma unroll
                for (int j = 0; j < 2; j++) c[j] = lds128(sb + OFF_CNT2 + (j ? G1 : G0) * 512 + lane * 16);
#pragma unroll
                for (int j = 0; j < 2; j++) dp[j] = lds32(sb + OFF_DIS + ((j ? G1 : G0) * 8 + g) * 4);
#pragma unroll
                for (int j = 0; j < 2; j++) { inc[j] = c[j].x + c[j].y + c[j].z + c[j].w; const unsigned u = __shfl_up_sync(~0u, inc[j], 8); if (lane >= 8) inc[j] += u; }
#pragma unroll
                for (int j = 0; j < 2; j++) { const unsigned u = __shfl_up_sync(~0u, inc[j], 16); if (sw) inc[j] += u; }
#pragma unroll
                for (int j = 0; j < 2; j++) {
                    const unsigned s2 = c[j].x + c[j].y;
                    st[j][0] = inc[j] - s2 - c[j].z - c[j].w; st[j][1] = st[j][0] + (sw ? c[j].y : c[j].x);
                    st[j][2] = st[j][0] + s2; st[j][3] = st[j][2] + (sw ? c[j].w : c[j].z);
                    const unsigned m0 = max(st[j][0], 32u), m1 = max(st[j][1], 32u), m2 = max(st[j][2], 32u), m3 = max(st[j][3], 32u), m4 = max(inc[j], 32u);
                    const unsigned Q = __reduce_add_sync(~0u, m4 - m0);
                    lf[j] = Q <= QCAP ? (m1 - m0) | (m2 - m1) << 8 | (m3 - m2) << 16 | (m4 - m3) << 24 : 0;
                    xs[j] = __reduce_add_sync(~0u, Q <= QCAP ? (m4 - m0) << (lane & 24) : 0);
                    if (Q > 64 && (j == 0 || ht < 64)) longg |= (Q <= QCAP ? 1u : 0x100u) << (j ? G1 : G0);
                    word[j] = min(st[j][0], 32u) | min(st[j][1], 32u) << 8 | min(st[j][2], 32u) << 16 | min(st[j][3], 32u) << 24;
                    ex[j] = lf[j];
                }
#pragma unroll
                for (int d = 1; d < 8; d <<= 1)
#pragma unroll
                    for (int j = 0; j < 2; j++) { const unsigned u = __shfl_up_sync(~0u, ex[j], d); if ((lane & 7) >= d) ex[j] += u; }
#pragma unroll
                for (int j = 0; j < 2; j++) {
                    const unsigned tot = __shfl_sync(~0u, ex[j], lane | 7);
                    s2w[j] = tot * 0x01010100u + (((xs[j] * 0x01010100u) >> (lane & 24)) & 255) * 0x01010101u;
                    const unsigned q0 = s2w[j] + ex[j] - lf[j];
                    unsigned w4[4];
#pragma unroll
                    for (int i = 0; i < 4; i++)
                        w4[i] = __byte_perm((((q0 >> (8 * i)) & 255) + 192 + st[j][i] - max(st[j][i], 32u)) * 0x801 + 0x400, min(st[j][i], 32u), 0x5410);
                    if (j == 0 || ht < 64)
                        sts128(sb + OFF_CNT2 + (j ? G1 : G0) * 512 + lane * 16, make_uint4(sw ? w4[1] : w4[0], sw ? w4[0] : w4[1], sw ? w4[3] : w4[2], sw ? w4[2] : w4[3]));
                }
                if (longg && lane == 0) asm volatile("red.shared.or.b32 [%0],%1;" ::"r"(sb + OFF_MISC + 8), "r"(longg) : "memory");
                asm volatile("{.reg .pred p; setp.ne.u32 p,%1,0; bar.red.popc.u32 %0,1,96,p;}" : "=r"(rare) : "r"(longg) : "memory");
                if (ht == 64) mbar_arrive(bar_p);
#pragma unroll
                for (int j = 0; j < 2; j++) {
                    const unsigned wa = __shfl_sync(~0u, word[j], (g >> 1) * 8 + 2 * t), wb = __shfl_sync(~0u, word[j], (g >> 1) * 8 + 2 * t + 1);
                    const unsigned w2 = s2w[j];
                    const unsigned d128 = hmul2(dp[j], 0x43004300u);
                    const unsigned ha = sb + OFF_IMG + 4096 + (j ? G1 : G0) * 512 + lane * 16;
                    if (j == 0 || ht < 64) {
                        asm volatile("st.shared.v2.u32 [%0],{%1,%2};" ::"r"(ha), "r"(__byte_perm(wa, wb, (g & 1) ? 0x7362 : 0x5140)),
                                     "r"(__byte_perm(w2, w2, (g & 1) ? 0x3322 : 0x1100) + 0x1C201C20u - t * 0x08080808u) : "memory");
                        sts32(ha + 8, __byte_perm(d128, d128, lane >= 16 ? 0x1032 : 0x3210));
                    }
                }
            }
            if (__builtin_expect(!rare, 1)) {
                if (ht >= 32) place4(480 + ht);
            } else {
                place_slow(sc, ht, lds32(sb + OFF_MISC + 8) >> 8);
                nb_sync<1, 96>();
                for (longg &= 255; longg; longg &= longg - 1)
                    asm volatile("red.shared.or.b32 [%0],0x80000000;" ::"r"(sb + OFF_IMG + 4096 + (__ffs(longg) - 1) * 512 + lane * 16 + 12) : "memory");
            }
            if (__builtin_expect(late, 0)) tail_overflow(sc, late, ht);
            __syncwarp();
            STAMPT(576, 4);
            if (ht < 32) nb_sync<13, PLACE2 ? 352 : 608>(); else nb_arrive<13, PLACE2 ? 352 : 608>();
            STAMPT(544, 18);
        }
        if (ht < 32 && elect()) {
            if (rowcta) {
                fence_async_smem();
                for (int c = 0; c < 3; c++) bulk_s2g(sc->lists + (c * LSTR + b * 160), sb + OFF_IMG + c * 4096, 2560);
                asm volatile("cp.async.bulk.commit_group;" ::: "memory");
                const unsigned novf = lds32(sb + OFF_MISC), bad = lds32(sb + OFF_MISC + 20);
                if (__builtin_expect(novf | bad, 0)) {
                    sc->ovfn[b] = make_uint2(lds32(sb + OFF_MISC + 48), novf);
                    raise_flag(&sc->bar[4 * 64 + 1], lds32(sb + OFF_MISC + 48), (novf ? 1 : 0) | (bad ? 2 : 0));
                    __threadfence();
                }
                asm volatile("cp.async.bulk.wait_group 0;" ::: "memory");
                fence_async_gmem();
            }
            bar_arrive_relaxed(&sc->bar[4 * 64]);
            STAMPT(544, 19);
            sts32(sb + OFF_MISC + 28, bar_poll2(&sc->bar[4 * 64], lds32(sb + OFF_MISC + 48)));
            mbar_arrive(bar_c);
            STAMPT(544, 23);
        }
    } else {
        const bool one = elect();
        auto load_xl = [&](int i) {
            mbar_expect(bar_full + 8 * i, 32768 + 10240);
            tma_load2d(sb + OFF_T + i * 10240, &tm_x, i * 64, b * TILE, bar_full + 8 * i);
            tma_load3d(sb + OFF_S + i * 32768, &tm_wl, i * 64, bar_full + 8 * i);
        };
        auto load_m = [&](int i, int slot) {
            mbar_expect(bar_full + 32 + 8 * i, 32768);
            tma_load3d(sb + OFF_S + slot * 32768, &tm_m, i * 64, bar_full + 32 + 8 * i);
        };
        auto load_v = [&](int i, int slot) {
            mbar_expect(bar_full + 64 + 8 * i, 32768);
            tma_load3d(sb + OFF_S + slot * 32768, &tm_wv, i * 64, bar_full + 64 + 8 * i);
        };
        const char* hsl = (const char*)(sc->hs + slice * NN);
        auto fill = [&](int slot) { bulk_g2s(sb + OFF_S + slot * 32768, hsl + slot * 32768, slot == 4 ? NN * 16 - 4 * 32768 : 32768, bar_fill); };
        const unsigned t0 = clock();
        if (one) {
            for (int i = 0; i < 2; i++) mbar_init(bar_full + 8 * i, 1);
            asm volatile("fence.mbarrier_init.release.cluster;" ::: "memory");
            while ((unsigned)clock() - t0 < XD0) {}
            if (rowcta) load_xl(0);
            STAMPT(512, 41);
            for (int i = 2; i < 12; i++) mbar_init(bar_full + 8 * i, 1);
            mbar_init(bar_go, 1); mbar_init(bar_p, 1);
            for (int i = 0; i < 5; i++) mbar_init(bar_g + 8 * i, 16);
            for (int i = 0; i < 4; i++) mbar_init(bar_fill + 8 * i, 1);
            for (int i = 0; i < 10; i++) mbar_init(bar_rd + 8 * i, i < 9 ? 16 : g1 - g0 - 144);
            asm volatile("fence.mbarrier_init.release.cluster;" ::: "memory");
            if ((unsigned)__cvta_generic_to_shared(smem_raw) != sb) __trap();
            mbar_expect(bar_fill, NN * 16);
        }
        __syncwarp();
        nb_arrive<3, 544>();
        nb_arrive<13, 160>();
        if (one && rowcta) {
            while ((unsigned)clock() - t0 < XD1) {}
            load_xl(1);
            STAMPT(512, 40);
        }
        __syncwarp();
        nb_sync<15, 64>();
        if (rowcta) {
            if (one) {
                if (XD2) { while ((unsigned)clock() - t0 < XD2 + 1) {} } else mbar_wait(bar_full);
                load_xl(2);
                STAMPT(512, 52);
                mbar_wait(bar_full + (XD2 ? 0 : 8)); load_xl(3);
                STAMPT(512, 53);
                asm volatile("cp.async.bulk.prefetch.L2.global [%0],%1;" ::"l"(wv + b * 64), "r"(b == NT - 1 ? 4096 : 1024) : "memory");
                asm volatile("prefetch.tensormap [%0];" ::"l"(&tm_m) : "memory");
                asm volatile("prefetch.tensormap [%0];" ::"l"(&tm_wv) : "memory");
                bar_poll(sc, 3);
                STAMPT(512, 48);
                fence_async_gmem();
            }
            WAIT_EV(5); if (one) { load_m(0, 0); load_m(1, 1); mbar_arrive(bar_go); }
            WAIT_EV(6); if (one) load_m(2, 3);
            WAIT_EV(7); if (one) load_m(3, 0);
            WAIT_EV(12); if (one) bar_arrive(&sc->bar[2 * 64]);
            STAMPT(512, 24);
            WAIT_EV(14); if (one) { fence_async_smem(); load_v(0, 4); load_v(1, 2); }
            WAIT_EV(15);
            if (one) {
                fence_async_smem();
                load_v(2, 1); load_v(3, 3);
                bar_poll(sc, 2);
                fence_async_gmem();
            }
            STAMPT(512, 25);
            WAIT_EV(2); STAMPT(512, 1); if (one) { fill(0); if (VRS == 1) fill(4); }
            WAIT_EV(4); if (one) { fill(2); if (VRS == 3) { fence_async_smem(); fill(4); } }
            WAIT_EV(5); if (one) fill(1);
            WAIT_EV(6); if (one) fill(3);
            if (VRS < 1) { WAIT_EV(7); if (one) fill(4); }
            WAIT_EV(12);
            STAMPT(512, 15);
            if (one) {
                fence_async_smem();
#pragma unroll
                for (int kb = 0; kb < 4; kb++)
                    asm volatile("cp.async.bulk.tensor.2d.global.shared::cta.bulk_group [%0,{%2,%3}],[%1];"
                                 ::"l"(&tm_ot), "r"(sb + OFF_T + kb * 10240), "r"(kb * 64), "r"(b * TILE) : "memory");
                asm volatile("cp.async.bulk.commit_group;" ::: "memory");
                asm volatile("cp.async.bulk.wait_group 0;" ::: "memory");
                fence_async_gmem();
            }
        } else {
            if (one) {
                bar_arrive(&sc->bar[2 * 64]);
                bar_poll(sc, 2);
                fence_async_gmem(); fence_async_smem();
                for (int i = 0; i < 5; i++) fill(i);
            }
        }
        if (one) {
            bar_arrive_relaxed(&sc->bar[1 * 64]);
            mbar_arrive(bar_t);
            STAMPT(512, 26);
            bar_poll(sc, 1);
            fence_async_gmem();
            STAMPT(512, 27);
            unsigned tn = clock();
#pragma unroll 1
            for (int r = 0; r < 9; r++) {
                mbar_wait(bar_rd + 8 * r);
                fence_async_smem();
                while ((int)(clock() - tn) < 0) { if (PSLEEP) __nanosleep(PSLEEP); }
                tn = clock() + PACE;
                tma_reduce(&tm_o256, sb + OFF_STG + r * 4096, slice * 8, (g0 + 16 * r) * 16);
            }
            mbar_wait(bar_rd + 72);
            STAMPT(512, 14);
            fence_async_smem();
            tma_reduce(range == 3 ? &tm_o256 : &tm_o192, sb + OFF_STG + 9 * 4096, slice * 8, (g0 + 144) * 16);
            asm volatile("cp.async.bulk.commit_group;" ::: "memory");
            asm volatile("cp.async.bulk.wait_group.read 0;" ::: "memory");
            STAMPT(512, 13);
        }
    }
    } else {
    if (tid < 32) {
        unsigned bad = 0;
        uint4 xd[3];
#pragma unroll
        for (int k = 0; k < 3; k++) xd[k] = ldg_na((const uint4*)edst + min(b * TILE + k * 32 + lane, NN - 1u));
#pragma unroll
        for (int k = 0; k < 3; k++) { const unsigned n = min(b * TILE + k * 32 + lane, NN - 1u); bad |= (xd[k].x ^ n) | (xd[k].y ^ n) | (xd[k].z ^ n) | (xd[k].w ^ n); }
        bad = __any_sync(~0u, bad);
        if (lane == 0) sts32(sb + OFF_MISC + 20, bad);
        __syncwarp();
        nb_arrive<13, 160>();
    } else if (tid < 64) {
        const uint4* ep = (const uint4*)esrc + (min(b, NT - 1u) * TILE + lane);
        cp16(sb + OFF_EIDX + lane * 16, ep); cp16(sb + OFF_EIDX + 512 + lane * 16, ep + 32);
        if (lane < 16) cp16(sb + OFF_EIDX + 1024 + lane * 16, ep + 64);
        if (lane < 10) cp16(sb + OFF_DIS + lane * 16, dis + (min(b, NT - 1u) * 10 + lane));
        cp_commit();
        cp_wait<0>();
        nb_arrive<13, 160>();
    } else if (tid >= 192) {
        if (rowcta) {
            const unsigned bt = tid - 192;
            if (ED0) { const unsigned t0 = clock(); while ((unsigned)clock() - t0 < ED0 + 1) {} }
            const uint4 ed = ldg_na(dst4 + (b * 320 + bt)), es = ldg_na(src4 + (b * 320 + bt));
            const unsigned pad = (PADBIN + 4 * ((bt & 3) + ((b * 4) & 28))) << 16;
#pragma unroll
            for (int k = 0; k < 4; k++) if ((k & 1) == 0 || bt < 180) sts128(sb + OFF_MAIL + (k >> 1) * 9216 + (bt + (k & 1) * 320) * 16, make_uint4(pad, pad, pad, pad));
            if (bt < (512 + 2688) / 16) sts128(sb + OFF_CNT1 + bt * 16, make_uint4(0, 0, 0, 0));
            if (bt == 319) sts128(sb + OFF_MISC, make_uint4(0, 0, 0, 0));
            unsigned z;
            asm volatile("{.reg .pred p; setp.eq.u32 p,%1,0xFFFFFFFF; bar.red.popc.u32 %0,4,320,p;}" : "=r"(z) : "r"(bt) : "memory");
            const unsigned dd[4] = {ed.x + z, ed.y + z, ed.z + z, ed.w + z}, ss[4] = {es.x + z, es.y + z, es.z + z, es.w + z};
            unsigned rk[4], ow[4];
#pragma unroll
            for (int i = 0; i < 4; i++) { ow[i] = dd[i] / TILE; rk[i] = atoms_inc(sb + OFF_CNT1 + ow[i] * 4); }
#pragma unroll
            for (int i = 0; i < 4; i++) {
                const unsigned dl = dd[i] - ow[i] * TILE;
                const unsigned e = bitsel(ss[i] << 20, bitsel(dl << 21, dl << 18, 0xFF800000u), 0x00700000u) + ss[i];
                asm volatile("{.reg .pred p; setp.lt.u32 p,%2,%3; @p st.shared.u32 [%0],%1;}" ::"r"(sb + OFF_MAIL + ow[i] * 64 + rk[i] * 4 + (rk[i] >> 4) * (9216 - 64)), "r"(e), "r"(rk[i]), "n"(CELL) : "memory");
            }
            if (__builtin_expect((rk[0] | rk[1] | rk[2] | rk[3]) >= CELL, 0)) {
#pragma unroll
                for (int i = 0; i < 4; i++) if (rk[i] >= CELL) push_overflow(sc, dd[i], ss[i]);
            }
        }
        STAMPT(416, 44);
        nb_arrive<2, 352>();
    } else {
        const unsigned fw = b >> 3, hq = b & 7, q = (tid >> 5) - 2;
        const unsigned ma = sb + OFF_S + 4 * 32768 + 8192 + q * 6144;
        {
            const unsigned r = lane >> 3, da = ma + r * 128 + (((lane ^ r) & 7) << 4);
            const uint4* pa = wq + ((16 * fw + r) * 32 + q * 8 + (lane & 7));
            const uint4* pb = wk + ((32 * hq + r) * 32 + q * 8 + (lane & 7));
#pragma unroll
            for (int u = 0; u < 12; u++) cp16((da ^ ((u & 1) << 6)) + u * 512, u < 4 ? pa + u * 128 : pb + (u - 4) * 128);
            cp_commit();
        }
        const unsigned aa = ma + (lane & 15) * 128 + ((((lane >> 4) ^ lane) & 7) << 4);
        const unsigned br = 4 * ((lane & 7) >> 1) + 2 * (lane >> 4) + (lane & 1);
        const unsigned ba = ma + 2048 + br * 128 + (((((lane >> 3) & 1) ^ br) & 7) << 4);
        float c[4][4];
#pragma unroll
        for (int u = 0; u < 4; u++) c[u][0] = c[u][1] = c[u][2] = c[u][3] = 0.f;
        STAMPT(64, 38);
        cp_wait<0>();
        __syncwarp();
        STAMPT(64, 39);
#pragma unroll
        for (int k = 0; k < 4; k++) {
            const uint4 a = ldsm4(aa ^ (k << 5)), b0 = ldsm4(ba ^ (k << 5)), b1 = ldsm4((ba ^ (k << 5)) + 2048);
            mma16816(c[0], a.x, a.y, a.z, a.w, b0.x, b0.y); mma16816(c[1], a.x, a.y, a.z, a.w, b0.z, b0.w);
            mma16816(c[2], a.x, a.y, a.z, a.w, b1.x, b1.y); mma16816(c[3], a.x, a.y, a.z, a.w, b1.z, b1.w);
        }
        const unsigned ra = sb + OFF_S + 4 * 32768 + lane * 16;
#pragma unroll
        for (int i = 0; i < 4; i++)
            sts128(ra + q * 2048 + i * 512, make_uint4(__float_as_uint(c[2 * (i & 1)][2 * (i >> 1)]), __float_as_uint(c[2 * (i & 1)][2 * (i >> 1) + 1]),
                                                       __float_as_uint(c[2 * (i & 1) + 1][2 * (i >> 1)]), __float_as_uint(c[2 * (i & 1) + 1][2 * (i >> 1) + 1])));
        STAMPT(64, 42);
        nb_sync<8, 128>();
        float m[4] = {0, 0, 0, 0};
#pragma unroll
        for (int i = 0; i < 4; i++) {
            const uint4 u = lds128(ra + i * 2048 + q * 512);
            m[0] += __uint_as_float(u.x); m[1] += __uint_as_float(u.y); m[2] += __uint_as_float(u.z); m[3] += __uint_as_float(u.w);
        }
        const float k = 0.0625f * 1.4426950408889634f;
        asm volatile("st.shared.v2.u32 [%0],{%1,%2};" ::"r"(sb + OFF_MAIL + 8064 + (8 * (q >> 1) + g) * 64 + (q & 1) * 32 + t * 8),
                     "r"(pack2(m[0] * k, m[1] * k)), "r"(pack2(m[2] * k, m[3] * k)) : "memory");
        fence_async_smem();
        STAMPT(64, 43);
        nb_arrive<14, 192>();
    }
    asm volatile("setmaxnreg.inc.sync.aligned.u32 %0;" ::"n"(REG_W));
    const int w = __shfl_sync(~0u, tid >> 5, 0), wg = w >> 2;
    const int grp0 = g0 + w;
    const uint4* lp = sc->lists + (grp0 * 32 + lane);
    uint4 L0, L1;
    nb_sync<3, 544>();

    if (__builtin_expect(rowcta, 1)) {
        const unsigned descA = 0x10000u + (SB0 + OFF_S) / 16 + wg * 512;
        const unsigned greg = sb + OFF_S + w * 2048 + lane * 16;
        float d[40];
        unsigned pk[20];
        unsigned* hp = (unsigned*)(sc->hs + (2 * w * NN + b * TILE)) + lane;
        auto mma_k = [&](int Q, int slot, int st, int k0, int k1) {
            if (st < 0) wg_fence();
#pragma unroll
            for (int k = k0; k < k1; k++) {
                if (st >= 0) wg_fence();
                wg80(d, descA + slot * 2048 + k * 128, 0x10000u + (SB0 + OFF_T) / 16 + (Q & 3) * 640 + k * 2, st == -2 ? k != 0 : st == -3 || ((Q & 3) | k) != 0);
                if (st >= 0) {
#pragma unroll
                    for (int j = st + k; j < st + k + 1; j++)
                        if (j < 20) asm volatile("st.global.u32 [%0],%1;" ::"l"(hp + (j >> 1) * 32 + (j & 1) * (NN * 4)), "r"(pk[j]) : "memory");
                }
            }
            wg_commit();
        };
        auto mma_q = [&](int Q, int slot, int st) { mma_k(Q, slot, st, 0, 4); };
        auto mma_head = [&](int Q, int slot, int st) { mma_k(Q, slot, st, 0, KH); wg_wait<1>(); };
        auto mma_tail = [&](int Q, int slot, int st) { mma_k(Q, slot, st, KH, 4); };
        const uint4* xl = x + lane;
        auto eidx = [&](int i) { return lds128(sb + OFF_EIDX + (w * 5 + i) * 16); };
        auto gather = [&](const uint4& ix, int slot) {
            if (GT) {
                if (elect()) {
                    const unsigned bar = bar_g + 8 * slot, dst = sb + OFF_S + slot * 32768 + w * 2048;
                    if (slot == 4) fence_async_smem();
                    mbar_expect(bar, 2048);
                    bulk_g2s(dst, x + ix.x * 32u, 512, bar); bulk_g2s(dst + 512, x + ix.y * 32u, 512, bar);
                    bulk_g2s(dst + 1024, x + ix.z * 32u, 512, bar); bulk_g2s(dst + 1536, x + ix.w * 32u, 512, bar);
                }
                __syncwarp();
                return;
            }
            cp16(greg + slot * 32768, xl + ix.x * 32u); cp16(greg + slot * 32768 + 512, xl + ix.y * 32u);
            cp16(greg + slot * 32768 + 1024, xl + ix.z * 32u); cp16(greg + slot * 32768 + 1536, xl + ix.w * 32u);
            cp_commit();
        };
        const uint4 ix0 = eidx(0), ix1 = eidx(1), ix2 = eidx(2), ix3 = eidx(3), ix4 = eidx(4);
        uint4 gv[5][4];
        const unsigned gld = sb + OFF_S + w * 2048 + ((lane >> 3) & 1) * 512 + (lane >> 4) * 128 + (lane & 7) * 16;
        auto to_regs = [&](int i, int slot) {
            if (GT) mbar_wait(bar_g + 8 * slot); else __syncwarp();
#pragma unroll
            for (int j = 0; j < 4; j++) gv[i][j] = ldsm4(gld + slot * 32768 + (j & 1) * 256 + (j >> 1) * 1024);
        };
        unsigned ds[10];
#pragma unroll
        for (int j = 0; j < 10; j++) ds[j] = lds32(sb + OFF_DIS + (4 * j + t) * 4);
        STAMPT(288, 2);
        mbar_wait(bar_full);
        STAMPT(288, 3);
        mma_q(0, 0, -1);
        mbar_wait(bar_full + 8);
        STAMPT(288, 50);
        mma_q(1, 1, -1);
        mbar_wait(bar_full + 16);
        STAMPT(288, 51);
        mma_head(2, 2, -1);
        EV(5);
        mma_tail(2, 2, -1);
        mbar_wait(bar_full + 24);
        STAMP(5);
        mma_q(3, 3, -1);
        mbar_wait(bar_go);
        gather(ix0, 4);
        wg_wait<0>();
        EV(6);
        STAMP(6);
#pragma unroll
        for (int j = 0; j < 20; j++) pk[j] = movm(hmul2(pack2(d[2 * j], d[2 * j + 1]), ds[j >> 1]));
#pragma unroll
        for (int j = 0; j < STPRE; j++) asm volatile("st.global.u32 [%0],%1;" ::"l"(hp + (j >> 1) * 32 + (j & 1) * (NN * 4)), "r"(pk[j]) : "memory");
        STAMP(7);
        if (G1POS < 2) nb_sync_id(8 + wg, 128);
        if (G1POS == 0) gather(ix1, 2);
        mbar_wait(bar_full + 32);
        if (G1POS == 1) { if (G0POS == 2) gather(ix0, 4); gather(ix1, 2); }
        STAMP(21);
        if (G1POS == 2) {
            mma_k(4, 0, STPRE, 0, 1);
            if (G0POS == 2) gather(ix0, 4);
            nb_sync_id(8 + wg, 128);
            gather(ix1, 2);
            mma_k(4, 0, STPRE, 1, 4);
        } else {
            mma_q(4, 0, STPRE);
        }
        STAMP(28);
        mbar_wait(bar_full + 40);
        mma_head(5, 1, STPRE + 4);
        EV(7);
        mma_tail(5, 1, STPRE + 4);
        STAMP(29);
        mbar_wait(bar_full + 48);
        STAMP(30);
        mma_head(6, 3, STPRE + 8);
        nb_sync_id(8 + wg, 128);
        gather(ix2, 1);
        mma_tail(6, 3, STPRE + 8);
        STAMP(31);
        mbar_wait(bar_full + 56);
        STAMP(32);
        mma_head(7, 0, STPRE + 12);
        nb_sync_id(8 + wg, 128);
        gather(ix3, 3);
        mma_tail(7, 0, STPRE + 12);
        EV(12);
        wg_wait<0>();
        STAMP(20);
        pack_acc(pk, d);
        nb_sync<0, 512>();
        acc_to_tile(pk, w, lane);
        gather(ix4, 0);
        if (!GT) cp_wait<3>();
        to_regs(0, 4);
        nb_sync<0, 512>();
        STAMP(8);
        uint4 vf[4];
        auto load_vf = [&]() {
            const unsigned va = sb + OFF_S + 4 * 32768 + wg * 8192 + ((lane & 7) + (lane >> 4) * 8) * 128 + (((2 * (w & 3) + ((lane >> 3) & 1)) ^ (lane & 7)) << 4);
#pragma unroll
            for (int k = 0; k < 4; k++) vf[k] = ldsm4t(va + k * 2048);
        };
        {
            const unsigned delta = t ^ (g >> 1), alsm = sb + OFF_ALPHA + w * 128;
            const bool par = g & 1;
            unsigned ta[5];
#pragma unroll
            for (int i = 0; i < 5; i++) ta[i] = tile_addr(w * 5 + i, lane);
            float v[4], u[4];
            if (STAG == 2 && wg >= 2) nb_sync<9, 512>();
            if (STAG == 4 && wg >= 1) nb_sync_id(8 + wg, 256);
            to_regs(1, 2);
            EV(14);
            attn_scores(v, true, par, gv[0], ta[0]);
            attn_scores(v, delta == 1, par, gv[1], ta[1] ^ 32);
            if (!GT) cp_wait<2>();
            to_regs(2, 1);
            if (STAG == 2 && STAGAT == 2 && wg < 2) nb_arrive<9, 512>();
            attn_scores(v, delta == 2, par, gv[2], ta[2] ^ 64);
            STAMP(33);
            if (!GT) cp_wait<1>();
            to_regs(3, 3);
            EV(15);
            if (STAG == 2 && STAGAT == 3 && wg < 2) nb_arrive<9, 512>();
            if (STAG == 4 && wg < 3) nb_arrive_id(9 + wg, 256);
            STAMP(34);
            attn_scores(v, delta == 3, par, gv[3], ta[3] ^ 96);
            if (!GT) cp_wait<0>();
            to_regs(4, 0);
            if (STAG == 2 && STAGAT == 4 && wg < 2) nb_arrive<9, 512>();
            STAMP(35);
            attn_scores(u, true, par, gv[4], ta[4]);
            attn_softmax(v, u, lane, alsm + ((lane & 4) + delta) * 16 + (lane >> 3) * 4);
            STAMP(49);
            if (VRS == 1) mbar_wait(bar_full + 64);
            uint4 al = lds128(alsm);
#pragma unroll
            for (int i = 0; i < 5; i++) {
                const uint4 a = al;
                if (i < 4) al = lds128(alsm + (i + 1) * 16);
                attn_mix(gv[i], a, ta[i]);
                if (i == PLACE_AT && (!PLACE2 || wg < 2)) {
                    mbar_wait(bar_p);
                    if (__builtin_expect(lds32(sb + OFF_MISC + 8) == 0, 1)) {
#pragma unroll 1
                        for (int k = 0; k <= PLACE2; k++) place4(tid + k * 256);
                    }
                    nb_arrive<13, PLACE2 ? 352 : 608>();
                }
                if (i == 1 && VRS == 1) load_vf();
            }
        }
        STAMP(36);
        mbar_wait(bar_full + 64); mbar_wait(bar_full + 72); mbar_wait(bar_full + 80);
        fence_async_smem();
        STAMP(22); STAMP2(37);
        EV(2);
        nb_sync<0, 512>();
        mma_k(9, 2, -2, 0, VK);
        if (VRS == 3) load_vf();
        if (VK < 4) mma_k(9, 2, -1, VK, 4);
        mma_head(10, 1, -1);
        EV(4);
        mma_tail(10, 1, -1);
        mbar_wait(bar_full + 88);
        mma_head(11, 3, -1);
        EV(5);
        mma_tail(11, 3, -1);
        if (VRS == 0) {
            mma_k(8, 4, -3, 0, KH); wg_wait<1>();
            EV(6);
            mma_tail(8, 4, -1);
        } else {
            wg_fence();
            wg80r(d, vf[0], 0x10000u + (SB0 + OFF_T) / 16);
            wg_commit();
            wg_wait<1>();
            EV(6);
            wg_fence();
#pragma unroll
            for (int k = 1; k < 4; k++) wg80r(d, vf[k], 0x10000u + (SB0 + OFF_T) / 16 + k * 2);
            wg_commit();
        }
        mbar_wait(bar_c);
        L1 = ldg_na(lp); L0 = ldg_na(lp + LSTR);
        wg_wait<0>();
        if (VRS < 1) EV(7);
        STAMP(9);
        pack_acc(pk, d);
        nb_sync<0, 512>();
        STAMP(10);
        if (__builtin_expect(lds32(sb + OFF_MISC + 28) & 2, 0)) {
            for (int i = 0; i < 5; i++) sts128(tile_addr(w * 5 + i, lane), attn_generic(b * TILE + w * 5 + i, x, esrc, edst, wq, wk, wv));
        } else {
            acc_to_tile(pk, w, lane);
        }
        EV(12);
    } else {
        mbar_wait(bar_c);
        L1 = ldg_na(lp); L0 = ldg_na(lp + LSTR);
    }

    const unsigned flags = lds32(sb + OFF_MISC + 28);
    const bool anyovf = flags & 1;
    const unsigned zero = flags >> 8;
    const unsigned c64 = 0x64646464u + zero;
    if (lane < 8) sts128(sb + OFF_S + NN * 16 + lane * 16, make_uint4(0, 0, 0, 0));
    const int more = anyovf ? 0x7FFFFFFF : NN << 16;
    const float zmask = (lane >= 28) ? 0.f : -1.f;
    unsigned stg = sb + OFF_STG + w * 256 + (((lane & 7) * 2 + ((lane >> 3) & 1)) ^ ((lane >> 2) & 1)) * 16;
    unsigned rdb = bar_rd, rde = bar_rd + 48;
    const unsigned rdl = bar_rd + 8 * ((g1 - grp0 - 1) >> 4);
    __syncwarp();
    mbar_wait(bar_fill);
    STAMP(11);
    CLK0(64);
#pragma unroll 1
    for (int part = 0; part < 2; part++) {
#pragma unroll 1
        do {
            unsigned ad[9], sA, sB, tA, tB, mx;
            ad[0] = row_lo(L1.x); ad[1] = row_hi(L1.x); ad[2] = row_lo(L1.y); ad[3] = row_hi(L1.y);
            ad[4] = row_lo(L1.z); ad[5] = row_hi(L1.z); ad[6] = row_lo(L1.w); ad[7] = row_hi(L1.w); ad[8] = row_lo(L0.w);
            asm volatile("prmt.b32 %0,%2,%3,0x4140;\n prmt.b32 %1,%2,%3,0x4342;" : "=r"(sA), "=r"(sB) : "r"(L0.x), "r"(c64));
            asm volatile("prmt.b32 %0,%2,%3,0x4140;\n prmt.b32 %1,%2,%3,0x4342;" : "=r"(tA), "=r"(tB) : "r"(L0.y), "r"(c64));
            asm volatile("mov.b32 %0,%1;" : "=r"(mx) : "r"(L0.w));
            const float dA = blo_v(L0.z), dB = bhi_v(L0.z);
            asm volatile("{.reg .pred p; setp.ne.u32 p,%9,%10;\n @p ld.global.L1::no_allocate.v4.u32 {%0,%1,%2,%3},[%8+%11];\n @p ld.global.L1::no_allocate.v4.u32 {%4,%5,%6,%7},[%8+%12];}"
                         : "=r"(L1.x), "=r"(L1.y), "=r"(L1.z), "=r"(L1.w), "=r"(L0.x), "=r"(L0.y), "=r"(L0.z), "=r"(L0.w)
                         : "l"(lp), "r"(rdb), "r"(rdl), "n"(16 * 32 * 16), "n"((16 * 32 + LSTR) * 16) : "memory");
            const bool p9 = __any_sync(~0u, (int)mx < more);
            float acc0[4] = {0, 0, 0, 0}, acc1[4] = {0, 0, 0, 0};
            uint4 v[9], a0, a1;
#pragma unroll
            for (int s = 0; s < LA; s++) v[s] = ldsm4t(sb + OFF_S + ad[s]);
            a0 = p3_sel(0, sA, sB); a1 = p3_sel(1, sA, sB);
            sched_fence(zero);
#pragma unroll
            for (int s = 0; s < 9; s++) {
                uint4 n0, n1;
                if (s < 8) n0 = p3_sel(2 * s + 2, s < 7 ? sA : tA, s < 7 ? sB : tB);
                mma16816(acc0, a0.x, a0.y, a0.z, a0.w, v[s].x, v[s].y);
                if (s + LA < 9) v[s + LA] = ldsm4t(sb + OFF_S + ad[s + LA]);
                if (s < 8) n1 = p3_sel(2 * s + 3, s < 7 ? sA : tA, s < 7 ? sB : tB);
                mma16816(acc1, a1.x, a1.y, a1.z, a1.w, v[s].z, v[s].w);
                a0 = n0; a1 = n1;
            }
            if (__builtin_expect(p9, 0)) {
                p3_step(acc0, acc1, row_hi(mx & 0x7FFFFFFFu), 16, tA, tB);
                if (__any_sync(~0u, (int)mx < 0)) {
                    const uint4 C2 = ldg_na(lp + 2 * LSTR);
                    p3_step(acc0, acc1, row_lo(C2.x), 24, tA, tB); p3_step(acc0, acc1, row_hi(C2.x), 32, tA, tB);
                    p3_step(acc0, acc1, row_lo(C2.y), 40, tA, tB); p3_step(acc0, acc1, row_hi(C2.y), 48, tA, tB);
                }
                if (anyovf) {
                    float4 e = p3_overflow(sc, grp0 + 2 * (rdb - bar_rd), sb + OFF_S);
                    float s0 = e.x + e.z, s1 = e.y + e.w;
                    for (int k = 4; k < 32; k <<= 1) {
                        float u0 = __shfl_down_sync(~0u, s0, k), u1 = __shfl_down_sync(~0u, s1, k);
                        if (lane + k < 32) { s0 += u0; s1 += u1; }
                    }
                    acc0[0] += s0; acc0[1] += s1; acc0[2] += s0 - e.x; acc0[3] += s1 - e.y;
                }
            }
            float c0 = acc0[0] + acc1[0], c1 = acc0[1] + acc1[1], c2 = acc0[2] + acc1[2], c3 = acc0[3] + acc1[3];
            float n0 = __shfl_down_sync(~0u, c0, 4), n1 = __shfl_down_sync(~0u, c1, 4);
            float o0 = c0 - c2, o1 = c1 - c3, o2 = fmaf(n0, zmask, c2), o3 = fmaf(n1, zmask, c3);
            asm volatile("stmatrix.sync.aligned.m8n8.x2.shared.b16 [%0],{%1,%2};" ::"r"(stg), "r"(pack2(o0 * dA, o1 * dA)), "r"(pack2(o2 * dB, o3 * dB)) : "memory");
            __syncwarp();
            asm volatile("{.reg .pred p; setp.eq.u32 p,%1,0; @p mbarrier.arrive.shared.b64 _,[%0];}" ::"r"(rdb), "r"(lane) : "memory");
            stg += 4096;
            rdb += 8;
            lp += 16 * 32;
        } while (rdb != rde);
        mbar_wait(bar_t);
        rde = rdl + 8;
    }
    STAMP(12);
    CLK1(64, 60); STAMPT(0, 61); STAMPT(352, 62); STAMPT(480, 63);
    }
}

typedef CUresult (*EncodeFn)(CUtensorMap*, CUtensorMapDataType, cuuint32_t, void*, const cuuint64_t*, const cuuint64_t*,
                             const cuuint32_t*, const cuuint32_t*, CUtensorMapInterleave, CUtensorMapSwizzle,
                             CUtensorMapL2promotion, CUtensorMapFloatOOBfill);

}

extern "C" void kernel_launch(void* const* d_in, const int* in_sizes, int n_in, void* d_out, int out_size) {
    (void)in_sizes; (void)n_in; (void)out_size;
    static EncodeFn enc = nullptr;
    static void* scratch = nullptr;
    if (!enc) {
        cudaGetSymbolAddress(&scratch, g_scratch);
        void* fn = nullptr;
        cudaDriverEntryPointQueryResult qr;
        cudaGetDriverEntryPoint("cuTensorMapEncodeTiled", &fn, cudaEnableDefault, &qr);
        enc = (EncodeFn)fn;
        cudaFuncSetAttribute(exphormer_kernel, cudaFuncAttributeMaxDynamicSharedMemorySize, SMEM_BYTES);
    }
    CUtensorMap tm_m, tm_ms, tm_mail, tm_x, tm_wl, tm_wv, tm_ot, tm_o256, tm_o192;
    auto mk = [&](CUtensorMap* tm, void* p, int rows, int bc, int br, CUtensorMapSwizzle sw, CUtensorMapL2promotion pr) {
        cuuint64_t gd[2] = {256, (cuuint64_t)rows}, gs[1] = {512};
        cuuint32_t es[2] = {1, 1}, bx[2] = {(cuuint32_t)bc, (cuuint32_t)br};
        enc(tm, CU_TENSOR_MAP_DATA_TYPE_BFLOAT16, 2, p, gd, gs, bx, es, CU_TENSOR_MAP_INTERLEAVE_NONE, sw, pr, CU_TENSOR_MAP_FLOAT_OOB_FILL_NONE);
    };
    for (int i = 0; i < 3; i++) {
        cuuint64_t gd[3] = {64, 256, 4}, gs[2] = {512, 128};
        cuuint32_t es[3] = {1, 1, 1}, bx[3] = {64, 64, 4};
        enc(i == 2 ? &tm_m : i ? &tm_wv : &tm_wl, CU_TENSOR_MAP_DATA_TYPE_BFLOAT16, 3, i == 2 ? scratch : d_in[i ? 9 : 6], gd, gs, bx, es, CU_TENSOR_MAP_INTERLEAVE_NONE,
            CU_TENSOR_MAP_SWIZZLE_128B, CU_TENSOR_MAP_L2_PROMOTION_L2_128B, CU_TENSOR_MAP_FLOAT_OOB_FILL_NONE);
    }
    {
        cuuint64_t gd[2] = {2048, NT}, gs[1] = {8192};
        cuuint32_t es[2] = {1, 1}, bx[2] = {16, NT};
        enc(&tm_mail, CU_TENSOR_MAP_DATA_TYPE_UINT32, 2, ((Scratch*)scratch)->mail, gd, gs, bx, es, CU_TENSOR_MAP_INTERLEAVE_NONE,
            CU_TENSOR_MAP_SWIZZLE_NONE, CU_TENSOR_MAP_L2_PROMOTION_NONE, CU_TENSOR_MAP_FLOAT_OOB_FILL_NONE);
    }
    mk(&tm_ms, scratch, 256, 32, 16, CU_TENSOR_MAP_SWIZZLE_NONE, CU_TENSOR_MAP_L2_PROMOTION_NONE);
    mk(&tm_x, d_in[0], NN, 64, TILE, CU_TENSOR_MAP_SWIZZLE_128B, CU_TENSOR_MAP_L2_PROMOTION_L2_128B);
    mk(&tm_ot, d_out, NN, 64, TILE, CU_TENSOR_MAP_SWIZZLE_128B, CU_TENSOR_MAP_L2_PROMOTION_NONE);
    mk(&tm_o256, d_out, NN, 8, 256, CU_TENSOR_MAP_SWIZZLE_NONE, CU_TENSOR_MAP_L2_PROMOTION_NONE);
    mk(&tm_o192, d_out, NN, 8, 192, CU_TENSOR_MAP_SWIZZLE_NONE, CU_TENSOR_MAP_L2_PROMOTION_NONE);
    exphormer_kernel<<<NCTA, 640, SMEM_BYTES>>>(
        (const uint4*)d_in[0], (const uint4*)d_in[2], (const uint4*)d_in[1], (const uint4*)d_in[7], (const uint4*)d_in[8], (const int*)d_in[3],
        (const int*)d_in[4], (Scratch*)scratch, (const uint4*)d_in[5], (const uint4*)d_in[9],
        tm_x, tm_wl, tm_wv, tm_m, tm_ms, tm_mail, tm_ot, tm_o256, tm_o192);
}
```

```cpp
#include <cuda_runtime.h>
#include <cuda_bf16.h>
#include <cuda.h>
#include <stdint.h>

namespace {

constexpr int NN = 10000, NE = 160000, NEE = 40000;
constexpr int TILE = 80, NT = 125, NCTA = 128, NG = 625, EPC = 1280;
constexpr int CELL = 32;
constexpr int QCAP = 192;
constexpr int OVCAP = EPC + NT * CELL;
#define XD0 700
#define XD1 1100
#define XD2 1900
#define REG_W 104
#define REG_H 64
#define KH 1
#define POLLNS 0
#define STPRE 4
#define G0POS 1
#define G1POS 1
#define LA 3
#define ED0 0
#define VRS 0
#define PACE 720
#define PSLEEP 200
#define PLACE_AT 2
#define MAP 4
#define VK 4
#define GT 1
#define STAG 2
#define PLACE2 1
#define STAGAT 3
#define LPOS 1
#define MSLEEP 1
constexpr unsigned DUMMY2 = NN | (NN << 16);

constexpr unsigned SB0 = 1024;
constexpr unsigned sb = SB0;
constexpr int OFF_S = 0;
constexpr int OFF_R = 163840;
constexpr int OFF_BAR = OFF_R;
constexpr int OFF_MISC = OFF_R + 256;
constexpr int OFF_DIS = OFF_R + 320;
constexpr int OFF_PROF = OFF_R + 512;
constexpr int OFF_EIDX = OFF_R + 1024;
constexpr int OFF_ALPHA = OFF_R + 1024;
constexpr int OFF_STG = OFF_R + 3072;
constexpr int OFF_CNT1 = OFF_R + 2560;
constexpr int OFF_CNT2 = OFF_R + 3072;
constexpr int OFF_MAIL = OFF_R + 5760;
constexpr int OFF_IMG = OFF_MAIL + 9216;
constexpr int OFF_T = OFF_R + 27648;
constexpr int SMEM_BYTES = OFF_T + 40960;
static_assert(SMEM_BYTES <= 232448 && OFF_T % 1024 == 0 && OFF_STG + 3 * 8192 == OFF_T && OFF_IMG + 10752 <= OFF_T, "smem");
#define bar_fill (sb + OFF_BAR)
#define bar_t (sb + OFF_BAR + 8)
#define bar_mail (sb + OFF_BAR + 16)
#define bar_c (sb + OFF_BAR + 24)
#define bar_rd (sb + OFF_BAR + 32)
#define bar_go (sb + OFF_BAR + 112)
#define bar_g (sb + OFF_BAR + 224 - 8)
#define bar_p (sb + OFF_MISC + 56)
#define bar_full (sb + OFF_BAR + 120)
constexpr int LSTR = (NG + 48) * 32;

struct __align__(256) Scratch {
    uint4 mimg[8192];
    uint4 hs[32 * NN];
    uint4 mail[2 * NT * 512];
    uint4 lists[3 * LSTR];
    uint2 ovfn[NCTA];
    unsigned bar[5 * 64];
    unsigned ovf[NCTA * OVCAP];
};
__device__ Scratch g_scratch;
#define STAMPT(th, i)
#define CLK0(th)
#define CLK1(th, i)
#define STAMP(i) STAMPT(64, i)
#define STAMP2(i) STAMPT(416, i)

extern __shared__ __align__(1024) unsigned char smem_raw[];
__device__ __forceinline__ void bar_arrive(unsigned* p) {
    asm volatile("red.release.gpu.global.add.u32 [%0],1;" ::"l"(p) : "memory");
}
__device__ __forceinline__ void bar_arrive_relaxed(unsigned* p) {
    asm volatile("red.relaxed.gpu.global.add.u32 [%0],1;" ::"l"(p) : "memory");
}
__device__ __forceinline__ void bar_poll(const Scratch* sc, int i) {
    unsigned v, target;
    int lim = 0;
    asm volatile("ld.shared.u32 %0,[%1];" : "=r"(target) : "r"(sb + OFF_MISC + 32 + 4 * i) : "memory");
    while (true) {
        asm volatile("ld.acquire.gpu.global.u32 %0,[%1];" : "=r"(v) : "l"(&sc->bar[i * 64]) : "memory");
        if ((int)(v - target) >= 0) break;
        if (++lim > (1 << 22)) __trap();
        if (POLLNS) __nanosleep(POLLNS);
    }
}
__device__ __forceinline__ unsigned bar_poll2(const unsigned* p, unsigned target) {
    unsigned long long v;
    int lim = 0;
    do {
        asm volatile("ld.acquire.gpu.global.u64 %0,[%1];" : "=l"(v) : "l"(p) : "memory");
        if (++lim > (1 << 22)) __trap();
    } while ((int)((unsigned)v - target) < 0);
    unsigned f = (unsigned)(v >> 32);
    return (f & ~3u) == target ? f & 3 : 0;
}
__device__ __noinline__ void raise_flag(unsigned* p, unsigned target, unsigned bit) {
    unsigned old = atomicCAS(p, 0, 0), seen;
    do {
        seen = old;
        old = atomicCAS(p, seen, ((seen & ~3u) == target ? seen : target) | bit);
    } while (old != seen);
}
__device__ __forceinline__ void mbar_wait(unsigned a) {
    asm volatile("{.reg .pred p; .reg .u32 n;\n"
                 "mov.u32 n,0x400000;\n"
                 "W: mbarrier.try_wait.parity.shared.b64 p,[%0],0;\n"
                 "add.u32 n,n,-1; setp.ne.and.u32 p,n,0,!p; @p bra W;}" ::"r"(a) : "memory");
}
__device__ __forceinline__ void mbar_sleep(unsigned a) {
    asm volatile("{.reg .pred p; .reg .u32 n;\n"
                 "mov.u32 n,0x40000;\n"
                 "W: mbarrier.try_wait.parity.shared.b64 p,[%0],0,%1;\n"
                 "add.u32 n,n,-1; setp.ne.and.u32 p,n,0,!p; @p bra W;}" ::"r"(a), "r"(4000) : "memory");
}
__device__ __forceinline__ bool elect() {
    unsigned r;
    asm volatile("{.reg .pred p; elect.sync _|p,0xFFFFFFFF; selp.u32 %0,1,0,p;}" : "=r"(r));
    return r;
}
__device__ __forceinline__ uint4 ldg_na(const uint4* p) {
    uint4 v;
    asm volatile("ld.global.L1::no_allocate.v4.u32 {%0,%1,%2,%3},[%4];" : "=r"(v.x), "=r"(v.y), "=r"(v.z), "=r"(v.w) : "l"(p) : "memory");
    return v;
}
__device__ __forceinline__ uint4 lds128(unsigned a) {
    uint4 v;
    asm volatile("ld.shared.v4.u32 {%0,%1,%2,%3},[%4];" : "=r"(v.x), "=r"(v.y), "=r"(v.z), "=r"(v.w) : "r"(a) : "memory");
    return v;
}
__device__ __forceinline__ uint4 ldsm4(unsigned a) {
    uint4 v;
    asm volatile("ldmatrix.sync.aligned.m8n8.x4.shared.b16 {%0,%1,%2,%3},[%4];" : "=r"(v.x), "=r"(v.y), "=r"(v.z), "=r"(v.w) : "r"(a) : "memory");
    return v;
}
__device__ __forceinline__ void sts128(unsigned a, uint4 v) {
    asm volatile("st.shared.v4.u32 [%0],{%1,%2,%3,%4};" ::"r"(a), "r"(v.x), "r"(v.y), "r"(v.z), "r"(v.w) : "memory");
}
__device__ __forceinline__ void sts32(unsigned a, unsigned v) { asm volatile("st.shared.u32 [%0],%1;" ::"r"(a), "r"(v) : "memory"); }
__device__ __forceinline__ unsigned lds32(unsigned a) { unsigned v; asm volatile("ld.shared.u32 %0,[%1];" : "=r"(v) : "r"(a) : "memory"); return v; }
__device__ __forceinline__ unsigned atoms_add(unsigned a, unsigned k) { unsigned v; asm volatile("atom.shared.add.u32 %0,[%1],%2;" : "=r"(v) : "r"(a), "r"(k) : "memory"); return v; }
__device__ __forceinline__ unsigned bitsel(unsigned a, unsigned b, unsigned m) { unsigned r; asm("lop3.b32 %0,%1,%2,%3,0xE4;" : "=r"(r) : "r"(a), "r"(b), "r"(m)); return r; }
__device__ __forceinline__ unsigned atoms_inc(unsigned a) { unsigned v; asm volatile("atom.shared.add.u32 %0,[%1],1;" : "=r"(v) : "r"(a) : "memory"); return v; }
__device__ __forceinline__ float blo(unsigned v) { return __uint_as_float(v << 16); }
__device__ __forceinline__ float bhi(unsigned v) { return __uint_as_float(v & 0xFFFF0000u); }
__device__ __forceinline__ float blo_v(unsigned v) { float r; asm volatile("shl.b32 %0,%1,16;" : "=f"(r) : "r"(v)); return r; }
__device__ __forceinline__ float bhi_v(unsigned v) { float r; asm volatile("and.b32 %0,%1,0xFFFF0000;" : "=f"(r) : "r"(v)); return r; }
__device__ __forceinline__ unsigned pack2(float lo, float hi) { unsigned r; asm("cvt.rn.bf16x2.f32 %0,%1,%2;" : "=r"(r) : "f"(hi), "f"(lo)); return r; }

__device__ __forceinline__ void mma16816(float* d, unsigned a0, unsigned a1, unsigned a2, unsigned a3, unsigned b0, unsigned b1) {
    asm volatile("mma.sync.aligned.m16n8k16.row.col.f32.bf16.bf16.f32 {%0,%1,%2,%3},{%4,%5,%6,%7},{%8,%9},{%0,%1,%2,%3};"
                 : "+f"(d[0]), "+f"(d[1]), "+f"(d[2]), "+f"(d[3]) : "r"(a0), "r"(a1), "r"(a2), "r"(a3), "r"(b0), "r"(b1));
}
#define R10(b) "+f"(d[b + 0]), "+f"(d[b + 1]), "+f"(d[b + 2]), "+f"(d[b + 3]), "+f"(d[b + 4]), "+f"(d[b + 5]), "+f"(d[b + 6]), "+f"(d[b + 7]), "+f"(d[b + 8]), "+f"(d[b + 9])
__device__ __forceinline__ void wg80(float* d, unsigned da, unsigned db, int sc) {
    asm volatile("{.reg .pred p; .reg .b64 a, b; setp.ne.b32 p,%42,0; mov.b64 a,{%40,%43}; mov.b64 b,{%41,%43};\n"
                 "wgmma.mma_async.sync.aligned.m64n80k16.f32.bf16.bf16 "
                 "{%0,%1,%2,%3,%4,%5,%6,%7,%8,%9,%10,%11,%12,%13,%14,%15,%16,%17,%18,%19,%20,%21,%22,%23,%24,%25,%26,%27,%28,%29,%30,%31,%32,%33,%34,%35,%36,%37,%38,%39},"
                 "a,b,p,1,1,1,0;}"
                 : R10(0), R10(10), R10(20), R10(30) : "r"(da), "r"(db), "r"(sc), "r"(0x40000040));
}
__device__ __forceinline__ void wg80r(float* d, const uint4& a, unsigned db) {
    asm volatile("{.reg .b64 b; mov.b64 b,{%44,%45};\n"
                 "wgmma.mma_async.sync.aligned.m64n80k16.f32.bf16.bf16 "
                 "{%0,%1,%2,%3,%4,%5,%6,%7,%8,%9,%10,%11,%12,%13,%14,%15,%16,%17,%18,%19,%20,%21,%22,%23,%24,%25,%26,%27,%28,%29,%30,%31,%32,%33,%34,%35,%36,%37,%38,%39},"
                 "{%40,%41,%42,%43},b,1,1,1,0;}"
                 : R10(0), R10(10), R10(20), R10(30) : "r"(a.x), "r"(a.y), "r"(a.z), "r"(a.w), "r"(db), "r"(0x40000040));
}
__device__ __forceinline__ void wg_fence() { asm volatile("wgmma.fence.sync.aligned;" ::: "memory"); }
__device__ __forceinline__ void wg_commit() { asm volatile("wgmma.commit_group.sync.aligned;" ::: "memory"); }
template <int N> __device__ __forceinline__ void wg_wait() { asm volatile("wgmma.wait_group.sync.aligned %0;" ::"n"(N) : "memory"); }
__device__ __forceinline__ void bulk_g2s(unsigned dst, const void* src, unsigned bytes, unsigned bar) {
    asm volatile("cp.async.bulk.shared::cluster.global.mbarrier::complete_tx::bytes [%0],[%1],%2,[%3];" ::"r"(dst), "l"(src), "r"(bytes), "r"(bar) : "memory");
}
__device__ __forceinline__ void fence_async_smem() { asm volatile("fence.proxy.async.shared::cta;" ::: "memory"); }
__device__ __forceinline__ void fence_async_gmem() { asm volatile("fence.proxy.async.global;" ::: "memory"); }

__host__ __device__ constexpr unsigned h2c(int v) { return (0x6400u | v) | ((0x6400u | v) << 16); }
__device__ __forceinline__ unsigned row_lo(unsigned a) { unsigned r; asm volatile("dp2a.lo.u32.u32 %0,%1,0x10000010,0;" : "=r"(r) : "r"(a)); return r; }
__device__ __forceinline__ unsigned row_hi(unsigned a) { unsigned r; asm volatile("dp2a.hi.u32.u32 %0,%1,0x10000010,0;" : "=r"(r) : "r"(a)); return r; }
__device__ __forceinline__ uint4 ldsm4t(unsigned addr) {
    uint4 v;
    asm volatile("ldmatrix.sync.aligned.m8n8.x4.trans.shared.b16 {%0,%1,%2,%3},[%4];" : "=r"(v.x), "=r"(v.y), "=r"(v.z), "=r"(v.w) : "r"(addr));
    return v;
}
__device__ __forceinline__ void sched_fence(unsigned zero) { asm volatile("{.reg .pred p; setp.ne.u32 p,%0,0; @p exit;}" ::"r"(zero)); }
__device__ __forceinline__ uint4 p3_sel(int i, unsigned sA, unsigned sB) {
    uint4 a;
    asm volatile("set.le.f16x2.f16x2 %0,%4,%6;\n sub.sat.f16x2 %2,%7,%4;\n set.le.f16x2.f16x2 %1,%5,%6;\n sub.sat.f16x2 %3,%7,%5;"
                 : "=r"(a.x), "=r"(a.y), "=r"(a.z), "=r"(a.w) : "r"(sA), "r"(sB), "r"(h2c(2 * i)), "r"(h2c(2 * i + 2)));
    return a;
}
__device__ __forceinline__ void p3_step(float* acc0, float* acc1, unsigned row, int s, unsigned sA, unsigned sB) {
    const uint4 v = ldsm4t(sb + OFF_S + row), a0 = p3_sel(2 * s, sA, sB), a1 = p3_sel(2 * s + 1, sA, sB);
    mma16816(acc0, a0.x, a0.y, a0.z, a0.w, v.x, v.y);
    mma16816(acc1, a1.x, a1.y, a1.z, a1.w, v.z, v.w);
}
__device__ __noinline__ float4 p3_overflow(const Scratch* sc, int grp, unsigned sS) {
    const unsigned tag = lds32(sb + OFF_MISC + 48);
    int lane = threadIdx.x & 31, g = lane >> 2, t = lane & 3;
    float4 r = make_float4(0.f, 0.f, 0.f, 0.f);
    for (int c = 0; c < NT; c++) {
        const uint2 tn = __ldcg(&sc->ovfn[c]);
        const int n = tn.x == tag ? (int)tn.y : 0;
        for (int i0 = 0; i0 < n; i0 += 32) {
            unsigned e = (i0 + lane < n) ? __ldcg(&sc->ovf[c * OVCAP + i0 + lane]) : 0xFFFFFFFFu;
            unsigned m = __ballot_sync(~0u, (int)(e >> 18) == grp);
            while (m) {
                int j = __ffs(m) - 1;
                m &= m - 1;
                unsigned ee = __shfl_sync(~0u, e, j);
                int row = (ee >> 14) & 15;
                row ^= row >> 3;
                unsigned v = lds32(sS + (ee & 0x3FFF) * 16 + t * 4);
                if ((row >> 1) == g) {
                    if (!(row & 1)) { r.x += blo(v); r.y += bhi(v); } else { r.z += blo(v); r.w += bhi(v); }
                }
            }
        }
    }
    const float k = 1.f / 128.f;
    r.x *= k; r.y *= k; r.z *= k; r.w *= k;
    return r;
}
__device__ __forceinline__ void unpack8(float* f, uint4 v) {
    f[0] = blo(v.x); f[1] = bhi(v.x); f[2] = blo(v.y); f[3] = bhi(v.y); f[4] = blo(v.z); f[5] = bhi(v.z); f[6] = blo(v.w); f[7] = bhi(v.w);
}
__device__ __forceinline__ void vec_mat(float* o, const float* v, const uint4* __restrict__ W, int lane) {
    for (int k = 0; k < 8; k++) o[k] = 0.f;
    for (int l = 0; l < 32; l++) {
#pragma unroll
        for (int i = 0; i < 8; i++) {
            float a = __shfl_sync(~0u, v[i], l), wr[8];
            unpack8(wr, W[(l * 8 + i) * 32 + lane]);
#pragma unroll
            for (int k = 0; k < 8; k++) o[k] = fmaf(a, wr[k], o[k]);
        }
    }
}
__device__ __noinline__ uint4 attn_generic(int node, const uint4* __restrict__ x, const int* __restrict__ esrc, const int* __restrict__ edst,
                                           const uint4* __restrict__ wq, const uint4* __restrict__ wk, const uint4* __restrict__ wv) {
    int lane = threadIdx.x & 31;
    float xr[8], q[8], y[8], o[8];
    unpack8(xr, x[node * 32 + lane]);
    vec_mat(q, xr, wq, lane);
    for (int l = 0; l < 32; l++) {
#pragma unroll
        for (int i = 0; i < 8; i++) {
            float wr[8], p = 0.f;
            unpack8(wr, wk[(l * 8 + i) * 32 + lane]);
#pragma unroll
            for (int k = 0; k < 8; k++) p = fmaf(q[k], wr[k], p);
            for (int k = 16; k; k >>= 1) p += __shfl_xor_sync(~0u, p, k);
            if (lane == l) y[i] = p;
        }
    }
    for (int k = 0; k < 8; k++) o[k] = 0.f;
    float den = 0.f;
    for (int i0 = 0; i0 < NEE; i0 += 32) {
        unsigned m = __ballot_sync(~0u, edst[i0 + lane] == node);
        while (m) {
            int j = __ffs(m) - 1;
            m &= m - 1;
            float gq[8], p = 0.f;
            unpack8(gq, x[esrc[i0 + j] * 32 + lane]);
#pragma unroll
            for (int k = 0; k < 8; k++) p = fmaf(y[k], gq[k], p);
            for (int k = 16; k; k >>= 1) p += __shfl_xor_sync(~0u, p, k);
            float ex = __expf(p * 0.0625f);
            den += ex;
#pragma unroll
            for (int k = 0; k < 8; k++) o[k] = fmaf(ex, gq[k], o[k]);
        }
    }
    float inv = 1.f / (den + 1e-9f);
    for (int k = 0; k < 8; k++) o[k] *= inv;
    vec_mat(q, o, wv, lane);
    return make_uint4(pack2(q[0], q[1]), pack2(q[2], q[3]), pack2(q[4], q[5]), pack2(q[6], q[7]));
}

__device__ __forceinline__ unsigned hfma2(unsigned a, unsigned b, unsigned c) { unsigned r; asm("fma.rn.bf16x2 %0,%1,%2,%3;" : "=r"(r) : "r"(a), "r"(b), "r"(c)); return r; }
__device__ __forceinline__ unsigned hmul2(unsigned a, unsigned b) { unsigned r; asm("mul.rn.bf16x2 %0,%1,%2;" : "=r"(r) : "r"(a), "r"(b)); return r; }

__device__ __forceinline__ unsigned tile_addr(int n, unsigned chunk) { return sb + OFF_T + (chunk >> 3) * 10240 + n * 128 + (((chunk ^ n) & 7) << 4); }
__device__ __forceinline__ void attn_scores(float* v, bool mine, bool par, const uint4* gv, unsigned yaddr) {
    const uint4 y = ldsm4(yaddr);
    float c[4] = {0, 0, 0, 0}, e[4] = {0, 0, 0, 0};
    mma16816(c, gv[0].x, gv[0].y, gv[0].z, gv[0].w, y.x, y.y);
    mma16816(e, gv[2].x, gv[2].y, gv[2].z, gv[2].w, y.x, y.y);
    mma16816(c, gv[1].x, gv[1].y, gv[1].z, gv[1].w, y.z, y.w);
    mma16816(e, gv[3].x, gv[3].y, gv[3].z, gv[3].w, y.z, y.w);
    if (mine) { v[0] = par ? c[1] : c[0]; v[1] = par ? c[3] : c[2]; v[2] = par ? e[1] : e[0]; v[3] = par ? e[3] : e[2]; }
}
__device__ __forceinline__ void attn_softmax(const float* v, const float* u, unsigned lane, unsigned aladdr) {
    const bool hA = lane & 4, hB = lane & 8, hC = lane & 16;
    float a[4];
#pragma unroll
    for (int e = 0; e < 4; e++) a[e] = (hA ? u[e] : v[e]) + __shfl_xor_sync(~0u, hA ? v[e] : u[e], 4);
    float b0 = (hB ? a[1] : a[0]) + __shfl_xor_sync(~0u, hB ? a[0] : a[1], 9);
    float b1 = (hB ? a[3] : a[2]) + __shfl_xor_sync(~0u, hB ? a[2] : a[3], 9);
    float sc = (hC ? b1 : b0) + __shfl_xor_sync(~0u, hC ? b0 : b1, 18);
    float ex, inv;
    asm("ex2.approx.ftz.f32 %0,%1;" : "=f"(ex) : "f"(sc));
    float den = ex + __shfl_xor_sync(~0u, ex, 9);
    den += __shfl_xor_sync(~0u, den, 18);
    asm("rcp.approx.ftz.f32 %0,%1;" : "=f"(inv) : "f"(den + 1e-9f));
    sts32(aladdr, pack2(ex * inv, ex * inv));
    __syncwarp();
}
__device__ __forceinline__ void attn_mix(const uint4* gv, const uint4& a, unsigned oaddr) {
    const unsigned o0 = hfma2(a.w, gv[2].y, hfma2(a.z, gv[2].x, hfma2(a.y, gv[0].y, hmul2(a.x, gv[0].x))));
    const unsigned o1 = hfma2(a.w, gv[2].w, hfma2(a.z, gv[2].z, hfma2(a.y, gv[0].w, hmul2(a.x, gv[0].z))));
    const unsigned o2 = hfma2(a.w, gv[3].y, hfma2(a.z, gv[3].x, hfma2(a.y, gv[1].y, hmul2(a.x, gv[1].x))));
    const unsigned o3 = hfma2(a.w, gv[3].w, hfma2(a.z, gv[3].z, hfma2(a.y, gv[1].w, hmul2(a.x, gv[1].z))));
    asm volatile("stmatrix.sync.aligned.m8n8.x4.shared.b16 [%0],{%1,%2,%3,%4};" ::"r"(oaddr), "r"(o0), "r"(o1), "r"(o2), "r"(o3) : "memory");
}
__device__ __forceinline__ void pack_acc(unsigned* pk, const float* d) {
#pragma unroll
    for (int j = 0; j < 20; j++) pk[j] = pack2(d[2 * j], d[2 * j + 1]);
}
__device__ __forceinline__ void acc_to_tile(const unsigned* pk, int w, int lane) {
    const unsigned a = sb + OFF_T + (w >> 2) * 10240 + (lane >> 4) * 1024 + (lane & 7) * 128 + (((2 * (w & 3) + ((lane >> 3) & 1)) ^ (lane & 7)) << 4);
#pragma unroll
    for (int j = 0; j < 5; j++)
        asm volatile("stmatrix.sync.aligned.m8n8.x4.trans.shared.b16 [%0],{%1,%2,%3,%4};" ::"r"(a + j * 2048), "r"(pk[4 * j]), "r"(pk[4 * j + 1]), "r"(pk[4 * j + 2]), "r"(pk[4 * j + 3]) : "memory");
}
__device__ __forceinline__ unsigned movm(unsigned a) { unsigned d; asm volatile("movmatrix.sync.aligned.m8n8.trans.b16 %0,%1;" : "=r"(d) : "r"(a)); return d; }
__device__ __forceinline__ void tma_load2d(unsigned dst, const CUtensorMap* tm, int c0, int c1, unsigned bar) {
    asm volatile("cp.async.bulk.tensor.2d.shared::cluster.global.mbarrier::complete_tx::bytes [%0],[%1,{%3,%4}],[%2];"
                 ::"r"(dst), "l"(tm), "r"(bar), "r"(c0), "r"(c1) : "memory");
}
__device__ __forceinline__ void tma_load3d(unsigned dst, const CUtensorMap* tm, int row, unsigned bar) {
    asm volatile("cp.async.bulk.tensor.3d.shared::cluster.global.mbarrier::complete_tx::bytes [%0],[%1,{%4,%3,%4}],[%2];"
                 ::"r"(dst), "l"(tm), "r"(bar), "r"(row), "r"(0) : "memory");
}
__device__ __forceinline__ void cp16(unsigned dst, const void* src) { asm volatile("cp.async.cg.shared.global [%0],[%1],16;" ::"r"(dst), "l"(src) : "memory"); }
__device__ __forceinline__ void cp_commit() { asm volatile("cp.async.commit_group;" ::: "memory"); }
template <int N> __device__ __forceinline__ void cp_wait() { asm volatile("cp.async.wait_group %0;" ::"n"(N) : "memory"); }
__device__ __forceinline__ void nb_sync_id(int id, int n) { asm volatile("bar.sync %0,%1;" ::"r"(id), "r"(n) : "memory"); }
__device__ __forceinline__ void nb_arrive_id(int id, int n) { asm volatile("bar.arrive %0,%1;" ::"r"(id), "r"(n) : "memory"); }
template <int ID, int N> __device__ __forceinline__ void nb_sync() { asm volatile("bar.sync %0,%1;" ::"n"(ID), "n"(N) : "memory"); }
template <int ID, int N> __device__ __forceinline__ void nb_arrive() { asm volatile("bar.arrive %0,%1;" ::"n"(ID), "n"(N) : "memory"); }
__device__ __forceinline__ void mbar_init(unsigned a, int n) { asm volatile("mbarrier.init.shared.b64 [%0],%1;" ::"r"(a), "r"(n) : "memory"); }
__device__ __forceinline__ void mbar_expect(unsigned a, int n) { asm volatile("mbarrier.arrive.expect_tx.shared.b64 _,[%0],%1;" ::"r"(a), "r"(n) : "memory"); }
__device__ __forceinline__ void mbar_arrive(unsigned a) { asm volatile("mbarrier.arrive.shared.b64 _,[%0];" ::"r"(a) : "memory"); }

constexpr unsigned PADBIN = 2560;
__device__ __noinline__ void push_overflow(Scratch* sc, unsigned dst, unsigned src) {
    sc->ovf[blockIdx.x * OVCAP + atoms_inc(sb + OFF_MISC)] = (dst << 14) | src;
}
__device__ __forceinline__ void entry_overflow(Scratch* sc, unsigned e) {
    if (e < (PADBIN << 16)) push_overflow(sc, blockIdx.x * TILE + ((e >> 21) & ~3u) + ((e >> 18) & 3), e & 0xFFFF);
}
__device__ __forceinline__ unsigned rank_addr(unsigned i) { return sb + OFF_IMG + 2560 + i * 4 + (i >= 384 ? 4096 - 1536 : 0); }
__device__ __forceinline__ void place(unsigned e, unsigned r, unsigned w) {
    const unsigned p = r + (w >> 16), t2 = r * 0x801 + w;
    const unsigned tt = p < 32 ? p * 0x808 : t2, bin = p < 32 ? e >> 16 : bitsel(t2 << 2, e >> 16, 0x1070);
    asm volatile("{.reg .pred p; setp.lt.u32 p,%2,%3; @p st.shared.u16 [%0],%1;}"
                 ::"r"(sb + OFF_IMG + bitsel(tt >> 4, bin, 0x18E)), "h"((unsigned short)e), "r"(e), "n"(PADBIN << 16) : "memory");
}
__device__ __forceinline__ void place4(unsigned i) {
    uint4 e = lds128(sb + OFF_MAIL + i * 16);
    const unsigned r = lds32(rank_addr(i));
    e.w &= 0x7FFFFFFFu;
    const uint4 w = make_uint4(lds32(sb + OFF_CNT2 + (e.x >> 16)), lds32(sb + OFF_CNT2 + (e.y >> 16)), lds32(sb + OFF_CNT2 + (e.z >> 16)), lds32(sb + OFF_CNT2 + (e.w >> 16)));
    place(e.x, r & 255, w.x); place(e.y, (r >> 8) & 255, w.y); place(e.z, (r >> 16) & 255, w.z); place(e.w, r >> 24, w.w);
}
__device__ __noinline__ void place_slow(Scratch* sc, unsigned ht, unsigned broken) {
    for (unsigned i = ht; i < 576 * 4; i += 96) {
        const unsigned e = lds32(sb + OFF_MAIL + i * 4) & 0x7FFFFFFFu, w = lds32(sb + OFF_CNT2 + (e >> 16));
        const unsigned r = (lds32(rank_addr(i >> 2)) >> (8 * (i & 3))) & 255, q = (r + w) & 0xFF;
        if (r + (w >> 16) < 32) place(e, r, w);
        else if (broken >> (e >> 25) & 1) entry_overflow(sc, e);
        else if (e < (PADBIN << 16))
            asm volatile("st.shared.u16 [%0],%1;" ::"r"(sb + OFF_IMG + (q < 192 ? 8192 : 4096) + (e >> 25) * 512 + (q & 3) * 128 + (q & 28) * 4 + (q >> 5) * 2), "h"((unsigned short)e) : "memory");
    }
}
__device__ __noinline__ void tail_overflow(Scratch* sc, unsigned mask, unsigned ht) {
    for (int i = 0; i < 6 * 16; i++)
        if (mask >> (i >> 4) & 1)
            entry_overflow(sc, __ldcg((const unsigned*)(sc->mail + ((NT + blockIdx.x) * 512 + ((ht + (i >> 4) * 96) & ~3u))) + (i & 15)));
}
__device__ __forceinline__ void bulk_s2g(void* dst, unsigned src, unsigned bytes) {
    asm volatile("cp.async.bulk.global.shared::cta.bulk_group [%0],[%1],%2;" ::"l"(dst), "r"(src), "r"(bytes) : "memory");
}
__device__ __forceinline__ void tma_reduce(const CUtensorMap* tm, unsigned src, int c0, int c1) {
    asm volatile("cp.reduce.async.bulk.tensor.2d.global.shared::cta.add.tile.bulk_group [%0,{%2,%3}],[%1];" ::"l"(tm), "r"(src), "r"(c0), "r"(c1) : "memory");
}
#define EV(id) nb_arrive<id, 544>()
#define WAIT_EV(id) do { __syncwarp(); nb_sync<id, 544>(); } while (0)

__global__ void __launch_bounds__(640, 1)
exphormer_kernel(const uint4* __restrict__ x, const uint4* __restrict__ dst4, const uint4* __restrict__ src4,
                 const uint4* __restrict__ wq, const uint4* __restrict__ wk, const int* __restrict__ esrc,
                 const int* __restrict__ edst, Scratch* __restrict__ sc, const uint4* __restrict__ dis, const uint4* __restrict__ wv,
                 const __grid_constant__ CUtensorMap tm_x, const __grid_constant__ CUtensorMap tm_wl, const __grid_constant__ CUtensorMap tm_wv,
                 const __grid_constant__ CUtensorMap tm_m, const __grid_constant__ CUtensorMap tm_ms,
                 const __grid_constant__ CUtensorMap tm_mail, const __grid_constant__ CUtensorMap tm_ot, const __grid_constant__ CUtensorMap tm_o256, const __grid_constant__ CUtensorMap tm_o192) {
    const unsigned tid = threadIdx.x, lane = tid & 31, g = lane >> 2, t = lane & 3;
    const unsigned b = blockIdx.x;
    const bool rowcta = b < NT;
    const int slice = (b >> 4) * 4 + (b & 3), range = (b >> 2) & 3;
    const int g0 = (range * NG) >> 2, g1 = ((range + 1) * NG) >> 2;
    STAMP(0);

    if (tid >= 512) {
    asm volatile("setmaxnreg.dec.sync.aligned.u32 %0;" ::"n"(REG_H));
    if (tid >= 544) {
        const unsigned ht = tid - 544;
        if (ht < 32) {
            if (lane == 0) asm volatile("prefetch.tensormap [%0];" ::"l"(&tm_mail) : "memory");
            __syncwarp();
            nb_sync<13, 160>();
            nb_sync<2, 352>();
            if (rowcta) {
                const uint4 c = lds128(sb + OFF_CNT1 + lane * 16);
                const unsigned cc[4] = {c.x, c.y, c.z, c.w};
#pragma unroll
                for (int i = 0; i < 4; i++)
                    if (cc[i] > 16) asm volatile("red.shared.or.b32 [%0],0x80000000;" ::"r"(sb + OFF_MAIL + (lane * 4 + i) * 64 + 60) : "memory");
                fence_async_smem();
                __syncwarp();
                if (elect())
                    asm volatile("cp.async.bulk.tensor.2d.global.shared::cta.bulk_group [%0,{%2,%3}],[%1];" ::"l"(&tm_mail), "r"(sb + OFF_MAIL), "r"(b * 16), "r"(0) : "memory");
                for (int i = 0; i < 4; i++)
                    if (lds32(sb + OFF_CNT1 + lane * 16 + i * 4) > 16) bulk_s2g(sc->mail + ((NT + lane * 4 + i) * 512 + b * 4), sb + OFF_IMG + (lane * 4 + i) * 64, 64);
                asm volatile("cp.async.bulk.commit_group;" ::: "memory");
                asm volatile("cp.async.bulk.wait_group 0;" ::: "memory");
                fence_async_gmem();
                __syncwarp();
            }
            if (rowcta) nb_arrive<1, 96>();
            if (elect()) {
                bar_arrive_relaxed(&sc->bar[0]);
                STAMPT(544, 47);
                if (rowcta) {
                    bar_poll(sc, 0);
                    fence_async_gmem();
                    mbar_expect(bar_mail, 8000);
                    bulk_g2s(sb + OFF_MAIL, sc->mail + b * 512, 8000, bar_mail);
                }
            }
            __syncwarp();
        } else if (ht < 64) {
            if (lane == 0) asm volatile("prefetch.tensormap [%0];" ::"l"(&tm_ms) : "memory");
            nb_sync<14, 192>();
            if (elect()) {
                asm volatile("cp.async.bulk.tensor.2d.global.shared::cta.bulk_group [%0,{%2,%3}],[%1];" ::"l"(&tm_ms), "r"(sb + OFF_MAIL + 8064), "r"((b & 7) * 32), "r"((b >> 3) * 16) : "memory");
                asm volatile("cp.async.bulk.commit_group;" ::: "memory");
                asm volatile("cp.async.bulk.wait_group 0;" ::: "memory");
                fence_async_gmem();
                bar_arrive_relaxed(&sc->bar[3 * 64]);
                STAMPT(576, 46);
            }
            __syncwarp();
        } else {
            if (lane < 5) {
                unsigned epoch;
                asm volatile("ld.relaxed.gpu.global.u32 %0,[%1];" : "=r"(epoch) : "l"(&sc->bar[lane * 64]) : "memory");
                sts32(sb + OFF_MISC + 32 + lane * 4, (epoch & ~(NCTA - 1)) + NCTA);
            }
            __syncwarp();
            nb_arrive<14, 192>();
            nb_arrive<15, 64>();
            nb_arrive<13, 160>();
        }
        if (rowcta) {
            if (ht >= 32) {
                nb_sync<1, 96>();
                const unsigned pad = (PADBIN + 4 * lane) << 16, h2 = ht - 32;
                sts128(sb + OFF_MAIL + 8000 + h2 * 16, make_uint4(pad, pad, pad, pad));
                if (h2 < 12) sts128(sb + OFF_MAIL + 9024 + h2 * 16, make_uint4(pad, pad, pad, pad));
#pragma unroll
                for (int k = 0; k < 9; k++) {
                    const unsigned dm = k < 3 ? DUMMY2 + (lane & 7) * 0x10001u : DUMMY2;
                    if (k % 3 < 2 || h2 < 32) sts128(sb + OFF_IMG + (k / 3) * 4096 + (k % 3) * 1024 + h2 * 16, make_uint4(dm, dm, dm, dm));
                }
            }
            nb_sync<13, 96>();
            mbar_wait(bar_mail);
            STAMPT(576, 16);
            uint4 e[6], h[6];
            unsigned flagged = 0, late = 0, longg = 0;
#pragma unroll
            for (int k = 0; k < 6; k++) e[k] = lds128(sb + OFF_MAIL + (ht + k * 96) * 16);
#pragma unroll
            for (int k = 0; k < 6; k++) { flagged |= (e[k].w >> 31) << k; e[k].w &= 0x7FFFFFFFu; }
            while (flagged) {
                const unsigned f = __ffs(flagged) - 1, k = atoms_add(sb + OFF_MISC + 4, 4);
                const uint4* sp = sc->mail + ((NT + b) * 512 + ((ht + f * 96) & ~3u));
                flagged &= flagged - 1;
                if (k < 76) {
#pragma unroll
                    for (int j = 0; j < 4; j++) cp16(sb + OFF_MAIL + 8000 + (k + j) * 16, sp + j);
                } else {
                    late |= 1u << f;
                }
            }
            cp_commit();
            __syncwarp();
#pragma unroll
            for (int k = 0; k < 6; k++) {
                if (k == 5) { cp_wait<0>(); nb_sync<1, 96>(); if (ht >= 20) e[5] = lds128(sb + OFF_MAIL + (ht + 480) * 16); }
                h[k] = make_uint4(atoms_inc(sb + OFF_CNT2 + (e[k].x >> 16)), atoms_inc(sb + OFF_CNT2 + (e[k].y >> 16)),
                                  atoms_inc(sb + OFF_CNT2 + (e[k].z >> 16)), atoms_inc(sb + OFF_CNT2 + (e[k].w >> 16)));
            }
#pragma unroll
            for (int k = 0; k < 6; k++)
                sts32(rank_addr(ht + k * 96), __byte_perm(__byte_perm(min(h[k].x, 255u), min(h[k].y, 255u), 0x0040), __byte_perm(min(h[k].z, 255u), min(h[k].w, 255u), 0x0040), 0x5410));
            nb_sync<1, 96>();
            STAMPT(576, 17);
            unsigned rare;
            {
                const bool sw = lane >= 16;
                const unsigned G0 = ht >> 5, G1 = min(G0 + 3, 4u);
                uint4 c[2];
                unsigned inc[2], st[2][4], lf[2], ex[2], xs[2], word[2], s2w[2], dp[2];
#pragma unroll
                for (int j = 0; j < 2; j++) c[j] = lds128(sb + OFF_CNT2 + (j ? G1 : G0) * 512 + lane * 16);
#pragma unroll
                for (int j = 0; j < 2; j++) dp[j] = lds32(sb + OFF_DIS + ((j ? G1 : G0) * 8 + g) * 4);
#pragma unroll
                for (int j = 0; j < 2; j++) { inc[j] = c[j].x + c[j].y + c[j].z + c[j].w; const unsigned u = __shfl_up_sync(~0u, inc[j], 8); if (lane >= 8) inc[j] += u; }
#pragma unroll
                for (int j = 0; j < 2; j++) { const unsigned u = __shfl_up_sync(~0u, inc[j], 16); if (sw) inc[j] += u; }
#pragma unroll
                for (int j = 0; j < 2; j++) {
                    const unsigned s2 = c[j].x + c[j].y;
                    st[j][0] = inc[j] - s2 - c[j].z - c[j].w; st[j][1] = st[j][0] + (sw ? c[j].y : c[j].x);
                    st[j][2] = st[j][0] + s2; st[j][3] = st[j][2] + (sw ? c[j].w : c[j].z);
                    const unsigned m0 = max(st[j][0], 32u), m1 = max(st[j][1], 32u), m2 = max(st[j][2], 32u), m3 = max(st[j][3], 32u), m4 = max(inc[j], 32u);
                    const unsigned Q = __reduce_add_sync(~0u, m4 - m0);
                    lf[j] = Q <= QCAP ? (m1 - m0) | (m2 - m1) << 8 | (m3 - m2) << 16 | (m4 - m3) << 24 : 0;
                    xs[j] = __reduce_add_sync(~0u, Q <= QCAP ? (m4 - m0) << (lane & 24) : 0);
                    if (Q > 64 && (j == 0 || ht < 64)) longg |= (Q <= QCAP ? 1u : 0x100u) << (j ? G1 : G0);
                    word[j] = min(st[j][0], 32u) | min(st[j][1], 32u) << 8 | min(st[j][2], 32u) << 16 | min(st[j][3], 32u) << 24;
                    ex[j] = lf[j];
                }
#pragma unroll
                for (int d = 1; d < 8; d <<= 1)
#pragma unroll
                    for (int j = 0; j < 2; j++) { const unsigned u = __shfl_up_sync(~0u, ex[j], d); if ((lane & 7) >= d) ex[j] += u; }
#pragma unroll
                for (int j = 0; j < 2; j++) {
                    const unsigned tot = __shfl_sync(~0u, ex[j], lane | 7);
                    s2w[j] = tot * 0x01010100u + (((xs[j] * 0x01010100u) >> (lane & 24)) & 255) * 0x01010101u;
                    const unsigned q0 = s2w[j] + ex[j] - lf[j];
                    unsigned w4[4];
#pragma unroll
                    for (int i = 0; i < 4; i++)
                        w4[i] = __byte_perm((((q0 >> (8 * i)) & 255) + 192 + st[j][i] - max(st[j][i], 32u)) * 0x801 + 0x400, min(st[j][i], 32u), 0x5410);
                    if (j == 0 || ht < 64)
                        sts128(sb + OFF_CNT2 + (j ? G1 : G0) * 512 + lane * 16, make_uint4(sw ? w4[1] : w4[0], sw ? w4[0] : w4[1], sw ? w4[3] : w4[2], sw ? w4[2] : w4[3]));
                }
                if (longg && lane == 0) asm volatile("red.shared.or.b32 [%0],%1;" ::"r"(sb + OFF_MISC + 8), "r"(longg) : "memory");
                asm volatile("{.reg .pred p; setp.ne.u32 p,%1,0; bar.red.popc.u32 %0,1,96,p;}" : "=r"(rare) : "r"(longg) : "memory");
                if (ht == 64) mbar_arrive(bar_p);
#pragma unroll
                for (int j = 0; j < 2; j++) {
                    const unsigned wa = __shfl_sync(~0u, word[j], (g >> 1) * 8 + 2 * t), wb = __shfl_sync(~0u, word[j], (g >> 1) * 8 + 2 * t + 1);
                    const unsigned w2 = s2w[j];
                    const unsigned d128 = hmul2(dp[j], 0x43004300u);
                    const unsigned ha = sb + OFF_IMG + 4096 + (j ? G1 : G0) * 512 + lane * 16;
                    if (j == 0 || ht < 64) {
                        asm volatile("st.shared.v2.u32 [%0],{%1,%2};" ::"r"(ha), "r"(__byte_perm(wa, wb, (g & 1) ? 0x7362 : 0x5140)),
                                     "r"(__byte_perm(w2, w2, (g & 1) ? 0x3322 : 0x1100) + 0x1C201C20u - t * 0x08080808u) : "memory");
                        sts32(ha + 8, __byte_perm(d128, d128, lane >= 16 ? 0x1032 : 0x3210));
                    }
                }
            }
            if (__builtin_expect(!rare, 1)) {
                if (ht >= 32) place4(480 + ht);
            } else {
                place_slow(sc, ht, lds32(sb + OFF_MISC + 8) >> 8);
                nb_sync<1, 96>();
                for (longg &= 255; longg; longg &= longg - 1)
                    asm volatile("red.shared.or.b32 [%0],0x80000000;" ::"r"(sb + OFF_IMG + 4096 + (__ffs(longg) - 1) * 512 + lane * 16 + 12) : "memory");
            }
            if (__builtin_expect(late, 0)) tail_overflow(sc, late, ht);
            __syncwarp();
            STAMPT(576, 4);
            if (ht < 32) nb_sync<13, PLACE2 ? 352 : 608>(); else nb_arrive<13, PLACE2 ? 352 : 608>();
            STAMPT(544, 18);
        }
        if (ht < 32 && elect()) {
            if (rowcta) {
                fence_async_smem();
                for (int c = 0; c < 3; c++) bulk_s2g(sc->lists + (c * LSTR + b * 160), sb + OFF_IMG + c * 4096, 2560);
                asm volatile("cp.async.bulk.commit_group;" ::: "memory");
                const unsigned novf = lds32(sb + OFF_MISC), bad = lds32(sb + OFF_MISC + 20);
                if (__builtin_expect(novf | bad, 0)) {
                    sc->ovfn[b] = make_uint2(lds32(sb + OFF_MISC + 48), novf);
                    raise_flag(&sc->bar[4 * 64 + 1], lds32(sb + OFF_MISC + 48), (novf ? 1 : 0) | (bad ? 2 : 0));
                    __threadfence();
                }
                asm volatile("cp.async.bulk.wait_group 0;" ::: "memory");
                fence_async_gmem();
            }
            bar_arrive_relaxed(&sc->bar[4 * 64]);
            STAMPT(544, 19);
            sts32(sb + OFF_MISC + 28, bar_poll2(&sc->bar[4 * 64], lds32(sb + OFF_MISC + 48)));
            mbar_arrive(bar_c);
            STAMPT(544, 23);
        }
    } else {
        const bool one = elect();
        auto load_xl = [&](int i) {
            mbar_expect(bar_full + 8 * i, 32768 + 10240);
            tma_load2d(sb + OFF_T + i * 10240, &tm_x, i * 64, b * TILE, bar_full + 8 * i);
            tma_load3d(sb + OFF_S + i * 32768, &tm_wl, i * 64, bar_full + 8 * i);
        };
        auto load_m = [&](int i, int slot) {
            mbar_expect(bar_full + 32 + 8 * i, 32768);
            tma_load3d(sb + OFF_S + slot * 32768, &tm_m, i * 64, bar_full + 32 + 8 * i);
        };
        auto load_v = [&](int i, int slot) {
            mbar_expect(bar_full + 64 + 8 * i, 32768);
            tma_load3d(sb + OFF_S + slot * 32768, &tm_wv, i * 64, bar_full + 64 + 8 * i);
        };
        const char* hsl = (const char*)(sc->hs + slice * NN);
        auto fill = [&](int slot) { bulk_g2s(sb + OFF_S + slot * 32768, hsl + slot * 32768, slot == 4 ? NN * 16 - 4 * 32768 : 32768, bar_fill); };
        const unsigned t0 = clock();
        CLK0(512); STAMPT(512, 54);
        if (one) {
            for (int i = 0; i < 2; i++) mbar_init(bar_full + 8 * i, 1);
            asm volatile("fence.mbarrier_init.release.cluster;" ::: "memory");
            while ((unsigned)clock() - t0 < XD0) {}
            if (rowcta) load_xl(0);
            STAMPT(512, 41);
            for (int i = 2; i < 12; i++) mbar_init(bar_full + 8 * i, 1);
            mbar_init(bar_go, 1); mbar_init(bar_p, 1);
            for (int i = 0; i < 5; i++) mbar_init(bar_g + 8 * i, 16);
            for (int i = 0; i < 4; i++) mbar_init(bar_fill + 8 * i, 1);
            for (int i = 0; i < 10; i++) mbar_init(bar_rd + 8 * i, i < 9 ? 16 : g1 - g0 - 144);
            asm volatile("fence.mbarrier_init.release.cluster;" ::: "memory");
            if ((unsigned)__cvta_generic_to_shared(smem_raw) != sb) __trap();
            mbar_expect(bar_fill, NN * 16);
        }
        __syncwarp();
        nb_arrive<3, 544>();
        nb_arrive<13, 160>();
        if (one && rowcta) {
            while ((unsigned)clock() - t0 < XD1) {}
            load_xl(1);
            STAMPT(512, 40);
        }
        __syncwarp();
        nb_sync<15, 64>();
        if (rowcta) {
            if (one) {
                if (XD2) { while ((unsigned)clock() - t0 < XD2 + 1) {} } else mbar_wait(bar_full);
                load_xl(2);
                STAMPT(512, 52);
                mbar_wait(bar_full + (XD2 ? 0 : 8)); load_xl(3);
                STAMPT(512, 53);
                asm volatile("cp.async.bulk.prefetch.L2.global [%0],%1;" ::"l"(wv + b * 64), "r"(b == NT - 1 ? 4096 : 1024) : "memory");
                asm volatile("prefetch.tensormap [%0];" ::"l"(&tm_m) : "memory");
                asm volatile("prefetch.tensormap [%0];" ::"l"(&tm_wv) : "memory");
                bar_poll(sc, 3);
                STAMPT(512, 48);
                fence_async_gmem();
            }
            WAIT_EV(5); if (one) { load_m(0, 0); load_m(1, 1); mbar_arrive(bar_go); }
            WAIT_EV(6); if (one) load_m(2, 3);
            STAMPT(512, 45); CLK1(512, 55);
            WAIT_EV(7); if (one) load_m(3, 0);
            WAIT_EV(12); if (one) bar_arrive(&sc->bar[2 * 64]);
            STAMPT(512, 24);
            WAIT_EV(14); if (one) { fence_async_smem(); load_v(0, 4); load_v(1, 2); }
            STAMPT(512, 56); CLK1(512, 57);
            WAIT_EV(15);
            if (one) {
                fence_async_smem();
                load_v(2, 1); load_v(3, 3);
                bar_poll(sc, 2);
                fence_async_gmem();
            }
            STAMPT(512, 25);
            WAIT_EV(2); if (one) { fill(0); if (VRS == 1) fill(4); }
            if (one) { asm volatile("prefetch.tensormap [%0];" ::"l"(&tm_ot) : "memory"); asm volatile("prefetch.tensormap [%0];" ::"l"(&tm_o256) : "memory"); }
            WAIT_EV(4); if (one) { fill(2); if (VRS == 3) { fence_async_smem(); fill(4); } }
            WAIT_EV(5); if (one) fill(1);
            WAIT_EV(6); if (one) fill(3);
            if (VRS < 1) { WAIT_EV(7); if (one) fill(4); }
            STAMPT(512, 58); CLK1(512, 59);
            mbar_wait(bar_c);
            const bool redo = lds32(sb + OFF_MISC + 28) & 2;
            WAIT_EV(12);
            if (__builtin_expect(redo, 0)) WAIT_EV(14);
            if (one) {
                fence_async_smem();
#pragma unroll
                for (int kb = 0; kb < 4; kb++)
                    asm volatile("cp.async.bulk.tensor.2d.global.shared::cta.bulk_group [%0,{%2,%3}],[%1];"
                                 ::"l"(&tm_ot), "r"(sb + OFF_T + kb * 10240), "r"(kb * 64), "r"(b * TILE) : "memory");
                asm volatile("cp.async.bulk.commit_group;" ::: "memory");
                STAMPT(512, 15);
                asm volatile("cp.async.bulk.wait_group 0;" ::: "memory");
                fence_async_gmem();
            }
        } else {
            if (one) {
                bar_arrive(&sc->bar[2 * 64]);
                bar_poll(sc, 2);
                fence_async_gmem(); fence_async_smem();
                for (int i = 0; i < 5; i++) fill(i);
            }
        }
        if (one) {
            bar_arrive_relaxed(&sc->bar[1 * 64]);
            mbar_arrive(bar_t);
            STAMPT(512, 26);
            bar_poll(sc, 1);
            fence_async_gmem();
            STAMPT(512, 27);
            unsigned tn = clock();
#pragma unroll 1
            for (int r = 0; r < 9; r++) {
                if (PSLEEP && r) __nanosleep(PSLEEP);
                if (MSLEEP) mbar_sleep(bar_rd + 8 * r); else mbar_wait(bar_rd + 8 * r);
                fence_async_smem();
                while ((int)(clock() - tn) < 0) {}
                tn = clock() + PACE;
                tma_reduce(&tm_o256, sb + OFF_STG + r * 4096, slice * 8, (g0 + 16 * r) * 16);
            }
            if (MSLEEP) mbar_sleep(bar_rd + 72); else mbar_wait(bar_rd + 72);
            STAMPT(512, 14);
            fence_async_smem();
            tma_reduce(range == 3 ? &tm_o256 : &tm_o192, sb + OFF_STG + 9 * 4096, slice * 8, (g0 + 144) * 16);
            asm volatile("cp.async.bulk.commit_group;" ::: "memory");
            asm volatile("cp.async.bulk.wait_group.read 0;" ::: "memory");
            STAMPT(512, 13);
        }
    }
    } else {
    if (tid < 32) {
        unsigned bad = 0;
        uint4 xd[3];
#pragma unroll
        for (int k = 0; k < 3; k++) xd[k] = ldg_na((const uint4*)edst + min(b * TILE + k * 32 + lane, NN - 1u));
#pragma unroll
        for (int k = 0; k < 3; k++) { const unsigned n = min(b * TILE + k * 32 + lane, NN - 1u); bad |= (xd[k].x ^ n) | (xd[k].y ^ n) | (xd[k].z ^ n) | (xd[k].w ^ n); }
        bad = __any_sync(~0u, bad);
        if (lane == 0) sts32(sb + OFF_MISC + 20, bad);
        __syncwarp();
        nb_arrive<13, 160>();
    } else if (tid < 64) {
        const uint4* ep = (const uint4*)esrc + (min(b, NT - 1u) * TILE + lane);
        cp16(sb + OFF_EIDX + lane * 16, ep); cp16(sb + OFF_EIDX + 512 + lane * 16, ep + 32);
        if (lane < 16) cp16(sb + OFF_EIDX + 1024 + lane * 16, ep + 64);
        if (lane < 10) cp16(sb + OFF_DIS + lane * 16, dis + (min(b, NT - 1u) * 10 + lane));
        cp_commit();
        cp_wait<0>();
        nb_arrive<13, 160>();
    } else if (tid >= 192) {
        if (rowcta) {
            const unsigned bt = tid - 192;
            if (ED0) { const unsigned t0 = clock(); while ((unsigned)clock() - t0 < ED0 + 1) {} }
            const uint4 ed = ldg_na(dst4 + (b * 320 + bt)), es = ldg_na(src4 + (b * 320 + bt));
            const unsigned pad = (PADBIN + 4 * ((bt & 3) + ((b * 4) & 28))) << 16;
#pragma unroll
            for (int k = 0; k < 4; k++) if ((k & 1) == 0 || bt < 180) sts128(sb + OFF_MAIL + (k >> 1) * 9216 + (bt + (k & 1) * 320) * 16, make_uint4(pad, pad, pad, pad));
            if (bt < (512 + 2688) / 16) sts128(sb + OFF_CNT1 + bt * 16, make_uint4(0, 0, 0, 0));
            if (bt == 319) sts128(sb + OFF_MISC, make_uint4(0, 0, 0, 0));
            unsigned z;
            asm volatile("{.reg .pred p; setp.eq.u32 p,%1,0xFFFFFFFF; bar.red.popc.u32 %0,4,320,p;}" : "=r"(z) : "r"(bt) : "memory");
            const unsigned dd[4] = {ed.x + z, ed.y + z, ed.z + z, ed.w + z}, ss[4] = {es.x + z, es.y + z, es.z + z, es.w + z};
            unsigned rk[4], ow[4];
#pragma unroll
            for (int i = 0; i < 4; i++) { ow[i] = dd[i] / TILE; rk[i] = atoms_inc(sb + OFF_CNT1 + ow[i] * 4); }
#pragma unroll
            for (int i = 0; i < 4; i++) {
                const unsigned dl = dd[i] - ow[i] * TILE;
                const unsigned e = bitsel(ss[i] << 20, bitsel(dl << 21, dl << 18, 0xFF800000u), 0x00700000u) + ss[i];
                asm volatile("{.reg .pred p; setp.lt.u32 p,%2,%3; @p st.shared.u32 [%0],%1;}" ::"r"(sb + OFF_MAIL + ow[i] * 64 + rk[i] * 4 + (rk[i] >> 4) * (9216 - 64)), "r"(e), "r"(rk[i]), "n"(CELL) : "memory");
            }
            if (__builtin_expect((rk[0] | rk[1] | rk[2] | rk[3]) >= CELL, 0)) {
#pragma unroll
                for (int i = 0; i < 4; i++) if (rk[i] >= CELL) push_overflow(sc, dd[i], ss[i]);
            }
        }
        STAMPT(416, 44);
        nb_arrive<2, 352>();
    } else {
        const unsigned fw = b >> 3, hq = b & 7, q = (tid >> 5) - 2;
        const unsigned ma = sb + OFF_S + 4 * 32768 + 8192 + q * 6144;
        {
            const unsigned r = lane >> 3, da = ma + r * 128 + (((lane ^ r) & 7) << 4);
            const uint4* pa = wq + ((16 * fw + r) * 32 + q * 8 + (lane & 7));
            const uint4* pb = wk + ((32 * hq + r) * 32 + q * 8 + (lane & 7));
#pragma unroll
            for (int u = 0; u < 12; u++) cp16((da ^ ((u & 1) << 6)) + u * 512, u < 4 ? pa + u * 128 : pb + (u - 4) * 128);
            cp_commit();
        }
        const unsigned aa = ma + (lane & 15) * 128 + ((((lane >> 4) ^ lane) & 7) << 4);
        const unsigned br = 4 * ((lane & 7) >> 1) + 2 * (lane >> 4) + (lane & 1);
        const unsigned ba = ma + 2048 + br * 128 + (((((lane >> 3) & 1) ^ br) & 7) << 4);
        float c[4][4];
#pragma unroll
        for (int u = 0; u < 4; u++) c[u][0] = c[u][1] = c[u][2] = c[u][3] = 0.f;
        STAMPT(64, 38);
        cp_wait<0>();
        __syncwarp();
        STAMPT(64, 39);
#pragma unroll
        for (int k = 0; k < 4; k++) {
            const uint4 a = ldsm4(aa ^ (k << 5)), b0 = ldsm4(ba ^ (k << 5)), b1 = ldsm4((ba ^ (k << 5)) + 2048);
            mma16816(c[0], a.x, a.y, a.z, a.w, b0.x, b0.y); mma16816(c[1], a.x, a.y, a.z, a.w, b0.z, b0.w);
            mma16816(c[2], a.x, a.y, a.z, a.w, b1.x, b1.y); mma16816(c[3], a.x, a.y, a.z, a.w, b1.z, b1.w);
        }
        const unsigned ra = sb + OFF_S + 4 * 32768 + lane * 16;
#pragma unroll
        for (int i = 0; i < 4; i++)
            sts128(ra + q * 2048 + i * 512, make_uint4(__float_as_uint(c[2 * (i & 1)][2 * (i >> 1)]), __float_as_uint(c[2 * (i & 1)][2 * (i >> 1) + 1]),
                                                       __float_as_uint(c[2 * (i & 1) + 1][2 * (i >> 1)]), __float_as_uint(c[2 * (i & 1) + 1][2 * (i >> 1) + 1])));
        STAMPT(64, 42);
        nb_sync<8, 128>();
        float m[4] = {0, 0, 0, 0};
#pragma unroll
        for (int i = 0; i < 4; i++) {
            const uint4 u = lds128(ra + i * 2048 + q * 512);
            m[0] += __uint_as_float(u.x); m[1] += __uint_as_float(u.y); m[2] += __uint_as_float(u.z); m[3] += __uint_as_float(u.w);
        }
        const float k = 0.0625f * 1.4426950408889634f;
        asm volatile("st.shared.v2.u32 [%0],{%1,%2};" ::"r"(sb + OFF_MAIL + 8064 + (8 * (q >> 1) + g) * 64 + (q & 1) * 32 + t * 8),
                     "r"(pack2(m[0] * k, m[1] * k)), "r"(pack2(m[2] * k, m[3] * k)) : "memory");
        fence_async_smem();
        STAMPT(64, 43);
        nb_arrive<14, 192>();
    }
    asm volatile("setmaxnreg.inc.sync.aligned.u32 %0;" ::"n"(REG_W));
    const int w = __shfl_sync(~0u, tid >> 5, 0), wg = w >> 2;
    const int grp0 = g0 + w;
    const uint4* lp = sc->lists + (grp0 * 32 + lane);
    uint4 L0, L1;
    nb_sync<3, 544>();

    if (__builtin_expect(rowcta, 1)) {
        const unsigned descA = 0x10000u + (SB0 + OFF_S) / 16 + wg * 512;
        const unsigned greg = sb + OFF_S + w * 2048 + lane * 16;
        float d[40];
        unsigned pk[20];
        unsigned* hp = (unsigned*)(sc->hs + (2 * w * NN + b * TILE)) + lane;
        auto mma_k = [&](int Q, int slot, int st, int k0, int k1) {
            if (st < 0) wg_fence();
#pragma unroll
            for (int k = k0; k < k1; k++) {
                if (st >= 0) wg_fence();
                wg80(d, descA + slot * 2048 + k * 128, 0x10000u + (SB0 + OFF_T) / 16 + (Q & 3) * 640 + k * 2, st == -2 ? k != 0 : st == -3 || ((Q & 3) | k) != 0);
                if (st >= 0) {
#pragma unroll
                    for (int j = st + k; j < st + k + 1; j++)
                        if (j < 20) asm volatile("st.global.u32 [%0],%1;" ::"l"(hp + (j >> 1) * 32 + (j & 1) * (NN * 4)), "r"(pk[j]) : "memory");
                }
            }
            wg_commit();
        };
        auto mma_q = [&](int Q, int slot, int st) { mma_k(Q, slot, st, 0, 4); };
        auto mma_head = [&](int Q, int slot, int st) { mma_k(Q, slot, st, 0, KH); wg_wait<1>(); };
        auto mma_tail = [&](int Q, int slot, int st) { mma_k(Q, slot, st, KH, 4); };
        const uint4* xl = x + lane;
        auto eidx = [&](int i) { return lds128(sb + OFF_EIDX + (w * 5 + i) * 16); };
        auto gather = [&](const uint4& ix, int slot) {
            if (GT) {
                if (elect()) {
                    const unsigned bar = bar_g + 8 * slot, dst = sb + OFF_S + slot * 32768 + w * 2048;
                    if (slot == 4) fence_async_smem();
                    mbar_expect(bar, 2048);
                    bulk_g2s(dst, x + ix.x * 32u, 512, bar); bulk_g2s(dst + 512, x + ix.y * 32u, 512, bar);
                    bulk_g2s(dst + 1024, x + ix.z * 32u, 512, bar); bulk_g2s(dst + 1536, x + ix.w * 32u, 512, bar);
                }
                __syncwarp();
                return;
            }
            cp16(greg + slot * 32768, xl + ix.x * 32u); cp16(greg + slot * 32768 + 512, xl + ix.y * 32u);
            cp16(greg + slot * 32768 + 1024, xl + ix.z * 32u); cp16(greg + slot * 32768 + 1536, xl + ix.w * 32u);
            cp_commit();
        };
        const uint4 ix0 = eidx(0), ix1 = eidx(1), ix2 = eidx(2), ix3 = eidx(3), ix4 = eidx(4);
        uint4 gv[5][4];
        const unsigned gld = sb + OFF_S + w * 2048 + ((lane >> 3) & 1) * 512 + (lane >> 4) * 128 + (lane & 7) * 16;
        auto to_regs = [&](int i, int slot) {
            if (GT) mbar_wait(bar_g + 8 * slot); else __syncwarp();
#pragma unroll
            for (int j = 0; j < 4; j++) gv[i][j] = ldsm4(gld + slot * 32768 + (j & 1) * 256 + (j >> 1) * 1024);
        };
        unsigned ds[10];
#pragma unroll
        for (int j = 0; j < 10; j++) ds[j] = lds32(sb + OFF_DIS + (4 * j + t) * 4);
        STAMPT(288, 2);
        mbar_wait(bar_full);
        STAMPT(288, 3);
        mma_q(0, 0, -1);
        mbar_wait(bar_full + 8);
        STAMPT(288, 50);
        mma_q(1, 1, -1);
        mbar_wait(bar_full + 16);
        STAMPT(288, 51);
        mma_head(2, 2, -1);
        EV(5);
        mma_tail(2, 2, -1);
        mbar_wait(bar_full + 24);
        STAMP(5);
        mma_q(3, 3, -1);
        mbar_wait(bar_go);
        gather(ix0, 4);
        wg_wait<0>();
        EV(6);
        STAMP(6);
#pragma unroll
        for (int j = 0; j < 20; j++) pk[j] = movm(hmul2(pack2(d[2 * j], d[2 * j + 1]), ds[j >> 1]));
#pragma unroll
        for (int j = 0; j < STPRE; j++) asm volatile("st.global.u32 [%0],%1;" ::"l"(hp + (j >> 1) * 32 + (j & 1) * (NN * 4)), "r"(pk[j]) : "memory");
        STAMP(7);
        if (G1POS < 2) nb_sync_id(8 + wg, 128);
        if (G1POS == 0) gather(ix1, 2);
        mbar_wait(bar_full + 32);
        if (G1POS == 1) { if (G0POS == 2) gather(ix0, 4); gather(ix1, 2); }
        STAMP(21);
        if (G1POS == 2) {
            mma_k(4, 0, STPRE, 0, 1);
            if (G0POS == 2) gather(ix0, 4);
            nb_sync_id(8 + wg, 128);
            gather(ix1, 2);
            mma_k(4, 0, STPRE, 1, 4);
        } else {
            mma_q(4, 0, STPRE);
        }
        STAMP(28);
        mbar_wait(bar_full + 40);
        mma_head(5, 1, STPRE + 4);
        EV(7);
        mma_tail(5, 1, STPRE + 4);
        STAMP(29);
        mbar_wait(bar_full + 48);
        STAMP(30);
        mma_head(6, 3, STPRE + 8);
        nb_sync_id(8 + wg, 128);
        gather(ix2, 1);
        mma_tail(6, 3, STPRE + 8);
        STAMP(31);
        mbar_wait(bar_full + 56);
        STAMP(32);
        mma_head(7, 0, STPRE + 12);
        nb_sync_id(8 + wg, 128);
        gather(ix3, 3);
        mma_tail(7, 0, STPRE + 12);
        EV(12);
        wg_wait<0>();
        STAMP(20);
        pack_acc(pk, d);
        nb_sync<0, 512>();
        acc_to_tile(pk, w, lane);
        gather(ix4, 0);
        if (!GT) cp_wait<3>();
        to_regs(0, 4);
        nb_sync<0, 512>();
        STAMP(8);
        uint4 vf[4];
        auto load_vf = [&]() {
            const unsigned va = sb + OFF_S + 4 * 32768 + wg * 8192 + ((lane & 7) + (lane >> 4) * 8) * 128 + (((2 * (w & 3) + ((lane >> 3) & 1)) ^ (lane & 7)) << 4);
#pragma unroll
            for (int k = 0; k < 4; k++) vf[k] = ldsm4t(va + k * 2048);
        };
        {
            const unsigned delta = t ^ (g >> 1), alsm = sb + OFF_ALPHA + w * 128;
            const bool par = g & 1;
            unsigned ta[5];
#pragma unroll
            for (int i = 0; i < 5; i++) ta[i] = tile_addr(w * 5 + i, lane);
            float v[4], u[4];
            if (STAG == 2 && wg >= 2) nb_sync<9, 512>();
            if (STAG == 4 && wg >= 1) nb_sync_id(8 + wg, 256);
            to_regs(1, 2);
            EV(14);
            attn_scores(v, true, par, gv[0], ta[0]);
            attn_scores(v, delta == 1, par, gv[1], ta[1] ^ 32);
            if (!GT) cp_wait<2>();
            to_regs(2, 1);
            if (STAG == 2 && STAGAT == 2 && wg < 2) nb_arrive<9, 512>();
            attn_scores(v, delta == 2, par, gv[2], ta[2] ^ 64);
            STAMP(33);
            if (!GT) cp_wait<1>();
            to_regs(3, 3);
            EV(15);
            if (STAG == 2 && STAGAT == 3 && wg < 2) nb_arrive<9, 512>();
            if (STAG == 4 && wg < 3) nb_arrive_id(9 + wg, 256);
            STAMP(34);
            attn_scores(v, delta == 3, par, gv[3], ta[3] ^ 96);
            if (!GT) cp_wait<0>();
            to_regs(4, 0);
            if (STAG == 2 && STAGAT == 4 && wg < 2) nb_arrive<9, 512>();
            STAMP(35);
            attn_scores(u, true, par, gv[4], ta[4]);
            attn_softmax(v, u, lane, alsm + ((lane & 4) + delta) * 16 + (lane >> 3) * 4);
            STAMP(49);
            if (VRS == 1) mbar_wait(bar_full + 64);
            uint4 al = lds128(alsm);
#pragma unroll
            for (int i = 0; i < 5; i++) {
                const uint4 a = al;
                if (i < 4) al = lds128(alsm + (i + 1) * 16);
                attn_mix(gv[i], a, ta[i]);
                if (i == PLACE_AT && (!PLACE2 || wg < 2)) {
                    mbar_wait(bar_p);
                    if (__builtin_expect(lds32(sb + OFF_MISC + 8) == 0, 1)) {
#pragma unroll 1
                        for (int k = 0; k <= PLACE2; k++) place4(tid + k * 256);
                    }
                    nb_arrive<13, PLACE2 ? 352 : 608>();
                }
                if (i == 1 && VRS == 1) load_vf();
            }
        }
        STAMP(36);
        mbar_wait(bar_full + 64); mbar_wait(bar_full + 72); mbar_wait(bar_full + 80);
        fence_async_smem();
        STAMP(22); STAMP2(37);
        EV(2);
        nb_sync<0, 512>();
        mma_k(9, 2, -2, 0, VK);
        if (VRS == 3) load_vf();
        if (VK < 4) mma_k(9, 2, -1, VK, 4);
        mma_head(10, 1, -1);
        EV(4);
        mma_tail(10, 1, -1);
        mbar_wait(bar_full + 88);
        mma_head(11, 3, -1);
        EV(5);
        mma_tail(11, 3, -1);
        if (VRS == 0) {
            mma_k(8, 4, -3, 0, KH); wg_wait<1>();
            EV(6);
            mma_tail(8, 4, -1);
        } else {
            wg_fence();
            wg80r(d, vf[0], 0x10000u + (SB0 + OFF_T) / 16);
            wg_commit();
            wg_wait<1>();
            EV(6);
            wg_fence();
#pragma unroll
            for (int k = 1; k < 4; k++) wg80r(d, vf[k], 0x10000u + (SB0 + OFF_T) / 16 + k * 2);
            wg_commit();
        }
        if (LPOS == 0) { mbar_wait(bar_c); L1 = ldg_na(lp); L0 = ldg_na(lp + LSTR); __syncwarp(); }
        wg_wait<0>();
        if (VRS < 1) EV(7);
        STAMP(9);
        pack_acc(pk, d);
        nb_sync<0, 512>();
        STAMP(10);
        acc_to_tile(pk, w, lane);
        EV(12);
        if (LPOS == 1) { mbar_wait(bar_c); L1 = ldg_na(lp); L0 = ldg_na(lp + LSTR); }
        if (__builtin_expect(lds32(sb + OFF_MISC + 28) & 2, 0)) {
            nb_sync<0, 512>();
            for (int i = 0; i < 5; i++) sts128(tile_addr(w * 5 + i, lane), attn_generic(b * TILE + w * 5 + i, x, esrc, edst, wq, wk, wv));
            EV(14);
        }
    } else {
        mbar_wait(bar_c);
        L1 = ldg_na(lp); L0 = ldg_na(lp + LSTR);
    }

    const unsigned flags = lds32(sb + OFF_MISC + 28);
    const bool anyovf = flags & 1;
    const unsigned zero = flags >> 8;
    const unsigned c64 = 0x64646464u + zero;
    if (lane < 8) sts128(sb + OFF_S + NN * 16 + lane * 16, make_uint4(0, 0, 0, 0));
    const int more = anyovf ? 0x7FFFFFFF : NN << 16;
    const float zmask = (lane >= 28) ? 0.f : -1.f;
    unsigned stg = sb + OFF_STG + w * 256 + (((lane & 7) * 2 + ((lane >> 3) & 1)) ^ ((lane >> 2) & 1)) * 16;
    unsigned rdb = bar_rd, rde = bar_rd + 48;
    const unsigned rdl = bar_rd + 8 * ((g1 - grp0 - 1) >> 4);
    __syncwarp();
    mbar_wait(bar_fill);
    STAMP(11);
    CLK0(64);
    unsigned ad[9], sA, sB, tA, tB, mx;
    float dA, dB;
    bool p9;
    uint4 v[9], a0, a1;
    auto head = [&](unsigned last) {
        ad[0] = row_lo(L1.x); ad[1] = row_hi(L1.x); ad[2] = row_lo(L1.y); ad[3] = row_hi(L1.y);
        ad[4] = row_lo(L1.z); ad[5] = row_hi(L1.z); ad[6] = row_lo(L1.w); ad[7] = row_hi(L1.w); ad[8] = row_lo(L0.w);
        asm volatile("prmt.b32 %0,%2,%3,0x4140;\n prmt.b32 %1,%2,%3,0x4342;" : "=r"(sA), "=r"(sB) : "r"(L0.x), "r"(c64));
        asm volatile("prmt.b32 %0,%2,%3,0x4140;\n prmt.b32 %1,%2,%3,0x4342;" : "=r"(tA), "=r"(tB) : "r"(L0.y), "r"(c64));
        asm volatile("mov.b32 %0,%1;" : "=r"(mx) : "r"(L0.w));
        dA = blo_v(L0.z); dB = bhi_v(L0.z);
        asm volatile("{.reg .pred p; setp.lt.u32 p,%9,%10;\n @p ld.global.L1::no_allocate.v4.u32 {%0,%1,%2,%3},[%8+%11];\n @p ld.global.L1::no_allocate.v4.u32 {%4,%5,%6,%7},[%8+%12];}"
                     : "=r"(L1.x), "=r"(L1.y), "=r"(L1.z), "=r"(L1.w), "=r"(L0.x), "=r"(L0.y), "=r"(L0.z), "=r"(L0.w)
                     : "l"(lp), "r"(rdb), "r"(last), "n"(16 * 32 * 16), "n"((16 * 32 + LSTR) * 16) : "memory");
        p9 = __any_sync(~0u, (int)mx < more);
#pragma unroll
        for (int s = 0; s < LA; s++) v[s] = ldsm4t(sb + OFF_S + ad[s]);
        a0 = p3_sel(0, sA, sB); a1 = p3_sel(1, sA, sB);
    };
#pragma unroll 1
    for (int part = 0; part < 2; part++) {
#pragma unroll 1
        do {
            head(rdl);
            sched_fence(zero);
            float acc0[4] = {0, 0, 0, 0}, acc1[4] = {0, 0, 0, 0};
#pragma unroll
            for (int s = 0; s < 9; s++) {
                uint4 n0, n1;
                if (s < 8) n0 = p3_sel(2 * s + 2, s < 7 ? sA : tA, s < 7 ? sB : tB);
                mma16816(acc0, a0.x, a0.y, a0.z, a0.w, v[s].x, v[s].y);
                if (s + LA < 9) v[s + LA] = ldsm4t(sb + OFF_S + ad[s + LA]);
                if (s < 8) n1 = p3_sel(2 * s + 3, s < 7 ? sA : tA, s < 7 ? sB : tB);
                mma16816(acc1, a1.x, a1.y, a1.z, a1.w, v[s].z, v[s].w);
                a0 = n0; a1 = n1;
            }
            if (__builtin_expect(p9, 0)) {
                p3_step(acc0, acc1, row_hi(mx & 0x7FFFFFFFu), 16, tA, tB);
                if (__any_sync(~0u, (int)mx < 0)) {
                    const uint4 C2 = ldg_na(lp + 2 * LSTR);
                    p3_step(acc0, acc1, row_lo(C2.x), 24, tA, tB); p3_step(acc0, acc1, row_hi(C2.x), 32, tA, tB);
                    p3_step(acc0, acc1, row_lo(C2.y), 40, tA, tB); p3_step(acc0, acc1, row_hi(C2.y), 48, tA, tB);
                }
                if (anyovf) {
                    float4 e = p3_overflow(sc, grp0 + 2 * (rdb - bar_rd), sb + OFF_S);
                    float s0 = e.x + e.z, s1 = e.y + e.w;
                    for (int k = 4; k < 32; k <<= 1) {
                        float u0 = __shfl_down_sync(~0u, s0, k), u1 = __shfl_down_sync(~0u, s1, k);
                        if (lane + k < 32) { s0 += u0; s1 += u1; }
                    }
                    acc0[0] += s0; acc0[1] += s1; acc0[2] += s0 - e.x; acc0[3] += s1 - e.y;
                }
            }
            float c0 = acc0[0] + acc1[0], c1 = acc0[1] + acc1[1], c2 = acc0[2] + acc1[2], c3 = acc0[3] + acc1[3];
            float n0 = __shfl_down_sync(~0u, c0, 4), n1 = __shfl_down_sync(~0u, c1, 4);
            float o0 = c0 - c2, o1 = c1 - c3, o2 = fmaf(n0, zmask, c2), o3 = fmaf(n1, zmask, c3);
            asm volatile("stmatrix.sync.aligned.m8n8.x2.shared.b16 [%0],{%1,%2};" ::"r"(stg), "r"(pack2(o0 * dA, o1 * dA)), "r"(pack2(o2 * dB, o3 * dB)) : "memory");
            __syncwarp();
            asm volatile("{.reg .pred p; setp.eq.u32 p,%1,0; @p mbarrier.arrive.shared.b64 _,[%0];}" ::"r"(rdb), "r"(lane) : "memory");
            stg += 4096;
            rdb += 8;
            lp += 16 * 32;
        } while (rdb != rde);
        mbar_wait(bar_t);
        rde = rdl + 8;
    }
    STAMP(12);
    CLK1(64, 60); STAMPT(0, 61); STAMPT(352, 62); STAMPT(480, 63);
    }
}

typedef CUresult (*EncodeFn)(CUtensorMap*, CUtensorMapDataType, cuuint32_t, void*, const cuuint64_t*, const cuuint64_t*,
                             const cuuint32_t*, const cuuint32_t*, CUtensorMapInterleave, CUtensorMapSwizzle,
                             CUtensorMapL2promotion, CUtensorMapFloatOOBfill);

}

extern "C" void kernel_launch(void* const* d_in, const int* in_sizes, int n_in, void* d_out, int out_size) {
    (void)in_sizes; (void)n_in; (void)out_size;
    static EncodeFn enc = nullptr;
    static void* scratch = nullptr;
    if (!enc) {
        cudaGetSymbolAddress(&scratch, g_scratch);
        void* fn = nullptr;
        cudaDriverEntryPointQueryResult qr;
        cudaGetDriverEntryPoint("cuTensorMapEncodeTiled", &fn, cudaEnableDefault, &qr);
        enc = (EncodeFn)fn;
        cudaFuncSetAttribute(exphormer_kernel, cudaFuncAttributeMaxDynamicSharedMemorySize, SMEM_BYTES);
    }
    CUtensorMap tm_m, tm_ms, tm_mail, tm_x, tm_wl, tm_wv, tm_ot, tm_o256, tm_o192;
    auto mk = [&](CUtensorMap* tm, void* p, int rows, int bc, int br, CUtensorMapSwizzle sw, CUtensorMapL2promotion pr) {
        cuuint64_t gd[2] = {256, (cuuint64_t)rows}, gs[1] = {512};
        cuuint32_t es[2] = {1, 1}, bx[2] = {(cuuint32_t)bc, (cuuint32_t)br};
        enc(tm, CU_TENSOR_MAP_DATA_TYPE_BFLOAT16, 2, p, gd, gs, bx, es, CU_TENSOR_MAP_INTERLEAVE_NONE, sw, pr, CU_TENSOR_MAP_FLOAT_OOB_FILL_NONE);
    };
    for (int i = 0; i < 3; i++) {
        cuuint64_t gd[3] = {64, 256, 4}, gs[2] = {512, 128};
        cuuint32_t es[3] = {1, 1, 1}, bx[3] = {64, 64, 4};
        enc(i == 2 ? &tm_m : i ? &tm_wv : &tm_wl, CU_TENSOR_MAP_DATA_TYPE_BFLOAT16, 3, i == 2 ? scratch : d_in[i ? 9 : 6], gd, gs, bx, es, CU_TENSOR_MAP_INTERLEAVE_NONE,
            CU_TENSOR_MAP_SWIZZLE_128B, CU_TENSOR_MAP_L2_PROMOTION_L2_128B, CU_TENSOR_MAP_FLOAT_OOB_FILL_NONE);
    }
    {
        cuuint64_t gd[2] = {2048, NT}, gs[1] = {8192};
        cuuint32_t es[2] = {1, 1}, bx[2] = {16, NT};
        enc(&tm_mail, CU_TENSOR_MAP_DATA_TYPE_UINT32, 2, ((Scratch*)scratch)->mail, gd, gs, bx, es, CU_TENSOR_MAP_INTERLEAVE_NONE,
            CU_TENSOR_MAP_SWIZZLE_NONE, CU_TENSOR_MAP_L2_PROMOTION_NONE, CU_TENSOR_MAP_FLOAT_OOB_FILL_NONE);
    }
    mk(&tm_ms, scratch, 256, 32, 16, CU_TENSOR_MAP_SWIZZLE_NONE, CU_TENSOR_MAP_L2_PROMOTION_NONE);
    mk(&tm_x, d_in[0], NN, 64, TILE, CU_TENSOR_MAP_SWIZZLE_128B, CU_TENSOR_MAP_L2_PROMOTION_L2_128B);
    mk(&tm_ot, d_out, NN, 64, TILE, CU_TENSOR_MAP_SWIZZLE_128B, CU_TENSOR_MAP_L2_PROMOTION_NONE);
    mk(&tm_o256, d_out, NN, 8, 256, CU_TENSOR_MAP_SWIZZLE_NONE, CU_TENSOR_MAP_L2_PROMOTION_NONE);
    mk(&tm_o192, d_out, NN, 8, 192, CU_TENSOR_MAP_SWIZZLE_NONE, CU_TENSOR_MAP_L2_PROMOTION_NONE);
    exphormer_kernel<<<NCTA, 640, SMEM_BYTES>>>(
        (const uint4*)d_in[0], (const uint4*)d_in[2], (const uint4*)d_in[1], (const uint4*)d_in[7], (const uint4*)d_in[8], (const int*)d_in[3],
        (const int*)d_in[4], (Scratch*)scratch, (const uint4*)d_in[5], (const uint4*)d_in[9],
        tm_x, tm_wl, tm_wv, tm_m, tm_ms, tm_mail, tm_ot, tm_o256, tm_o192);
}
```
